```python
import torch

def _softmax(x, axis=-1):
    return torch.softmax(x, dim=axis)
def _gelu(x):
    return torch.nn.functional.gelu(x, approximate="tanh")
def _silu(x):
    return torch.nn.functional.silu(x)
def _sigmoid(x):
    return torch.sigmoid(x)
def _layernorm(x, axis=-1, eps=1e-5):
    m = x.mean(dim=axis, keepdim=True)
    v = x.var(dim=axis, keepdim=True, unbiased=False)
    return (x - m) / torch.sqrt(v + eps)
def _scatter_add(tgt, idx, src, axis=0):
    return tgt.clone().index_add_(axis, idx, src)
def _segment_sum(src, seg, n):
    out = torch.zeros((n,) + src.shape[1:], dtype=src.dtype)
    return out.index_add_(0, seg, src)
def _pad(x, pw):
    flat = tuple(v for pair in reversed(pw) for v in pair)
    return torch.nn.functional.pad(x, flat)

kernel_name = 'concat_heads__ssm_conv_h3__compressed_kv_cla__prompt'

def setup_inputs():

    _w = (lambda a: (lambda t: t.to(torch.bfloat16) if t.is_floating_point() else t)(torch.as_tensor(a)))
    def _A_setup():
        B, S, D = 1, 2048, 448
        ks = 4
        return {
            "q": _w((lambda *s: torch.randn(*s, dtype=torch.bfloat16) * 0.05)(B, S, D)),
            "k": _w((lambda *s: torch.randn(*s, dtype=torch.bfloat16) * 0.1)(B, S, D)),
            "v": _w((lambda *s: torch.randn(*s, dtype=torch.bfloat16) * 0.1)(B, S, D)),
            "shift_k": _w((lambda *s: torch.randn(*s, dtype=torch.bfloat16) * 0.1)(D, ks) * 0.5),
            "ssm_k": _w((lambda *s: torch.randn(*s, dtype=torch.bfloat16) * 0.1)(D, S) * (1.0 / S ** 0.5)),
            "ssm_D": _w((lambda *s: torch.randn(*s, dtype=torch.bfloat16) * 0.1)(D)),
        }
    _A_in = _A_setup()

    def _B_setup():
        B, H, Sq, Sk, D, M = 1, 16, 2048, 2048, 256, 448
        Dc = 4 * D
        return {
            "x": _w((lambda *s: torch.randn(*s, dtype=torch.bfloat16) * 3.2)(B, Sq, M)),
            "c_kv": _w((lambda *s: torch.randn(*s, dtype=torch.bfloat16) * 0.05)(B, Sk, Dc)),
            "w_q": _w((lambda *s: torch.randn(*s, dtype=torch.bfloat16) * 3.2)(M, H, D) * (M ** -0.5)),
            "w_uk": _w((lambda *s: torch.randn(*s, dtype=torch.bfloat16) * 3.2)(Dc, H, D) * (Dc ** -0.5)),
            "w_uv": _w((lambda *s: torch.randn(*s, dtype=torch.bfloat16) * 0.05)(Dc, H, D) * (Dc ** -0.5)),
            "w_o": _w((lambda *s: torch.randn(*s, dtype=torch.bfloat16) * 0.05)(H, D, M) * ((H * D) ** -0.5)),
        }
    _B_in = _B_setup()

    return {
        "A_q": _A_in["q"],
        "A_k": _A_in["k"],
        "A_v": _A_in["v"],
        "A_shift_k": _A_in["shift_k"],
        "A_ssm_k": _A_in["ssm_k"],
        "A_ssm_D": _A_in["ssm_D"],
        "B_x": _B_in["x"],
        "B_c_kv": _B_in["c_kv"],
        "B_w_q": _B_in["w_q"],
        "B_w_uk": _B_in["w_uk"],
        "B_w_uv": _B_in["w_uv"],
        "B_w_o": _B_in["w_o"],
    }

def reference(A_q, A_k, A_v, A_shift_k, A_ssm_k, A_ssm_D, B_x, B_c_kv, B_w_q, B_w_uk, B_w_uv, B_w_o):
    def _A_ref(q, k, v, shift_k, ssm_k, ssm_D):
        B, S, D = q.shape
        ks = shift_k.shape[-1]
        k_pad = _pad(k, ((0, 0), (ks - 1, 0), (0, 0)))
        k_shift = torch.zeros_like(k)
        for t in range(ks):
            k_shift = k_shift + k_pad[:, t:t + S, :] * shift_k[:, ks - 1 - t][None, None, :]
        kv = k_shift * v
        L = 2 * S
        kv_pad = _pad(kv, ((0, 0), (0, S), (0, 0)))
        kf_pad = _pad(ssm_k, ((0, 0), (0, S)))
        kv_f = (lambda x, axes=(-2,-1): torch.fft.rfft2(x.float(), dim=axes))(kv_pad[:, None, :, :], axes=(1, 2))
        kf_f = (lambda x, axes=(-2,-1): torch.fft.rfft2(x.float(), dim=axes))(kf_pad[:, None, :], axes=(1, 2))
        kf_f = (lambda x, *d: x.permute(*d))(kf_f, 1, 2, 0)
        y_f = kv_f * kf_f[None, :, :, :]
        y = (lambda x, s, axes=(-2,-1): torch.fft.irfft2(x, s=s, dim=axes).to(torch.bfloat16))(y_f, (1, L), axes=(1, 2))[:, 0, :S, :]
        y = y + kv * ssm_D[None, None, :]
        return q * y

    def _B_ref(x, c_kv, w_q, w_uk, w_uv, w_o):
        B, Sq, M = x.shape[0], x.shape[1], x.shape[2]
        Sk = c_kv.shape[1]
        H, D = w_q.shape[1], w_q.shape[2]
        q = torch.einsum("bqm,mhd->bhqd", x, w_q)
        k = torch.einsum("bkc,chd->bhkd", c_kv, w_uk)
        v = torch.einsum("bkc,chd->bhkd", c_kv, w_uv)
        scores = torch.einsum("bhqd,bhkd->bhqk", q, k) * (D ** -0.5)
        off = Sk - Sq
        qi = torch.arange(Sq)[:, None]
        kj = torch.arange(Sk)[None, :]
        cmask = kj <= (qi + off)
        scores = torch.where(cmask[None, None], scores, -1e9)
        p = _softmax(scores, axis=-1)
        ctx = torch.einsum("bhqk,bhkd->bhqd", p, v)
        return torch.einsum("bhqd,hdm->bqm", ctx, w_o)

    a = _A_ref(A_q, A_k, A_v, A_shift_k, A_ssm_k, A_ssm_D)
    b = _B_ref(B_x, B_c_kv, B_w_q, B_w_uk, B_w_uv, B_w_o)
    return torch.concatenate([a, b], axis=-1)
```

```cpp
#include <cuda_runtime.h>
#include <cuda_bf16.h>
#include <cuda.h>
#include <stdint.h>

namespace {

typedef __nv_bfloat16 bf16;

constexpr int SEQ  = 2048;
constexpr int DA   = 448;
constexpr int NH   = 16;
constexpr int HD   = 256;
constexpr int DM   = 448;
constexpr int DC   = 1024;
constexpr int OUTW = DA + DM;
constexpr int NMAIN = 128;
constexpr int NCONV = 4;
constexpr int NCTA  = NMAIN + NCONV;
constexpr int LOG_DONE = 8;
constexpr int NTHREADS = 384;
constexpr int D_SPARE = 320;

__device__ __align__(1024) bf16 g_kv[2ull * SEQ * NH * HD];
__device__ __align__(1024) bf16 g_ctx[(size_t)NMAIN * 128 * HD];
__device__ __align__(1024) bf16 g_part[(size_t)8 * SEQ * DM];
__device__ __align__(128) uint8_t g_xs[DA * SEQ * 2];
constexpr uint32_t HO_STRIDE = 4224;
__device__ __align__(128) uint8_t g_ho[DA * HO_STRIDE];
struct alignas(128) Flag { unsigned v; unsigned pad[31]; };
struct Flags {
  Flag kv_ready[NH];
  Flag ctx_ready[NMAIN * 2];
  Flag part_ready[16 * 2];
  Flag x_ready[7];
  Flag z_ready[7];
  Flag zero_ready[16];
  alignas(128) unsigned long long done;
};
__device__ Flags g_flags;
#define TS(i)
#define TSG(i)
#define GT(i)
#define PT(i)
#define WHICH_TS 0
#define PCLK(var)
#define PACC(acc, t0)
#define PDECL
#define PDUMP()

struct alignas(64) Params {
  CUtensorMap ckv;
  CUtensorMap wuk;
  CUtensorMap wuv;
  CUtensorMap x;
  CUtensorMap wq;
  CUtensorMap kv;
  CUtensorMap part;
  CUtensorMap ctx;
  CUtensorMap wo;
  const bf16 *a_q, *a_k, *a_v, *a_shift, *a_ssmk, *a_D;
  bf16* out;
};

constexpr uint32_t P1_STAGE = 49152;
constexpr uint32_t P1_STG   = 196608;
constexpr uint32_t SLOT     = 32768;
constexpr int      NSLOT    = 5;
constexpr uint32_t QREG     = 163840;
constexpr uint32_t BARS     = 229376;
constexpr uint32_t SMEM_BYTES = BARS + 512 + 1024;
enum : uint32_t {
  B_P1_FULL = 0, B_P1_EMPTY = 4, B_RG_FULL = 8, B_RG_EMPTY = 13, B_ST_FULL = 18, B_ST_EMPTY = 20,
  B_DONE = 22, B_PFREE = 23, B_S2_FULL = 28, B_S2_EMPTY = 32, B_QFREE = 36, B_CTXF = 38, B_PART = 40, B_DONE_SSM = 42, B_COUNT = 43
};

template <typename T> __device__ __forceinline__ T* at(const void* base, uint32_t off) {
  asm volatile("" : "+r"(off));
  return reinterpret_cast<T*>(const_cast<char*>(static_cast<const char*>(base)) + off);
}
__device__ __forceinline__ unsigned* flag_at(Flag* f, uint32_t i) { return at<unsigned>(f, i * (uint32_t)sizeof(Flag)); }
__device__ __forceinline__ uint32_t smem_u32(const void* p) { return (uint32_t)__cvta_generic_to_shared(p); }
__device__ __forceinline__ void mbar_init(uint32_t bar, uint32_t cnt) {
  asm volatile("mbarrier.init.shared::cta.b64 [%0], %1;" :: "r"(bar), "r"(cnt) : "memory");
}
__device__ __forceinline__ void mbar_expect_tx(uint32_t bar, uint32_t bytes) {
  asm volatile("mbarrier.arrive.expect_tx.shared::cta.b64 _, [%0], %1;" :: "r"(bar), "r"(bytes) : "memory");
}
__device__ __forceinline__ void mbar_arrive(uint32_t bar) {
  asm volatile("mbarrier.arrive.shared::cta.b64 _, [%0];" :: "r"(bar) : "memory");
}
__device__ __forceinline__ void mbar_arrive_n(uint32_t bar, uint32_t n) {
  asm volatile("mbarrier.arrive.shared::cta.b64 _, [%0], %1;" :: "r"(bar), "r"(n) : "memory");
}
__device__ __forceinline__ void mbar_arrive_remote(uint32_t bar, uint32_t cta) {
  asm volatile("{\n.reg .b32 ra;\nmapa.shared::cluster.u32 ra, %0, %1;\n"
               "mbarrier.arrive.shared::cluster.b64 _, [ra];\n}" :: "r"(bar), "r"(cta) : "memory");
}
__device__ __forceinline__ bool mbar_try(uint32_t bar, uint32_t parity) {
  uint32_t ok;
  asm volatile("{\n.reg .pred p;\nmbarrier.try_wait.parity.shared::cta.b64 p, [%1], %2;\nselp.u32 %0, 1, 0, p;\n}"
               : "=r"(ok) : "r"(bar), "r"(parity) : "memory");
  return ok;
}
constexpr uint32_t SPIN_LIMIT = 1u << 24;
__device__ __forceinline__ void mbar_wait(uint32_t bar, uint32_t parity) {
  if (mbar_try(bar, parity)) return;
  uint32_t n = 0;
  while (!mbar_try(bar, parity)) { if (++n > SPIN_LIMIT) __trap(); }
}
__device__ __forceinline__ unsigned load_epoch() {
  unsigned long long d; asm volatile("ld.relaxed.gpu.global.u64 %0, [%1];" : "=l"(d) : "l"(&g_flags.done) : "memory");
  return (unsigned)(d >> LOG_DONE);
}
__device__ __forceinline__ void flag_wait(const unsigned* f, unsigned count, unsigned epoch) {
  const unsigned target = (epoch + 1) * count;
  uint32_t n = 0;
  while (true) {
    unsigned v;
    asm volatile("ld.acquire.gpu.global.u32 %0, [%1];" : "=r"(v) : "l"(f) : "memory");
    if ((int)(v - target) >= 0) break;
    if (++n > SPIN_LIMIT) __trap();
    __nanosleep(20);
  }
}
__device__ __forceinline__ void flag_wait_slow(const unsigned* f, unsigned count, unsigned epoch) {
  const unsigned target = (epoch + 1) * count;
  uint32_t n = 0;
  while (true) {
    unsigned v;
    asm volatile("ld.acquire.gpu.global.u32 %0, [%1];" : "=r"(v) : "l"(f) : "memory");
    if ((int)(v - target) >= 0) break;
    if (++n > SPIN_LIMIT / 16) __trap();
    __nanosleep(1000);
  }
}
__device__ __forceinline__ void cta_done(unsigned long long n) { asm volatile("red.relaxed.gpu.global.add.u64 [%0], %1;" :: "l"(&g_flags.done), "l"(n) : "memory"); }
__device__ __forceinline__ void flag_wait_fast(const unsigned* f, unsigned count, unsigned epoch) {
  const unsigned target = (epoch + 1) * count;
  uint32_t n = 0;
  while (true) {
    unsigned v;
    asm volatile("ld.acquire.gpu.global.u32 %0, [%1];" : "=r"(v) : "l"(f) : "memory");
    if ((int)(v - target) >= 0) break;
    if (++n > SPIN_LIMIT) __trap();
  }
}
__device__ __forceinline__ void fence_async_all() { asm volatile("fence.proxy.async;" ::: "memory"); }
__device__ __forceinline__ void flag_signal(unsigned* f) {
  asm volatile("fence.acq_rel.gpu;" ::: "memory");
  asm volatile("red.relaxed.gpu.global.add.u32 [%0], 1;" :: "l"(f) : "memory");
}
__device__ __forceinline__ void flag_signal_after_bulk(unsigned* f) {
  asm volatile("red.relaxed.gpu.global.add.u32 [%0], 1;" :: "l"(f) : "memory");
}
__device__ __forceinline__ void fence_async_smem() { asm volatile("fence.proxy.async.shared::cta;" ::: "memory"); }
#define HINTS 0
constexpr uint64_t POL_NORMAL = 0x1000000000000000ull, POL_FIRST = 0x12F0000000000000ull;
__device__ __forceinline__ constexpr uint64_t pol(bool first) { return first ? POL_FIRST : POL_NORMAL; }
__device__ __forceinline__ void tma_ld2(uint32_t dst, const CUtensorMap* m, uint32_t bar, int c0, int c1, uint64_t pl = POL_NORMAL) {
  asm volatile("cp.async.bulk.tensor.2d.shared::cluster.global.mbarrier::complete_tx::bytes.L2::cache_hint [%0], [%1, {%3, %4}], [%2], %5;"
               :: "r"(dst), "l"(m), "r"(bar), "r"(c0), "r"(c1), "l"(pl) : "memory");
}
__device__ __forceinline__ void tma_ld3(uint32_t dst, const CUtensorMap* m, uint32_t bar, int c0, int c1, int c2, uint64_t pl = POL_NORMAL) {
  asm volatile("cp.async.bulk.tensor.3d.shared::cluster.global.mbarrier::complete_tx::bytes.L2::cache_hint [%0], [%1, {%3, %4, %5}], [%2], %6;"
               :: "r"(dst), "l"(m), "r"(bar), "r"(c0), "r"(c1), "r"(c2), "l"(pl) : "memory");
}
__device__ __forceinline__ void tma_ld3_mc(uint32_t dst, const CUtensorMap* m, uint32_t bar, int c0, int c1, int c2, uint64_t pl = POL_NORMAL) {
  asm volatile("cp.async.bulk.tensor.3d.shared::cluster.global.mbarrier::complete_tx::bytes.multicast::cluster.L2::cache_hint [%0], [%1, {%3, %4, %5}], [%2], %6, %7;"
               :: "r"(dst), "l"(m), "r"(bar), "r"(c0), "r"(c1), "r"(c2), "h"((uint16_t)3), "l"(pl) : "memory");
}
__device__ __forceinline__ void bulk_ld(uint32_t dst, const void* src, uint32_t bytes, uint32_t bar) {
  asm volatile("cp.async.bulk.shared::cluster.global.mbarrier::complete_tx::bytes [%0], [%1], %2, [%3];"
               :: "r"(dst), "l"(src), "r"(bytes), "r"(bar) : "memory");
}
__device__ __forceinline__ void tma_st3(const CUtensorMap* m, uint32_t src, int c0, int c1, int c2) {
  asm volatile("cp.async.bulk.tensor.3d.global.shared::cta.bulk_group.L2::cache_hint [%0, {%2, %3, %4}], [%1], %5;"
               :: "l"(m), "r"(src), "r"(c0), "r"(c1), "r"(c2), "l"(pol(HINTS & 1024)) : "memory");
}
__device__ __forceinline__ void tma_ld2_mc(uint32_t dst, const CUtensorMap* m, uint32_t bar, int c0, int c1, uint64_t pl = POL_NORMAL) {
  asm volatile("cp.async.bulk.tensor.2d.shared::cluster.global.mbarrier::complete_tx::bytes.multicast::cluster.L2::cache_hint [%0], [%1, {%3, %4}], [%2], %5, %6;"
               :: "r"(dst), "l"(m), "r"(bar), "r"(c0), "r"(c1), "h"((uint16_t)3), "l"(pl) : "memory");
}
__device__ __forceinline__ void tma_st2(const CUtensorMap* m, uint32_t src, int c0, int c1) {
  asm volatile("cp.async.bulk.tensor.2d.global.shared::cta.bulk_group [%0, {%2, %3}], [%1];"
               :: "l"(m), "r"(src), "r"(c0), "r"(c1) : "memory");
}
__device__ __forceinline__ void tma_red2(const CUtensorMap* m, uint32_t src, int c0, int c1) {
  asm volatile("cp.reduce.async.bulk.tensor.2d.global.shared::cta.add.bulk_group [%0, {%2, %3}], [%1];"
               :: "l"(m), "r"(src), "r"(c0), "r"(c1) : "memory");
}
__device__ __forceinline__ void bulk_commit() { asm volatile("cp.async.bulk.commit_group;" ::: "memory"); }
__device__ __forceinline__ void bulk_wait_read() { asm volatile("cp.async.bulk.wait_group.read 0;" ::: "memory"); }
__device__ __forceinline__ void bulk_wait_all() { asm volatile("cp.async.bulk.wait_group 0;" ::: "memory"); }
__device__ __forceinline__ void prefetch_map(const CUtensorMap* m) { asm volatile("prefetch.tensormap [%0];" :: "l"(m) : "memory"); }
__device__ __forceinline__ void wg_fence() { asm volatile("wgmma.fence.sync.aligned;" ::: "memory"); }
__device__ __forceinline__ void wg_commit() { asm volatile("wgmma.commit_group.sync.aligned;" ::: "memory"); }
template <int N> __device__ __forceinline__ void wg_wait() { asm volatile("wgmma.wait_group.sync.aligned %0;" :: "n"(N) : "memory"); }
template <int N> __device__ __forceinline__ void reg_fence(float (&d)[N]) {
#pragma unroll
  for (int i = 0; i < N; i++) asm volatile("" : "+f"(d[i]) :: "memory");
}
template <int N> __device__ __forceinline__ void reg_fence(uint32_t (&d)[N]) {
#pragma unroll
  for (int i = 0; i < N; i++) asm volatile("" : "+r"(d[i]) :: "memory");
}
__device__ __forceinline__ uint32_t fresh_tid() { uint32_t t; asm volatile("mov.u32 %0, %%tid.x;" : "=r"(t)); return t; }
__device__ __forceinline__ uint32_t lane_base16() {
  const uint32_t t = fresh_tid(), lane = t & 31, wq = (t >> 5) & 3;
  return (16 * wq + (lane & 7) + 8 * ((lane >> 3) & 1)) * 128 + (((lane >> 4) ^ (lane & 7)) << 4);
}
__device__ __forceinline__ void named_sync(int id, int n) { asm volatile("bar.sync %0, %1;" :: "r"(id), "r"(n) : "memory"); }
__device__ __forceinline__ void named_arrive(int id, int n) { asm volatile("bar.arrive %0, %1;" :: "r"(id), "r"(n) : "memory"); }
__device__ __forceinline__ uint32_t pack_bf16(float lo, float hi) {
  uint32_t r; asm("cvt.rn.bf16x2.f32 %0, %1, %2;" : "=r"(r) : "f"(hi), "f"(lo)); return r;
}
__device__ __forceinline__ float ex2(float x) { float y; asm("ex2.approx.ftz.f32 %0, %1;" : "=f"(y) : "f"(x)); return y; }
__device__ __forceinline__ void stsm4(uint32_t addr, uint32_t a, uint32_t b, uint32_t c, uint32_t d) {
  asm volatile("stmatrix.sync.aligned.m8n8.x4.shared.b16 [%0], {%1, %2, %3, %4};" :: "r"(addr), "r"(a), "r"(b), "r"(c), "r"(d) : "memory");
}
__device__ __forceinline__ uint64_t mk_desc(uint32_t addr, uint32_t lbo, uint32_t sbo) {
  return (uint64_t)(((addr & 0x3FFFF) >> 4) | ((lbo >> 4) << 16)) | ((uint64_t)((sbo >> 4) | (1u << 30)) << 32);
}
__device__ __forceinline__ uint64_t desc_k(uint32_t addr)  { return mk_desc(addr, 16, 1024); }
__device__ __forceinline__ uint64_t desc_mn(uint32_t addr) { return mk_desc(addr, 8192, 1024); }
__device__ __forceinline__ uint64_t desc_add(uint64_t d, uint32_t bytes) { return d + (bytes >> 4); }

__device__ __forceinline__ void wgmma_ss_n256_tb(float (&d)[128], uint64_t da, uint64_t db, int sd) {
  asm volatile("{\n.reg .pred p;\nsetp.ne.b32 p, %130, 0;\n"
    "wgmma.mma_async.sync.aligned.m64n256k16.f32.bf16.bf16 "
    "{%0, %1, %2, %3, %4, %5, %6, %7, %8, %9, %10, %11, %12, %13, %14, %15, "
    "%16, %17, %18, %19, %20, %21, %22, %23, %24, %25, %26, %27, %28, %29, %30, %31, "
    "%32, %33, %34, %35, %36, %37, %38, %39, %40, %41, %42, %43, %44, %45, %46, %47, "
    "%48, %49, %50, %51, %52, %53, %54, %55, %56, %57, %58, %59, %60, %61, %62, %63, "
    "%64, %65, %66, %67, %68, %69, %70, %71, %72, %73, %74, %75, %76, %77, %78, %79, "
    "%80, %81, %82, %83, %84, %85, %86, %87, %88, %89, %90, %91, %92, %93, %94, %95, "
    "%96, %97, %98, %99, %100, %101, %102, %103, %104, %105, %106, %107, %108, %109, %110, %111, "
    "%112, %113, %114, %115, %116, %117, %118, %119, %120, %121, %122, %123, %124, %125, %126, %127}, "
    "%128, %129, p, 1, 1, 0, 1;\n}"
    : "+f"(d[0]), "+f"(d[1]), "+f"(d[2]), "+f"(d[3]), "+f"(d[4]), "+f"(d[5]), "+f"(d[6]), "+f"(d[7]),
      "+f"(d[8]), "+f"(d[9]), "+f"(d[10]), "+f"(d[11]), "+f"(d[12]), "+f"(d[13]), "+f"(d[14]), "+f"(d[15]),
      "+f"(d[16]), "+f"(d[17]), "+f"(d[18]), "+f"(d[19]), "+f"(d[20]), "+f"(d[21]), "+f"(d[22]), "+f"(d[23]),
      "+f"(d[24]), "+f"(d[25]), "+f"(d[26]), "+f"(d[27]), "+f"(d[28]), "+f"(d[29]), "+f"(d[30]), "+f"(d[31]),
      "+f"(d[32]), "+f"(d[33]), "+f"(d[34]), "+f"(d[35]), "+f"(d[36]), "+f"(d[37]), "+f"(d[38]), "+f"(d[39]),
      "+f"(d[40]), "+f"(d[41]), "+f"(d[42]), "+f"(d[43]), "+f"(d[44]), "+f"(d[45]), "+f"(d[46]), "+f"(d[47]),
      "+f"(d[48]), "+f"(d[49]), "+f"(d[50]), "+f"(d[51]), "+f"(d[52]), "+f"(d[53]), "+f"(d[54]), "+f"(d[55]),
      "+f"(d[56]), "+f"(d[57]), "+f"(d[58]), "+f"(d[59]), "+f"(d[60]), "+f"(d[61]), "+f"(d[62]), "+f"(d[63]),
      "+f"(d[64]), "+f"(d[65]), "+f"(d[66]), "+f"(d[67]), "+f"(d[68]), "+f"(d[69]), "+f"(d[70]), "+f"(d[71]),
      "+f"(d[72]), "+f"(d[73]), "+f"(d[74]), "+f"(d[75]), "+f"(d[76]), "+f"(d[77]), "+f"(d[78]), "+f"(d[79]),
      "+f"(d[80]), "+f"(d[81]), "+f"(d[82]), "+f"(d[83]), "+f"(d[84]), "+f"(d[85]), "+f"(d[86]), "+f"(d[87]),
      "+f"(d[88]), "+f"(d[89]), "+f"(d[90]), "+f"(d[91]), "+f"(d[92]), "+f"(d[93]), "+f"(d[94]), "+f"(d[95]),
      "+f"(d[96]), "+f"(d[97]), "+f"(d[98]), "+f"(d[99]), "+f"(d[100]), "+f"(d[101]), "+f"(d[102]), "+f"(d[103]),
      "+f"(d[104]), "+f"(d[105]), "+f"(d[106]), "+f"(d[107]), "+f"(d[108]), "+f"(d[109]), "+f"(d[110]), "+f"(d[111]),
      "+f"(d[112]), "+f"(d[113]), "+f"(d[114]), "+f"(d[115]), "+f"(d[116]), "+f"(d[117]), "+f"(d[118]), "+f"(d[119]),
      "+f"(d[120]), "+f"(d[121]), "+f"(d[122]), "+f"(d[123]), "+f"(d[124]), "+f"(d[125]), "+f"(d[126]), "+f"(d[127])
    : "l"(da), "l"(db), "r"(sd));
}
__device__ __forceinline__ void wgmma_ss_n64(float (&d)[32], uint64_t da, uint64_t db, int sd) {
  asm volatile("{\n.reg .pred p;\nsetp.ne.b32 p, %34, 0;\n"
    "wgmma.mma_async.sync.aligned.m64n64k16.f32.bf16.bf16 "
    "{%0, %1, %2, %3, %4, %5, %6, %7, %8, %9, %10, %11, %12, %13, %14, %15, "
    "%16, %17, %18, %19, %20, %21, %22, %23, %24, %25, %26, %27, %28, %29, %30, %31}, "
    "%32, %33, p, 1, 1, 0, 0;\n}"
    : "+f"(d[0]), "+f"(d[1]), "+f"(d[2]), "+f"(d[3]), "+f"(d[4]), "+f"(d[5]), "+f"(d[6]), "+f"(d[7]),
      "+f"(d[8]), "+f"(d[9]), "+f"(d[10]), "+f"(d[11]), "+f"(d[12]), "+f"(d[13]), "+f"(d[14]), "+f"(d[15]),
      "+f"(d[16]), "+f"(d[17]), "+f"(d[18]), "+f"(d[19]), "+f"(d[20]), "+f"(d[21]), "+f"(d[22]), "+f"(d[23]),
      "+f"(d[24]), "+f"(d[25]), "+f"(d[26]), "+f"(d[27]), "+f"(d[28]), "+f"(d[29]), "+f"(d[30]), "+f"(d[31])
    : "l"(da), "l"(db), "r"(sd));
}
__device__ __forceinline__ void wgmma_rs_n256_tb(float (&d)[128], uint32_t a0, uint32_t a1, uint32_t a2, uint32_t a3, uint64_t db, int sd) {
  asm volatile("{\n.reg .pred p;\nsetp.ne.b32 p, %133, 0;\n"
    "wgmma.mma_async.sync.aligned.m64n256k16.f32.bf16.bf16 "
    "{%0, %1, %2, %3, %4, %5, %6, %7, %8, %9, %10, %11, %12, %13, %14, %15, "
    "%16, %17, %18, %19, %20, %21, %22, %23, %24, %25, %26, %27, %28, %29, %30, %31, "
    "%32, %33, %34, %35, %36, %37, %38, %39, %40, %41, %42, %43, %44, %45, %46, %47, "
    "%48, %49, %50, %51, %52, %53, %54, %55, %56, %57, %58, %59, %60, %61, %62, %63, "
    "%64, %65, %66, %67, %68, %69, %70, %71, %72, %73, %74, %75, %76, %77, %78, %79, "
    "%80, %81, %82, %83, %84, %85, %86, %87, %88, %89, %90, %91, %92, %93, %94, %95, "
    "%96, %97, %98, %99, %100, %101, %102, %103, %104, %105, %106, %107, %108, %109, %110, %111, "
    "%112, %113, %114, %115, %116, %117, %118, %119, %120, %121, %122, %123, %124, %125, %126, %127}, "
    "{%128, %129, %130, %131}, %132, p, 1, 1, 1;\n}"
    : "+f"(d[0]), "+f"(d[1]), "+f"(d[2]), "+f"(d[3]), "+f"(d[4]), "+f"(d[5]), "+f"(d[6]), "+f"(d[7]),
      "+f"(d[8]), "+f"(d[9]), "+f"(d[10]), "+f"(d[11]), "+f"(d[12]), "+f"(d[13]), "+f"(d[14]), "+f"(d[15]),
      "+f"(d[16]), "+f"(d[17]), "+f"(d[18]), "+f"(d[19]), "+f"(d[20]), "+f"(d[21]), "+f"(d[22]), "+f"(d[23]),
      "+f"(d[24]), "+f"(d[25]), "+f"(d[26]), "+f"(d[27]), "+f"(d[28]), "+f"(d[29]), "+f"(d[30]), "+f"(d[31]),
      "+f"(d[32]), "+f"(d[33]), "+f"(d[34]), "+f"(d[35]), "+f"(d[36]), "+f"(d[37]), "+f"(d[38]), "+f"(d[39]),
      "+f"(d[40]), "+f"(d[41]), "+f"(d[42]), "+f"(d[43]), "+f"(d[44]), "+f"(d[45]), "+f"(d[46]), "+f"(d[47]),
      "+f"(d[48]), "+f"(d[49]), "+f"(d[50]), "+f"(d[51]), "+f"(d[52]), "+f"(d[53]), "+f"(d[54]), "+f"(d[55]),
      "+f"(d[56]), "+f"(d[57]), "+f"(d[58]), "+f"(d[59]), "+f"(d[60]), "+f"(d[61]), "+f"(d[62]), "+f"(d[63]),
      "+f"(d[64]), "+f"(d[65]), "+f"(d[66]), "+f"(d[67]), "+f"(d[68]), "+f"(d[69]), "+f"(d[70]), "+f"(d[71]),
      "+f"(d[72]), "+f"(d[73]), "+f"(d[74]), "+f"(d[75]), "+f"(d[76]), "+f"(d[77]), "+f"(d[78]), "+f"(d[79]),
      "+f"(d[80]), "+f"(d[81]), "+f"(d[82]), "+f"(d[83]), "+f"(d[84]), "+f"(d[85]), "+f"(d[86]), "+f"(d[87]),
      "+f"(d[88]), "+f"(d[89]), "+f"(d[90]), "+f"(d[91]), "+f"(d[92]), "+f"(d[93]), "+f"(d[94]), "+f"(d[95]),
      "+f"(d[96]), "+f"(d[97]), "+f"(d[98]), "+f"(d[99]), "+f"(d[100]), "+f"(d[101]), "+f"(d[102]), "+f"(d[103]),
      "+f"(d[104]), "+f"(d[105]), "+f"(d[106]), "+f"(d[107]), "+f"(d[108]), "+f"(d[109]), "+f"(d[110]), "+f"(d[111]),
      "+f"(d[112]), "+f"(d[113]), "+f"(d[114]), "+f"(d[115]), "+f"(d[116]), "+f"(d[117]), "+f"(d[118]), "+f"(d[119]),
      "+f"(d[120]), "+f"(d[121]), "+f"(d[122]), "+f"(d[123]), "+f"(d[124]), "+f"(d[125]), "+f"(d[126]), "+f"(d[127])
    : "r"(a0), "r"(a1), "r"(a2), "r"(a3), "l"(db), "r"(sd));
}
__device__ __forceinline__ void wgmma_rs_n64_tb(float (&d)[32], uint32_t a0, uint32_t a1, uint32_t a2, uint32_t a3, uint64_t db, int sd) {
  asm volatile("{\n.reg .pred p;\nsetp.ne.b32 p, %37, 0;\n"
    "wgmma.mma_async.sync.aligned.m64n64k16.f32.bf16.bf16 "
    "{%0, %1, %2, %3, %4, %5, %6, %7, %8, %9, %10, %11, %12, %13, %14, %15, "
    "%16, %17, %18, %19, %20, %21, %22, %23, %24, %25, %26, %27, %28, %29, %30, %31}, "
    "{%32, %33, %34, %35}, %36, p, 1, 1, 1;\n}"
    : "+f"(d[0]), "+f"(d[1]), "+f"(d[2]), "+f"(d[3]), "+f"(d[4]), "+f"(d[5]), "+f"(d[6]), "+f"(d[7]),
      "+f"(d[8]), "+f"(d[9]), "+f"(d[10]), "+f"(d[11]), "+f"(d[12]), "+f"(d[13]), "+f"(d[14]), "+f"(d[15]),
      "+f"(d[16]), "+f"(d[17]), "+f"(d[18]), "+f"(d[19]), "+f"(d[20]), "+f"(d[21]), "+f"(d[22]), "+f"(d[23]),
      "+f"(d[24]), "+f"(d[25]), "+f"(d[26]), "+f"(d[27]), "+f"(d[28]), "+f"(d[29]), "+f"(d[30]), "+f"(d[31])
    : "r"(a0), "r"(a1), "r"(a2), "r"(a3), "l"(db), "r"(sd));
}
__device__ __forceinline__ void wgmma_rs_n32(float (&d)[16], uint32_t a0, uint32_t a1, uint32_t a2, uint32_t a3, uint64_t db, int sd) {
  asm volatile("{\n.reg .pred p;\nsetp.ne.b32 p, %21, 0;\n"
    "wgmma.mma_async.sync.aligned.m64n32k16.f32.bf16.bf16 "
    "{%0, %1, %2, %3, %4, %5, %6, %7, %8, %9, %10, %11, %12, %13, %14, %15}, "
    "{%16, %17, %18, %19}, %20, p, 1, 1, 0;\n}"
    : "+f"(d[0]), "+f"(d[1]), "+f"(d[2]), "+f"(d[3]), "+f"(d[4]), "+f"(d[5]), "+f"(d[6]), "+f"(d[7]),
      "+f"(d[8]), "+f"(d[9]), "+f"(d[10]), "+f"(d[11]), "+f"(d[12]), "+f"(d[13]), "+f"(d[14]), "+f"(d[15])
    : "r"(a0), "r"(a1), "r"(a2), "r"(a3), "l"(db), "r"(sd));
}
__device__ __forceinline__ void wgmma_rs_n64(float (&d)[32], uint32_t a0, uint32_t a1, uint32_t a2, uint32_t a3, uint64_t db, int sd) {
  asm volatile("{\n.reg .pred p;\nsetp.ne.b32 p, %37, 0;\n"
    "wgmma.mma_async.sync.aligned.m64n64k16.f32.bf16.bf16 "
    "{%0, %1, %2, %3, %4, %5, %6, %7, %8, %9, %10, %11, %12, %13, %14, %15, "
    "%16, %17, %18, %19, %20, %21, %22, %23, %24, %25, %26, %27, %28, %29, %30, %31}, "
    "{%32, %33, %34, %35}, %36, p, 1, 1, 0;\n}"
    : "+f"(d[0]), "+f"(d[1]), "+f"(d[2]), "+f"(d[3]), "+f"(d[4]), "+f"(d[5]), "+f"(d[6]), "+f"(d[7]),
      "+f"(d[8]), "+f"(d[9]), "+f"(d[10]), "+f"(d[11]), "+f"(d[12]), "+f"(d[13]), "+f"(d[14]), "+f"(d[15]),
      "+f"(d[16]), "+f"(d[17]), "+f"(d[18]), "+f"(d[19]), "+f"(d[20]), "+f"(d[21]), "+f"(d[22]), "+f"(d[23]),
      "+f"(d[24]), "+f"(d[25]), "+f"(d[26]), "+f"(d[27]), "+f"(d[28]), "+f"(d[29]), "+f"(d[30]), "+f"(d[31])
    : "r"(a0), "r"(a1), "r"(a2), "r"(a3), "l"(db), "r"(sd));
}

__device__ __forceinline__ uint4 lds16(uint32_t a) {
  uint4 v; asm volatile("ld.shared.v4.u32 {%0, %1, %2, %3}, [%4];" : "=r"(v.x), "=r"(v.y), "=r"(v.z), "=r"(v.w) : "r"(a) : "memory"); return v;
}
__device__ __forceinline__ void sts16(uint32_t a, uint32_t x, uint32_t y, uint32_t z, uint32_t w) {
  asm volatile("st.shared.v4.u32 [%0], {%1, %2, %3, %4};" :: "r"(a), "r"(x), "r"(y), "r"(z), "r"(w) : "memory");
}
__device__ __forceinline__ uint32_t lds4(uint32_t a) { uint32_t v; asm volatile("ld.shared.u32 %0, [%1];" : "=r"(v) : "r"(a) : "memory"); return v; }
__device__ __forceinline__ uint32_t lds4v(uint32_t a) { uint32_t v; asm volatile("ld.volatile.shared.u32 %0, [%1];" : "=r"(v) : "r"(a) : "memory"); return v; }
__device__ __forceinline__ uint32_t bmul(uint32_t a, uint32_t b) { uint32_t r; asm("mul.rn.bf16x2 %0, %1, %2;" : "=r"(r) : "r"(a), "r"(b)); return r; }
__device__ __forceinline__ uint32_t badd(uint32_t a, uint32_t b) { uint32_t r; asm("add.rn.bf16x2 %0, %1, %2;" : "=r"(r) : "r"(a), "r"(b)); return r; }

__device__ __forceinline__ void ldsm4(uint32_t (&r)[4], uint32_t a) {
  asm volatile("ldmatrix.sync.aligned.m8n8.x4.shared.b16 {%0, %1, %2, %3}, [%4];" : "=r"(r[0]), "=r"(r[1]), "=r"(r[2]), "=r"(r[3]) : "r"(a) : "memory");
}
__device__ __forceinline__ uint32_t transpose8(uint32_t a) { uint32_t d; asm volatile("movmatrix.sync.aligned.m8n8.trans.b16 %0, %1;" : "=r"(d) : "r"(a)); return d; }

__device__ __forceinline__ void mma16816(float (&d)[4], const uint32_t (&a)[4], uint32_t b0, uint32_t b1) {
  asm volatile("mma.sync.aligned.m16n8k16.row.col.f32.bf16.bf16.f32 {%0, %1, %2, %3}, {%4, %5, %6, %7}, {%8, %9}, {%0, %1, %2, %3};"
               : "+f"(d[0]), "+f"(d[1]), "+f"(d[2]), "+f"(d[3]) : "r"(a[0]), "r"(a[1]), "r"(a[2]), "r"(a[3]), "r"(b0), "r"(b1));
}

#define CONV_LBO 1u
#define CONV_NRED 8
#define CONV_N 32
#define CONV_ORDER 2
#define EXP_SIDE 0
#define SIDE_AHEAD 2
#define CONV_ARRIVE 14
#define ARRIVE_KK 12
#define SIDE_DELAY_NS 4000
#define KVH(h) (h)
#define HEAD_MAP 1
#define EARLY_LD 3
constexpr int RED_BAR = 6;
constexpr int CV_BAR = 5;
constexpr int PP_BAR = 3;
template <int V> struct Int { static constexpr int value = V; };
struct Ring {
  uint32_t slot, phase;
  __device__ __forceinline__ void next() { if (++slot == NSLOT) { slot = 0; phase ^= 1; } }
};
__device__ __forceinline__ uint32_t bar_addr(uint32_t sb, uint32_t i) { return sb + BARS + 8 * i; }
constexpr int FILLS_BEFORE_FINAL = 11 + 2 * (2 * 15 + 4);
constexpr int FINAL_STG_SLOT = FILLS_BEFORE_FINAL % NSLOT, FINAL_STG_PHASE = (FILLS_BEFORE_FINAL / NSLOT) & 1;
__device__ __forceinline__ constexpr uint32_t fin_slot(int i4) { return (FINAL_STG_SLOT + 1 + i4) % NSLOT; }
__device__ __forceinline__ constexpr uint32_t fin_wrap(int i4) { return (FINAL_STG_SLOT + 1 + i4) >= NSLOT; }

__device__ __forceinline__ int q_tile(int h, int j, int which) { return ((h < 8) == (which == 0)) ? 15 - j : j; }

__device__ __forceinline__ int att_head(int h, int which) { return h; }
__device__ __forceinline__ int p1_head(int h, int t) { return h; }
__device__ __forceinline__ int p1_isv(int t) { return t >> 1; }
__device__ __forceinline__ int p1_rows(int h, int j, int t) { return 2 * j + (t & 1); }
#define KV_FLAG(h) (h)
#define KV_COUNT 16
struct Seg { int kv0, nt; bool diag, shared; };
__device__ __forceinline__ int num_segs(int h, int j, int which) { return q_tile(h, j, which) > q_tile(h, j ^ 1, which) ? 2 : 1; }
__device__ __forceinline__ Seg get_seg(int h, int j, int which, int sg) {
  const int qt = q_tile(h, j, which), qo = q_tile(h, j ^ 1, which);
  if (qt < qo) return Seg{0, 2 * qt + 2, true, true};
  const bool own = (sg == 1) == (which == 0);
  return own ? Seg{2 * qt, 2, true, false} : Seg{0, 2 * qt, false, true};
}
__device__ __forceinline__ void ring_acquire(uint32_t sb, Ring& r, uint32_t bytes) {
  mbar_wait(bar_addr(sb, B_RG_EMPTY + r.slot), r.phase ^ 1);
  mbar_expect_tx(bar_addr(sb, B_RG_FULL + r.slot), bytes);
}
__device__ __forceinline__ void load_tile4(uint32_t dst, const CUtensorMap* m, uint32_t full, int row, int blk0, int rank, bool shared, uint64_t pl = POL_NORMAL) {
  if (shared) {
    tma_ld3_mc(dst + rank * 16384, m, full, 0, row, blk0 + 2 * rank, pl);
  } else {
    tma_ld3(dst, m, full, 0, row, blk0, pl);
    tma_ld3(dst + 16384, m, full, 0, row, blk0 + 2, pl);
  }
}
__device__ __forceinline__ void producer_main(const Params& p, uint32_t sb, int h, int j) {
  const int rank = j & 1;
  const unsigned epoch = load_epoch();
  for (int it = EARLY_LD; it < 71; it++) {
    const int t = it >> 4, k = it & 15, s = it & 3;
    mbar_wait(bar_addr(sb, B_P1_EMPTY + s), ((it >> 2) & 1) ^ 1);
    const uint32_t full = bar_addr(sb, B_P1_FULL + s), dst = sb + s * P1_STAGE;
    mbar_expect_tx(full, P1_STAGE);
    if (t < 4) {
      tma_ld2(dst, &p.ckv, full, k * 64, p1_rows(h, j, t) * 128, pol((HINTS & 2) && t == 3));
      load_tile4(dst + 16384, p1_isv(t) ? &p.wuv : &p.wuk, full, k * 64, p1_head(h, t) * 4, rank, true, pol(HINTS & 1));
    } else {
      tma_ld2(dst, &p.x, full, k * 64, q_tile(h, j, 0) * 128, pol(HINTS & 64));
      load_tile4(dst + 16384, &p.wq, full, k * 64, att_head(h, 0) * 4, rank, true, pol(HINTS & 4));
    }
  }
  Ring r{0, 0};
  int nfill = 0;
  auto first5 = [&]() {
    if (nfill < 5) { if (nfill != 2) mbar_wait(bar_addr(sb, B_P1_EMPTY + (nfill < 2 ? nfill : nfill - 1)), nfill == 4 ? 0 : 1); nfill++; }
  };
  int hs = 5;
  auto shared_acquire = [&]() {
    mbar_wait(bar_addr(sb, B_RG_EMPTY + r.slot), r.phase ^ 1);
    if (hs < 5) {
      mbar_arrive_remote(bar_addr(sb, B_PFREE + r.slot), rank ^ 1);
      mbar_wait(bar_addr(sb, B_PFREE + r.slot), 0);
      hs++;
    }
    mbar_expect_tx(bar_addr(sb, B_RG_FULL + r.slot), 32768);
  };
  for (int which = 0; which < 2; which++) {
    const int qt = q_tile(h, j, which);
    if (which == 1) {
      for (int kc = 0; kc < 7; kc++) {
        if ((kc & 1) == 0) {
          ring_acquire(sb, r, kc == 6 ? 16384 : 32768);
          const uint32_t full = bar_addr(sb, B_RG_FULL + r.slot), dst = sb + r.slot * SLOT;
          tma_ld2(dst, &p.x, full, kc * 64, qt * 128);
          if (kc < 6) tma_ld2(dst + 16384, &p.x, full, kc * 64 + 64, qt * 128);
          r.next();
        }
        ring_acquire(sb, r, 32768);
        load_tile4(sb + r.slot * SLOT, &p.wq, bar_addr(sb, B_RG_FULL + r.slot), kc * 64, att_head(h, 1) * 4, rank, false);
        r.next();
      }
    }
    if (which == 0) { flag_wait(flag_at(g_flags.kv_ready, KV_FLAG(h)), KV_COUNT, epoch); fence_async_all(); }
    const int nseg = num_segs(h, j, which);
    for (int sg = 0; sg < nseg; sg++) {
      const Seg S = get_seg(h, j, which, sg);
      if (which == 1 && S.shared) hs = 0;
      for (int f = 0; f < 2 * S.nt; f++) {
        const bool isK = (f == 0) || ((f & 1) && f < 2 * S.nt - 1);
        const int tile = S.kv0 + (f == 0 ? 0 : (isK ? (f + 1) >> 1 : (f == 2 * S.nt - 1 ? S.nt - 1 : (f >> 1) - 1)));
        first5();
        shared_acquire();
        load_tile4(sb + r.slot * SLOT, &p.kv, bar_addr(sb, B_RG_FULL + r.slot), ((isK ? 0 : NH) + KVH(att_head(h, which))) * SEQ + tile * 64, 0, rank, S.shared, pol(which == 0 ? (HINTS & 8) : (HINTS & 32)));
        r.next();
      }
    }
  }
  mbar_wait(bar_addr(sb, B_RG_EMPTY + FINAL_STG_SLOT), FINAL_STG_PHASE ^ 1);
  mbar_arrive(bar_addr(sb, B_RG_FULL + FINAL_STG_SLOT));
  for (int i = 0; i < 14; i++) {
    const uint32_t sl = fin_slot(i & 3), ph = FINAL_STG_PHASE ^ fin_wrap(i & 3) ^ ((i >> 2) & 1);
    mbar_wait(bar_addr(sb, B_RG_EMPTY + sl), ph ^ 1);
    const uint32_t full = bar_addr(sb, B_RG_FULL + sl);
    mbar_expect_tx(full, 32768);
    tma_ld2_mc(sb + sl * SLOT + rank * 16384, &p.wo, full, (i >> 1) * 64, ((i & 1) ? att_head(h ^ 8, 0) : att_head(h, 1)) * HD + rank * 128, pol(HINTS & 16));
  }
  flag_wait_fast(flag_at(g_flags.part_ready, q_tile(h, j, 1) * 2), 16, epoch);
  mbar_arrive(bar_addr(sb, B_PART));
  flag_wait_fast(flag_at(g_flags.part_ready, q_tile(h, j, 1) * 2 + 1), 16, epoch);
  GT(56);
  mbar_arrive(bar_addr(sb, B_PART + 1));
}

__device__ __forceinline__ void storer_main(const Params& p, uint32_t sb, int h, int j, int w) {
  const uint32_t full = bar_addr(sb, B_ST_FULL + w), empty = bar_addr(sb, B_ST_EMPTY + w);
  const int lane = threadIdx.x & 31;
  const unsigned epoch = load_epoch();
  for (int job = 0; job < 8; job++) {
    const int t = job >> 1, half = job & 1;
    mbar_wait(full, job & 1);
    const uint32_t src = sb + P1_STG + w * 16384 + (lane >> 3) * 128;
    bf16* dst = at<bf16>(g_kv, (uint32_t)(((p1_isv(t) * NH + KVH(p1_head(h, t))) * SEQ + p1_rows(h, j, t) * 128 + w * 64 + (lane >> 3)) * HD + half * 128 + (lane & 7) * 8) * 2);
#pragma unroll 4
    for (int i = 0; i < 32; i++) {
      const int r4 = (i & 15) * 4;
      const uint4 v = lds16(src + (i >> 4) * 8192 + r4 * 128 + (((lane & 7) ^ ((r4 + (lane >> 3)) & 7)) << 4));
      *reinterpret_cast<uint4*>(dst + r4 * HD + (i >> 4) * 64) = v;
    }
    __syncwarp();
    if (lane == 0) mbar_arrive(empty);
  }
  __syncwarp();
  if (lane != 0) return;
  flag_signal(flag_at(g_flags.kv_ready, KV_FLAG(h)));
  const int cta = h * 8 + j;
  {
    mbar_wait(full, 0);
    tma_st3(&p.ctx, sb + QREG + w * 32768, 0, cta * 128 + w * 64, 0);
    bulk_commit();
    bulk_wait_read();
    mbar_arrive(empty);
    bulk_wait_all();
    flag_signal(flag_at(g_flags.ctx_ready, cta * 2 + w));
  }
  {
    flag_wait(flag_at(g_flags.ctx_ready, (cta ^ 64) * 2 + w), 1, epoch);
    fence_async_all();
    mbar_wait(bar_addr(sb, B_QFREE + w), 0);
    mbar_expect_tx(bar_addr(sb, B_CTXF + w), 32768);
    tma_ld3(sb + QREG + w * 32768, &p.ctx, bar_addr(sb, B_CTXF + w), 0, (cta ^ 64) * 128 + w * 64, 0);
    const int qt = q_tile(h, j, 1);
    const uint32_t stg = sb + FINAL_STG_SLOT * SLOT;
    for (int ch = 0; ch < 7; ch++) {
      const int b = ch & 1;
      mbar_wait(bar_addr(sb, B_S2_FULL + w * 2 + b), (ch >> 1) & 1);
      tma_st2(&p.part, stg + w * 16384 + b * 8192, ch * 64, (h & 7) * SEQ + qt * 128 + w * 64);
      bulk_commit();
      bulk_wait_read();
      mbar_arrive(bar_addr(sb, B_S2_EMPTY + w * 2 + b));
      if (ch == 5) { bulk_wait_all(); flag_signal_after_bulk(flag_at(g_flags.part_ready, qt * 2)); }
    }
    GT(48 + w);
    bulk_wait_all();
    GT(50 + w);
    flag_signal_after_bulk(flag_at(g_flags.part_ready, qt * 2 + 1));
    GT(52 + w);
  }
}

template <int OFF, int NB, int NREG>
__device__ __forceinline__ void store_blocks(uint32_t base, uint32_t lanebase, const uint32_t (&pk)[NREG]) {
#pragma unroll
  for (int J = 0; J < NB * 8; J += 2) {
    const uint32_t a = base + (J >> 3) * 8192 + (lanebase ^ ((J & 7) << 4));
    stsm4(a, pk[OFF + 2 * J], pk[OFF + 2 * J + 1], pk[OFF + 2 * J + 2], pk[OFF + 2 * J + 3]);
  }
}
__device__ __forceinline__ void warp_arrive(uint32_t bar, int lane) { __syncwarp(); if (lane == 0) mbar_arrive(bar); }
__device__ __forceinline__ void release(uint32_t bar, int lane, int rank, bool shared) {
  if (shared) { if (lane < 2) mbar_arrive_remote(bar, rank ^ lane); }
  else if (lane == 0) mbar_arrive_n(bar, 2);
}

__device__ __forceinline__ void consumer_main(const Params& p, uint32_t sb, int h, int j, int w) {
  const int lane = threadIdx.x & 31;
  const int rank = j & 1;
  const uint32_t st_full = bar_addr(sb, B_ST_FULL + w), st_empty = bar_addr(sb, B_ST_EMPTY + w);
  const uint32_t stg = sb + P1_STG + w * 16384;

  auto turn_begin = [&]() { named_sync(PP_BAR + w, 256); };
  auto turn_end = [&]() { named_arrive(PP_BAR + (w ^ 1), 256); };
  if (w == 1) named_arrive(PP_BAR, 256);
  float acc[128];
#pragma unroll
  for (int i = 0; i < 128; i++) acc[i] = 0.f;
  uint32_t pk[64];
#pragma unroll
  for (int i = 0; i < 64; i++) pk[i] = 0;
  PDECL;
  TSG(0); TS(1);
  const uint32_t qreg = sb + QREG + w * 32768;
  for (int t = 0; t < 5; t++) {
    const int nk = t < 4 ? 16 : 7;
#pragma unroll 1
    for (int k = 0; k < nk; k++) {
      const int it = t * 16 + k, s = k & 3;
      mbar_wait(bar_addr(sb, B_P1_FULL + s), (it >> 2) & 1);
      const uint64_t da = desc_k(sb + s * P1_STAGE + w * 8192), db = desc_mn(sb + s * P1_STAGE + 16384);
      turn_begin();
      wg_fence();
#pragma unroll
      for (int kk = 0; kk < 4; kk++) wgmma_ss_n256_tb(acc, desc_add(da, kk * 32), desc_add(db, kk * 2048), (k | kk) != 0);
      wg_commit();
      turn_end();
      const int k2 = t < 4 ? 6 : 3;
      if (t > 0 && (k == 0 || k == k2)) {
        const int job = 2 * (t - 1) + (k != 0);
        if (job > 0) mbar_wait(st_empty, (job - 1) & 1);
        if (k == 0) store_blocks<0, 2>(stg, lane_base16(), pk); else store_blocks<32, 2>(stg, lane_base16(), pk);
        warp_arrive(st_full, lane);
      }
      wg_wait<1>();
      if (k > 0) release(bar_addr(sb, B_P1_EMPTY + ((k - 1) & 3)), lane, rank, true);
    }
    wg_wait<0>();
    reg_fence(acc);
    release(bar_addr(sb, B_P1_EMPTY + ((nk - 1) & 3)), lane, rank, true);
#pragma unroll
    for (int i = 0; i < 64; i++) pk[i] = pack_bf16(acc[2 * i], acc[2 * i + 1]);
    TS(t < 4 ? 2 + t : 60);
  }
  mbar_wait(st_empty, 1);
  mbar_wait(bar_addr(sb, B_ST_EMPTY + (w ^ 1)), 1);
  mbar_wait(bar_addr(sb, B_P1_EMPTY + 3), 0);
  store_blocks<0, 4>(qreg, lane_base16(), pk);
  fence_async_smem();
  named_sync(1 + w, 128);
  TS(6);

  Ring r{0, 0};
  TS(15);
  constexpr float SC = 0.0625f * 1.4426950408889634f;
  for (int which = 0; which < 2; which++) {
    if (which == 1) {
#pragma unroll
      for (int i = 0; i < 128; i++) acc[i] = 0.f;
      uint32_t xaddr = 0, xslot = 0, prev_w = 0;
#pragma unroll 1
      for (int kc = 0; kc < 7; kc++) {
        if ((kc & 1) == 0) {
          mbar_wait(bar_addr(sb, B_RG_FULL + r.slot), r.phase);
          xaddr = sb + r.slot * SLOT + w * 8192;
          if (kc > 0) { prev_w |= xslot << 8 | 0x10000; }
          xslot = r.slot;
          r.next();
        } else {
          xaddr += 16384;
        }
        mbar_wait(bar_addr(sb, B_RG_FULL + r.slot), r.phase);
        const uint64_t da = desc_k(xaddr), db = desc_mn(sb + r.slot * SLOT);
        turn_begin();
        wg_fence();
#pragma unroll
        for (int kk = 0; kk < 4; kk++) wgmma_ss_n256_tb(acc, desc_add(da, kk * 32), desc_add(db, kk * 2048), (kc | kk) != 0);
        wg_commit();
        turn_end();
        wg_wait<1>();
        if (kc > 0) {
          if (prev_w & 0x10000) release(bar_addr(sb, B_RG_EMPTY + ((prev_w >> 8) & 0xff)), lane, rank, false);
          release(bar_addr(sb, B_RG_EMPTY + (prev_w & 0xff)), lane, rank, false);
        }
        prev_w = r.slot;
        r.next();
      }
      wg_wait<0>();
      reg_fence(acc);
      TS(61);
      release(bar_addr(sb, B_RG_EMPTY + xslot), lane, rank, false);
      release(bar_addr(sb, B_RG_EMPTY + prev_w), lane, rank, false);
#pragma unroll
      for (int i = 0; i < 64; i++) pk[i] = pack_bf16(acc[2 * i], acc[2 * i + 1]);
      mbar_wait(st_empty, 0);
      store_blocks<0, 4>(qreg, lane_base16(), pk);
      fence_async_smem();
      named_sync(1 + w, 128);
      TS(9);
    }
#pragma unroll
    for (int i = 0; i < 128; i++) acc[i] = 0.f;
    float s[32];
#pragma unroll
    for (int i = 0; i < 32; i++) s[i] = 0.f;
    uint32_t pa[16];
    float m0 = -INFINITY, m1 = -INFINITY, l0 = 0.f, l1 = 0.f;
    const uint64_t dq = desc_k(qreg);
    uint64_t dk = 0, dqq = 0, dv = 0;
    auto prep_qk = [&](uint32_t kaddr) { dk = desc_k(kaddr); dqq = dq + (kaddr >> 31); asm volatile("" : "+l"(dk), "+l"(dqq)); };
    auto prep_pv = [&](uint32_t vaddr) { dv = desc_mn(vaddr); asm volatile("" : "+l"(dv)); };
    auto issue_qk = [&]() {
#pragma unroll
      for (int kk = 0; kk < 16; kk++)
        wgmma_ss_n64(s, desc_add(dqq, (kk >> 2) * 8192 + (kk & 3) * 32), desc_add(dk, (kk >> 2) * 8192 + (kk & 3) * 32), kk != 0);
    };
    auto issue_pv = [&](int accumulate) {
#pragma unroll
      for (int kk = 0; kk < 4; kk++)
        wgmma_rs_n256_tb(acc, pa[4 * kk], pa[4 * kk + 1], pa[4 * kk + 2], pa[4 * kk + 3], desc_add(dv, kk * 2048), accumulate | kk);
    };
    auto mask_diag = [&]() {
      const uint32_t ft = fresh_tid();
      const int r0 = 16 * ((ft >> 5) & 3) + ((ft & 31) >> 2), c = ft & 3;
#pragma unroll
      for (int jj = 0; jj < 8; jj++) {
        const int cc = 8 * jj + 2 * c;
        if (cc > r0)         s[4 * jj]     = -INFINITY;
        if (cc + 1 > r0)     s[4 * jj + 1] = -INFINITY;
        if (cc > r0 + 8)     s[4 * jj + 2] = -INFINITY;
        if (cc + 1 > r0 + 8) s[4 * jj + 3] = -INFINITY;
      }
    };
    float a0, a1;
    auto softmax = [&]() -> bool {
      float x0 = fmaxf(s[0], s[1]), x1 = fmaxf(s[2], s[3]);
#pragma unroll
      for (int jj = 1; jj < 8; jj++) {
        x0 = fmaxf(x0, fmaxf(s[4 * jj], s[4 * jj + 1]));
        x1 = fmaxf(x1, fmaxf(s[4 * jj + 2], s[4 * jj + 3]));
      }
      x0 = fmaxf(x0, __shfl_xor_sync(0xffffffffu, x0, 1));
      x1 = fmaxf(x1, __shfl_xor_sync(0xffffffffu, x1, 1));
      x0 = fmaxf(x0, __shfl_xor_sync(0xffffffffu, x0, 2));
      x1 = fmaxf(x1, __shfl_xor_sync(0xffffffffu, x1, 2));
      const bool grow = __any_sync(0xffffffffu, fmaxf(x0 - m0, x1 - m1) * SC > 8.f);
      if (grow) {
        x0 = fmaxf(x0, m0); x1 = fmaxf(x1, m1);
        a0 = ex2((m0 - x0) * SC); a1 = ex2((m1 - x1) * SC);
        m0 = x0; m1 = x1;
        l0 *= a0; l1 *= a1;
      }
      const float b0 = -m0 * SC, b1 = -m1 * SC;
      float t0 = 0.f, t1 = 0.f, t2 = 0.f, t3 = 0.f;
#pragma unroll
      for (int jj = 0; jj < 8; jj++) {
        s[4 * jj]     = ex2(fmaf(s[4 * jj], SC, b0));
        s[4 * jj + 1] = ex2(fmaf(s[4 * jj + 1], SC, b0));
        s[4 * jj + 2] = ex2(fmaf(s[4 * jj + 2], SC, b1));
        s[4 * jj + 3] = ex2(fmaf(s[4 * jj + 3], SC, b1));
        t0 += s[4 * jj]; t1 += s[4 * jj + 1]; t2 += s[4 * jj + 2]; t3 += s[4 * jj + 3];
      }
      l0 += t0 + t1; l1 += t2 + t3;
      return grow;
    };
    auto softmax_fast = [&]() -> bool {
      const float b0 = -m0 * SC, b1 = -m1 * SC;
      float t0 = 0.f, t1 = 0.f, t2 = 0.f, t3 = 0.f;
#pragma unroll
      for (int jj = 0; jj < 8; jj++) {
        s[4 * jj]     = ex2(fmaf(s[4 * jj], SC, b0));
        s[4 * jj + 1] = ex2(fmaf(s[4 * jj + 1], SC, b0));
        s[4 * jj + 2] = ex2(fmaf(s[4 * jj + 2], SC, b1));
        s[4 * jj + 3] = ex2(fmaf(s[4 * jj + 3], SC, b1));
        t0 += s[4 * jj]; t1 += s[4 * jj + 1]; t2 += s[4 * jj + 2]; t3 += s[4 * jj + 3];
      }
      t0 += t1; t2 += t3;
      uint32_t redo;
      asm volatile("{\n.reg .pred p, q;\nsetp.le.f32 p, %1, 0f47800000;\nbarrier.cta.red.or.aligned.pred q, %2, 128, !p;\nselp.u32 %0, 1, 0, q;\n}"
                   : "=r"(redo) : "f"(fmaxf(t0, t2) + (t0 - t0) + (t2 - t2)), "r"(RED_BAR + w) : "memory");
      if (!redo) { l0 += t0; l1 += t2; }
      return redo;
    };
    auto rescale = [&]() {
#pragma unroll
      for (int i = 0; i < 32; i++) { acc[4 * i] *= a0; acc[4 * i + 1] *= a0; acc[4 * i + 2] *= a1; acc[4 * i + 3] *= a1; }
    };
    auto to_p = [&]() {
#pragma unroll
      for (int i = 0; i < 16; i++) pa[i] = pack_bf16(s[2 * i], s[2 * i + 1]);
    };

    const int nseg = num_segs(h, j, which);
#pragma unroll 1
    for (int sg = 0; sg < nseg; sg++) {
      const Seg S = get_seg(h, j, which, sg);
      const bool skip = S.diag && w == 0;
      const int n = S.nt - (skip ? 1 : 0);
      auto take = [&]() { const uint32_t sl = r.slot; mbar_wait(bar_addr(sb, B_RG_FULL + sl), r.phase); r.next(); return sl; };
      auto give = [&](uint32_t sl) { release(bar_addr(sb, B_RG_EMPTY + sl), lane, rank, S.shared); };
      uint32_t ks = take();
      if (sg == 0) TS(62 + which);
      prep_qk(sb + ks * SLOT);
      turn_begin();
      wg_fence();
      issue_qk();
      wg_commit();
      turn_end();
      wg_wait<0>();
      reg_fence(s);
      give(ks);
      const bool lastseg = which == 1 && sg == nseg - 1;
      if (lastseg && n == 1 && lane == 0) mbar_arrive(bar_addr(sb, B_QFREE + w));
      if (S.diag && n == 1) mask_diag();
      if (softmax() && sg > 0) rescale();
      to_p();
#pragma unroll 1
      for (int jj = 1; jj < n; jj++) {
        PCLK(c0);
        ks = take();
        PACC(pw_k, c0);
        PCLK(c1);
        const uint32_t vs = take();
        PACC(pw_v, c1);
        prep_qk(sb + ks * SLOT);
        prep_pv(sb + vs * SLOT);
        PCLK(c5);
        turn_begin();
        PACC(pw_p1, c5);
        PCLK(c6);
        wg_fence();
        issue_qk();
        wg_commit();
        issue_pv((sg > 0) | (jj > 1));
        wg_commit();
        turn_end();
        PACC(pw_p1w, c6);
        PCLK(c2);
        wg_wait<1>();
        PACC(pw_qk, c2);
        reg_fence(s);
        PCLK(c3);
        if (S.diag && jj == n - 1) mask_diag();
        bool grow = false;
        if (softmax_fast()) {
          wg_fence();
          issue_qk();
          wg_commit();
          wg_wait<0>();
          reg_fence(s);
          if (S.diag && jj == n - 1) mask_diag();
          grow = softmax();
        }
        give(ks);
        if (lastseg && jj == n - 1 && lane == 0) mbar_arrive(bar_addr(sb, B_QFREE + w));
        PACC(pw_sm, c3);
        PCLK(c4);
        wg_wait<0>();
        PACC(pw_pv, c4);
        reg_fence(acc);
        reg_fence(pa);
        give(vs);
        if (grow) rescale();
        to_p();
      }
      if (skip) { give(take()); turn_begin(); turn_end(); }
      {
        const uint32_t vs = take();
        prep_pv(sb + vs * SLOT);
        turn_begin();
        wg_fence();
        issue_pv((sg > 0) | (n > 1));
        wg_commit();
        turn_end();
        wg_wait<0>();
        reg_fence(acc);
        reg_fence(pa);
        give(vs);
      }
      if (skip) give(take());
    }
    TS(7 + 3 * which);
    l0 += __shfl_xor_sync(0xffffffffu, l0, 1); l1 += __shfl_xor_sync(0xffffffffu, l1, 1);
    l0 += __shfl_xor_sync(0xffffffffu, l0, 2); l1 += __shfl_xor_sync(0xffffffffu, l1, 2);
    const float i0 = 1.f / l0, i1 = 1.f / l1;
#pragma unroll
    for (int i = 0; i < 32; i++) {
      pk[2 * i]     = pack_bf16(acc[4 * i] * i0, acc[4 * i + 1] * i0);
      pk[2 * i + 1] = pack_bf16(acc[4 * i + 2] * i1, acc[4 * i + 3] * i1);
    }
    if (which == 0) {
      store_blocks<0, 4>(qreg, lane_base16(), pk);
      fence_async_smem();
      warp_arrive(st_full, lane);
    }
    TS(8 + 3 * which);
    if (which == 0) TS(31);
  }

  {
    float oa[32], ob[32];
#pragma unroll
    for (int i = 0; i < 32; i++) { oa[i] = 0.f; ob[i] = 0.f; }
    mbar_wait(bar_addr(sb, B_RG_FULL + FINAL_STG_SLOT), FINAL_STG_PHASE);
    const uint32_t stg2 = sb + FINAL_STG_SLOT * SLOT + w * 16384;
    auto stage_o = [&](float (&o)[32], int ch) {
      reg_fence(o);
      uint32_t q[16];
#pragma unroll
      for (int i = 0; i < 16; i++) q[i] = pack_bf16(o[2 * i], o[2 * i + 1]);
      if (ch >= 2) mbar_wait(bar_addr(sb, B_S2_EMPTY + w * 2 + (ch & 1)), ((ch >> 1) - 1) & 1);
      store_blocks<0, 1>(stg2 + (ch & 1) * 8192, lane_base16(), q);
    };
    auto hand_over = [&](int ch) {
      fence_async_smem();
      warp_arrive(bar_addr(sb, B_S2_FULL + w * 2 + (ch & 1)), lane);
    };
    uint32_t pk2[64];
#pragma unroll
    for (int i = 0; i < 64; i++) pk2[i] = 0;
    uint32_t p2 = 0;
    auto chunk = [&](int ch, auto odd, float (&o)[32], float (&oprev)[32]) {
      constexpr int I4 = decltype(odd)::value * 2;
      constexpr uint32_t s1 = fin_slot(I4), s2 = fin_slot(I4 + 1);
      const uint32_t f1 = FINAL_STG_PHASE ^ fin_wrap(I4) ^ ((ch >> 1) & 1), f2 = FINAL_STG_PHASE ^ fin_wrap(I4 + 1) ^ ((ch >> 1) & 1);
      const uint32_t z = (uint32_t)ch >> 8;
      mbar_wait(bar_addr(sb, B_RG_FULL + s1), f1);
      const uint64_t d1 = desc_mn(sb + s1 * SLOT) + z;
      turn_begin();
      wg_fence();
#pragma unroll
      for (int kk = 0; kk < 16; kk++) {
        wgmma_rs_n64_tb(o, pk[4 * kk], pk[4 * kk + 1], pk[4 * kk + 2], pk[4 * kk + 3], desc_add(d1, kk * 2048), kk != 0);
        if (kk == ARRIVE_KK) turn_end();
      }
      wg_commit();
      if (ch >= 1) {
        wg_wait<1>();
        if (ch <= 5) release(bar_addr(sb, B_RG_EMPTY + p2), lane, rank, true);
        stage_o(oprev, ch - 1);
      }
      mbar_wait(bar_addr(sb, B_RG_FULL + s2), f2);
      if (ch == 0) {
        mbar_wait(bar_addr(sb, B_CTXF + w), 0);
        const uint32_t t = fresh_tid(), ln = t & 31, row = 16 * ((t >> 5) & 3) + (ln & 15);
#pragma unroll
        for (int kk = 0; kk < 16; kk++) {
          uint32_t f[4];
          ldsm4(f, qreg + (kk >> 2) * 8192 + row * 128 + (((2 * (kk & 3) + (ln >> 4)) ^ (row & 7)) << 4));
          pk2[4 * kk] = f[0]; pk2[4 * kk + 1] = f[1]; pk2[4 * kk + 2] = f[2]; pk2[4 * kk + 3] = f[3];
        }
      }
      const uint64_t d2 = desc_mn(sb + s2 * SLOT) + z;
      turn_begin();
      wg_fence();
#pragma unroll
      for (int kk = 0; kk < 16; kk++) {
        wgmma_rs_n64_tb(o, pk2[4 * kk], pk2[4 * kk + 1], pk2[4 * kk + 2], pk2[4 * kk + 3], desc_add(d2, kk * 2048), 1);
        if (kk == ARRIVE_KK && (ch < 6 || w == 0)) turn_end();
      }
      wg_commit();
      if (ch >= 1) hand_over(ch - 1);
      wg_wait<1>();
      if (ch <= 4) release(bar_addr(sb, B_RG_EMPTY + s1), lane, rank, true);
      p2 = s2;
    };
#pragma unroll 1
    for (int ch = 0; ch < 6; ch += 2) { chunk(ch, Int<0>(), oa, ob); chunk(ch + 1, Int<1>(), ob, oa); }
    chunk(6, Int<0>(), oa, ob);
    wg_wait<0>();
    reg_fence(pk);
    reg_fence(pk2);
    stage_o(oa, 6);
    hand_over(6);
  }
  TS(12);
  if ((threadIdx.x & 127) == 0) GT(54 + w);

  {
    const int row0 = q_tile(h, j, 1) * 128 + (h & 7) * 16;
    const int tid = fresh_tid() - 128;
    uint32_t row[4], col[4];
#pragma unroll
    for (int v = 0; v < 3; v++) { const int idx = tid + 256 * v; row[v] = row0 + idx / 48; col[v] = (idx % 48) * 8; }
    row[3] = row0 + ((tid & 127) >> 3); col[3] = 384 + (tid & 7) * 8;
    uint4 ld[8][4];
    TS(16); TS(18);
    mbar_wait(bar_addr(sb, B_PART), 0);
#pragma unroll
    for (int hh = 0; hh < 8; hh++)
#pragma unroll
      for (int v = 0; v < 3; v++)
        ld[hh][v] = __ldcg(reinterpret_cast<const uint4*>(g_part + ((size_t)hh * SEQ + row[v]) * DM + col[v]));
    auto load_last = [&]() {
#pragma unroll
      for (int hh = 0; hh < 8; hh++) ld[hh][3] = __ldcg(reinterpret_cast<const uint4*>(g_part + ((size_t)hh * SEQ + row[3]) * DM + col[3]));
    };
    auto finish = [&](int v) {
      float sum[8] = {0.f, 0.f, 0.f, 0.f, 0.f, 0.f, 0.f, 0.f};
#pragma unroll
      for (int hh = 0; hh < 8; hh++) {
        const uint32_t u[4] = {ld[hh][v].x, ld[hh][v].y, ld[hh][v].z, ld[hh][v].w};
#pragma unroll
        for (int e = 0; e < 4; e++) { sum[2 * e] += __uint_as_float(u[e] << 16); sum[2 * e + 1] += __uint_as_float(u[e] & 0xffff0000u); }
      }
      uint4 o;
      o.x = pack_bf16(sum[0], sum[1]); o.y = pack_bf16(sum[2], sum[3]); o.z = pack_bf16(sum[4], sum[5]); o.w = pack_bf16(sum[6], sum[7]);
      *reinterpret_cast<uint4*>(p.out + (size_t)row[v] * OUTW + DA + col[v]) = o;
    };
    const bool early = tid < 128 && __all_sync(0xffffffffu, mbar_try(bar_addr(sb, B_PART + 1), 0));
    if (early) load_last();
    finish(0); finish(1); finish(2);
    if (tid < 128) {
      if (!early) { mbar_wait(bar_addr(sb, B_PART + 1), 0); load_last(); }
      TS(17);
      finish(3);
    }
  }
  TS(13); TSG(14);
}

namespace ssm {
constexpr int NCH = DA / NCONV;
constexpr int NS = 8, NP = 4;
constexpr uint32_t X0 = 896;
constexpr uint32_t HO = X0 + 4096;
constexpr uint32_t HE = HO + HO_STRIDE + 64;
constexpr uint32_t SSLOT = HE + 4096 + 64;
constexpr uint32_t PART = 264 * 16;
constexpr uint32_t OFF_P = NS * SSLOT, OFF_D = OFF_P + NP * 4 * PART, END = OFF_D + NCH * 4;
static_assert(SSLOT % 128 == 0 && HO % 128 == 0 && END <= BARS, "smem");
enum : uint32_t { B_FULL = 0, B_EMPTY = NS, B_PFULL = 2 * NS, B_PEMPTY = 2 * NS + NP };
__device__ __forceinline__ int channel(int cidx, int i) { return (i >> 4) * 64 + cidx * 16 + (i & 15); }

__device__ __forceinline__ void producer(const Params& p, uint32_t sb, int cidx, unsigned epoch) {
#pragma unroll 1
  for (int i = 0; i < NCH; i++) {
    const int s = i % NS, ch = channel(cidx, i);
    const uint32_t full = bar_addr(sb, B_FULL + s), dst = sb + s * SSLOT;
    mbar_wait(bar_addr(sb, B_EMPTY + s), ((i / NS) & 1) ^ 1);
    mbar_expect_tx(full, 4096 + 4128 + 4096);
    bulk_ld(dst + HE, at<uint8_t>(p.a_ssmk, ch * 4096), 4096, full);
    if ((i & 15) == 0) { flag_wait(flag_at(g_flags.x_ready, i >> 4), NMAIN, epoch); fence_async_all(); }
    bulk_ld(dst + HO, at<uint8_t>(g_ho, ch * HO_STRIDE), 4128, full);
    bulk_ld(dst + X0, at<uint8_t>(g_xs, ch * 4096), 4096, full);
  }
}

__device__ __forceinline__ void reducer(uint32_t sb, int cidx, int rw) {
#pragma unroll 1
  for (int i = rw; i < NCH; i += 3) {
    const uint32_t pb = sb + OFF_P + (i % NP) * 4 * PART;
    uint8_t* dst = at<uint8_t>(g_xs, channel(cidx, i) * 4096);
    mbar_wait(bar_addr(sb, B_PFULL + i % NP), (i / NP) & 1);
    asm volatile("cp.async.bulk.global.shared::cta.bulk_group [%0], [%1], 4096;" :: "l"(dst), "r"(pb + 3 * PART) : "memory");
    bulk_commit();
    bulk_wait_all();
#pragma unroll
    for (int k = 2; k >= 0; k--)
      asm volatile("cp.reduce.async.bulk.global.shared::cta.bulk_group.add.noftz.bf16 [%0], [%1], 4096;" :: "l"(dst), "r"(pb + k * PART) : "memory");
    bulk_commit();
    bulk_wait_read();
    mbar_arrive(bar_addr(sb, B_PEMPTY + i % NP));
    if (((i + 3) >> 4) != (i >> 4)) {
      bulk_wait_all();
      fence_async_all();
      flag_signal(flag_at(g_flags.z_ready, i >> 4));
    }
  }
}

__device__ __forceinline__ void mma_warpgroup(uint32_t sb, int w) {
  const int lane = threadIdx.x & 31, g = lane >> 2, c = lane & 3, wq = (threadIdx.x >> 5) & 3;
  const uint32_t aoff = ((g & 1) ? HO + 30 : HE) + (16 * wq - g + 2 * c) * 2;
  const uint32_t poff = OFF_P + wq * PART + (2 * wq + lane) * 16;
  const uint32_t dmask = (wq == 0 && c == (g >> 1)) ? ((g & 1) ? 0xffff0000u : 0xffffu) : 0u;
  constexpr int NE = 256 / CONV_N, LT = CONV_N == 64 ? 3 : 2;
  float acc[NE][CONV_N / 2];
  uint32_t fa[16][4];
#pragma unroll
  for (int e = 0; e < NE; e++)
#pragma unroll
    for (int i = 0; i < CONV_N / 2; i++) acc[e][i] = 0.f;
  auto load_a = [&](int i) {
    mbar_wait(bar_addr(sb, B_FULL + i % NS), (i / NS) & 1);
    const uint32_t ad = sb + (i % NS) * SSLOT + aoff;
#pragma unroll
    for (int m = 0; m < 16; m++) {
      fa[m][0] = lds4(ad + m * 256 + 16); fa[m][1] = lds4(ad + m * 256 + 144); fa[m][2] = lds4(ad + m * 256); fa[m][3] = lds4(ad + m * 256 + 128);
    }
    fa[0][2] = badd(fa[0][2], lds4(sb + OFF_D + i * 4) & dmask);
  };
  if (w == 1) named_arrive(PP_BAR, 256);
  load_a(w);
  if (threadIdx.x == 128) { GT(12); PT(10); }
#pragma unroll 1
  for (int i = w; i < NCH; i += 2) {
    const uint64_t db = (uint64_t)((((sb + (i % NS) * SSLOT + X0 - 16 * CONV_LBO) & 0x3FFFF) >> 4) | (CONV_LBO << 16)) | ((uint64_t)8 << 32);
    PCLK(c0);
    named_sync(PP_BAR + w, 256);
    PACC(t0, c0);
    PCLK(c1);
    wg_fence();
#pragma unroll
    for (int r = 0; r < 16; r++) {
      auto mm = [&](int e, int m) { wgmma_rs_n32(acc[e], fa[m][0], fa[m][1], fa[m][2], fa[m][3], db + (int64_t)(32 * e - 16 * m), m != 0); };
      mm(7, r);
      if (r < 14) mm(6, r); else mm(0, r - 14);
      if (r < 12) mm(5, r); else mm(1, r - 12);
      if (r < 10) mm(4, r); else mm(2, r - 10);
      if ((r & 1) == 0) mm(3, r >> 1);
      if (r == CONV_ARRIVE && (i + 1 < NCH)) named_arrive(PP_BAR + (w ^ 1), 256);
    }
    wg_commit();
    PACC(t1, c1);
    PCLK(c2);
    wg_wait<0>();
    PACC(t2, c2);
#pragma unroll
    for (int e = 0; e < NE; e++) reg_fence(acc[e]);
#pragma unroll
    for (int m = 0; m < 16; m++) reg_fence(fa[m]);
    if (lane == 0) mbar_arrive(bar_addr(sb, B_EMPTY + i % NS));
    PCLK(c3);
    PACC(t3, c3);
    PCLK(c4);
    mbar_wait(bar_addr(sb, B_PEMPTY + i % NP), ((i / NP) & 1) ^ 1);
    PACC(t4, c4);
    PCLK(c5);
    const uint32_t pa = sb + (i % NP) * 4 * PART + poff;
#pragma unroll
    for (int e = 0; e < 8; e++) {
      uint32_t u[4];
#pragma unroll
      for (int j = 0; j < 4; j++) {
        const int T = 4 * e + j, U = T - 1;
        constexpr int MK = (1 << LT) - 1;
        float lo = acc[T >> LT][4 * (T & MK)], hi = acc[T >> LT][4 * (T & MK) + 1];
        if (T > 0) { lo += acc[U >> LT][4 * (U & MK) + 2]; hi += acc[U >> LT][4 * (U & MK) + 3]; }
        u[j] = pack_bf16(lo, hi);
      }
      asm volatile("stmatrix.sync.aligned.m8n8.x4.trans.shared.b16 [%0], {%1, %2, %3, %4};" :: "r"(pa + e * 512), "r"(u[0]), "r"(u[1]), "r"(u[2]), "r"(u[3]) : "memory");
    }
    if (i + 2 < NCH) load_a(i + 2);
    fence_async_smem();
    warp_arrive(bar_addr(sb, B_PFULL + i % NP), lane);
    PACC(t5, c5);
  }
  if (threadIdx.x == 128) { PT(9); GT(13); }
}

__device__ __forceinline__ void init(const Params& p, uint32_t sb, int cidx) {
  if (threadIdx.x < NS * 32) {
    const uint32_t s = threadIdx.x >> 5, r = threadIdx.x & 31;
    sts16(sb + s * SSLOT + r * 16, 0, 0, 0, 0);
    if (r < 28) sts16(sb + s * SSLOT + (r < 24 ? 512 + r * 16 : HE - 64 + (r - 24) * 16), 0, 0, 0, 0);
  } else {
    const uint32_t t = threadIdx.x - NS * 32;
    if (t < NP * 24) sts16(sb + OFF_P + (t / 6) * PART + (t % 6) * 16, 0, 0, 0, 0);
    if (t < NCH) {
      const uint32_t d = (uint32_t)__ldg(reinterpret_cast<const unsigned short*>(p.a_D + channel(cidx, t))) * 0x10001u;
      asm volatile("st.shared.u32 [%0], %1;" :: "r"(sb + OFF_D + t * 4), "r"(d) : "memory");
    }
  }
  if (threadIdx.x == 0) {
    for (int i = 0; i < NS; i++) { mbar_init(bar_addr(sb, B_FULL + i), 1); mbar_init(bar_addr(sb, B_EMPTY + i), 4); }
    for (int i = 0; i < NP; i++) { mbar_init(bar_addr(sb, B_PFULL + i), 4); mbar_init(bar_addr(sb, B_PEMPTY + i), 1); }
  }
  fence_async_smem();
}

__device__ __forceinline__ void side_prepare(const Params& p, int cta, int rd) {
  const int lane = threadIdx.x & 31, t0 = 16 * cta + 8 * (lane & 1);
  if (EXP_SIDE & 16) { if (lane == 0) flag_signal_after_bulk(flag_at(g_flags.x_ready, rd)); return; }
#pragma unroll 1
  for (int ch = 64 * rd + (lane & ~1); ch < 64 * rd + 64; ch += 32) {
    const uint4 sv = __ldg(at<const uint4>(p.a_shift, ch * 8));
    const uint32_t* kp = at<const uint32_t>(p.a_k, (t0 * DA + ch) * 2);
    const uint32_t* vp = at<const uint32_t>(p.a_v, (t0 * DA + ch) * 2);
    uint32_t k0 = 0, k1 = 0, k2 = 0, kk[8], x[8];
    if (t0 > 0) { k0 = __ldg(kp - 3 * (DA / 2)); k1 = __ldg(kp - 2 * (DA / 2)); k2 = __ldg(kp - DA / 2); }
#pragma unroll
    for (int i = 0; i < 8; i++) { kk[i] = __ldg(kp + i * (DA / 2)); x[i] = __ldg(vp + i * (DA / 2)); }
    const uint32_t sh0 = __byte_perm(sv.x, sv.z, 0x5410), sh1 = __byte_perm(sv.x, sv.z, 0x7632);
    const uint32_t sh2 = __byte_perm(sv.y, sv.w, 0x5410), sh3 = __byte_perm(sv.y, sv.w, 0x7632);
#pragma unroll
    for (int i = 0; i < 8; i++) {
      uint32_t ks = bmul(k0, sh3);
      ks = badd(ks, bmul(k1, sh2)); ks = badd(ks, bmul(k2, sh1)); ks = badd(ks, bmul(kk[i], sh0));
      x[i] = bmul(ks, x[i]);
      k0 = k1; k1 = k2; k2 = kk[i];
    }
    uint4* dst = at<uint4>(g_xs, ch * 4096 + t0 * 2);
    if ((EXP_SIDE & 4) && (x[0] ^ x[1] ^ x[2] ^ x[3] ^ x[4] ^ x[5] ^ x[6] ^ x[7]) != 0x12345) continue;
    dst[0]   = make_uint4(__byte_perm(x[7], x[6], 0x5410), __byte_perm(x[5], x[4], 0x5410), __byte_perm(x[3], x[2], 0x5410), __byte_perm(x[1], x[0], 0x5410));
    dst[256] = make_uint4(__byte_perm(x[7], x[6], 0x7632), __byte_perm(x[5], x[4], 0x7632), __byte_perm(x[3], x[2], 0x7632), __byte_perm(x[1], x[0], 0x7632));
  }
  if (!(EXP_SIDE & 8)) {
    const int hc = 64 * rd + (cta >> 1), r0 = (cta & 1) * 128 + lane;
    const uint4* src = at<const uint4>(p.a_ssmk, hc * 4096 + r0 * 16);
    uint4* dst = at<uint4>(g_ho, hc * HO_STRIDE + r0 * 16);
    uint4 w[4];
    uint32_t nx[4];
#pragma unroll
    for (int i = 0; i < 4; i++) { w[i] = __ldg(src + 32 * i); nx[i] = r0 + 32 * i < 255 ? __ldg(reinterpret_cast<const uint32_t*>(src + 32 * i + 1)) : 0u; }
#pragma unroll
    for (int i = 0; i < 4; i++)
      dst[32 * i + 2] = make_uint4(__byte_perm(w[i].x, w[i].y, 0x5432), __byte_perm(w[i].y, w[i].z, 0x5432), __byte_perm(w[i].z, w[i].w, 0x5432), __byte_perm(w[i].w, nx[i], 0x5432));
    const uint32_t h0 = __shfl_sync(0xffffffffu, w[0].x, 0);
    if (r0 < 2) dst[0] = make_uint4(0, 0, 0, r0 ? h0 << 16 : 0u);
  }
  __syncwarp();
  if (lane == 0) { if (EXP_SIDE & 2) flag_signal_after_bulk(flag_at(g_flags.x_ready, rd)); else flag_signal(flag_at(g_flags.x_ready, rd)); }
}
__device__ __forceinline__ void side_finish(const Params& p, int cta, int rd) {
  const int lane = threadIdx.x & 31, t0 = 16 * cta + 8 * (lane & 1);
#pragma unroll 1
  for (int ch = 64 * rd + (lane & ~1); ch < 64 * rd + 64; ch += 32) {
    const uint4* src = at<const uint4>(g_xs, ch * 4096 + t0 * 2);
    const uint32_t* qp = at<const uint32_t>(p.a_q, (t0 * DA + ch) * 2);
    uint32_t* op = at<uint32_t>(p.out, (t0 * OUTW + ch) * 2);
    const uint4 z0 = __ldcg(src), z1 = __ldcg(src + 256);
    uint32_t q[8];
#pragma unroll
    for (int i = 0; i < 8; i++) q[i] = __ldg(qp + i * (DA / 2));
    const uint32_t a[4] = {z0.w, z0.z, z0.y, z0.x}, b[4] = {z1.w, z1.z, z1.y, z1.x};
#pragma unroll
    for (int i = 0; i < 4; i++) {
      op[(2 * i) * (OUTW / 2)]     = bmul(q[2 * i], __byte_perm(a[i], b[i], 0x7632));
      op[(2 * i + 1) * (OUTW / 2)] = bmul(q[2 * i + 1], __byte_perm(a[i], b[i], 0x5410));
    }
  }
}
__device__ __forceinline__ void side_work(const Params& p, int cta, unsigned epoch) {
#pragma unroll 1
  for (int rd = -SIDE_AHEAD; rd < 7; rd++) {
    if (rd >= 0) {
      if ((threadIdx.x & 31) == 0) flag_wait_slow(flag_at(g_flags.z_ready, rd), 3 * NCONV, epoch);
      __syncwarp();
    }
    if (rd + SIDE_AHEAD < 7) side_prepare(p, cta, rd + SIDE_AHEAD);
    if (rd >= 0 && !(EXP_SIDE & 1)) side_finish(p, cta, rd);
  }
}
}

__global__ void __cluster_dims__(2, 1, 1) __launch_bounds__(NTHREADS, 1)
concat_heads__ssm_conv_h3__compressed_kv_cla__prompt_kernel(const __grid_constant__ Params p) {
  extern __shared__ uint8_t smem_raw[];
  const uint32_t sb = (smem_u32(smem_raw) + 1023) & ~1023u;
  const int warp = __shfl_sync(0xffffffffu, threadIdx.x >> 5, 0);
  const int wg = warp >> 2;
  const int cta = blockIdx.x;
  const bool attn = cta < NMAIN;
  int h, u;
  {
    const int c = cta >> 1;
    if (c < 4) { h = 15; u = c; }
    else if (c < 36) { h = (c - 4) & 7; u = (c - 4) >> 3; }
    else { h = 8 + (c - 36) % 7; u = (c - 36) / 7; }
  }
  const int j = 2 * u + (cta & 1);
  if (!attn) ssm::init(p, sb, cta - NMAIN);
  if (attn && threadIdx.x == 0) {
    for (int i = 0; i < 4; i++) { mbar_init(bar_addr(sb, B_P1_FULL + i), 1); mbar_init(bar_addr(sb, B_P1_EMPTY + i), 16); }
    for (int i = 0; i < NSLOT; i++) {
      mbar_init(bar_addr(sb, B_RG_FULL + i), 1); mbar_init(bar_addr(sb, B_RG_EMPTY + i), 16); mbar_init(bar_addr(sb, B_PFREE + i), 1);
    }
    for (int i = 0; i < 2; i++) { mbar_init(bar_addr(sb, B_ST_FULL + i), 4); mbar_init(bar_addr(sb, B_ST_EMPTY + i), 1); }
    mbar_init(bar_addr(sb, B_DONE), 11);
    mbar_init(bar_addr(sb, B_PART), 1); mbar_init(bar_addr(sb, B_PART + 1), 1);
    for (int i = 0; i < 4; i++) { mbar_init(bar_addr(sb, B_S2_FULL + i), 4); mbar_init(bar_addr(sb, B_S2_EMPTY + i), 1); }
    for (int i = 0; i < 2; i++) { mbar_init(bar_addr(sb, B_QFREE + i), 4); mbar_init(bar_addr(sb, B_CTXF + i), 1); }
    asm volatile("fence.mbarrier_init.release.cluster;" ::: "memory");
  }
  if (attn && threadIdx.x == 32) {
    prefetch_map(&p.ckv); prefetch_map(&p.wuk); prefetch_map(&p.wuv); prefetch_map(&p.x); prefetch_map(&p.wq);
    prefetch_map(&p.kv); prefetch_map(&p.part); prefetch_map(&p.wo); prefetch_map(&p.ctx);
  }
  __syncwarp();
  asm volatile("barrier.cluster.arrive.release.aligned;" ::: "memory");
  if (attn && threadIdx.x == 0) {
    for (int k = 0; k < EARLY_LD; k++) {
      const uint32_t full = bar_addr(sb, B_P1_FULL + k), dst = sb + k * P1_STAGE;
      mbar_expect_tx(full, P1_STAGE);
      tma_ld2(dst, &p.ckv, full, k * 64, p1_rows(h, j, 0) * 128);
      load_tile4(dst + 16384, &p.wuk, full, k * 64, p1_head(h, 0) * 4, j & 1, false, pol(HINTS & 1));
    }
  }
  __syncwarp();
  asm volatile("barrier.cluster.wait.acquire.aligned;" ::: "memory");

  const int lane = threadIdx.x & 31;
  if (wg == 0) {
    if (!attn) {
      asm volatile("setmaxnreg.dec.sync.aligned.u32 40;");
      if (lane == 0) {
        if (warp == 0) { ssm::producer(p, sb, cta - NMAIN, load_epoch()); cta_done(32); }
        else ssm::reducer(sb, cta - NMAIN, warp - 1);
        if (warp == 1) GT(14);
      }
      return;
    }
    asm volatile("setmaxnreg.dec.sync.aligned.u32 40;");
    if (warp == 0) {
      if (lane == 0) { producer_main(p, sb, h, j); mbar_arrive(bar_addr(sb, B_DONE)); }
    } else if (warp < 3) {
      storer_main(p, sb, h, j, warp - 1);
      if (lane == 0) mbar_arrive(bar_addr(sb, B_DONE));
    } else {
      const unsigned epoch = load_epoch();
      ssm::side_work(p, h * 8 + j, epoch);
      if (lane == 0) { GT(57); mbar_wait(bar_addr(sb, B_DONE), 0); cta_done(1); }
    }
  } else {
    if (!attn) {
      asm volatile("setmaxnreg.inc.sync.aligned.u32 232;");
      if (p.out != nullptr) ssm::mma_warpgroup(sb, wg - 1);
      return;
    }
    asm volatile("setmaxnreg.inc.sync.aligned.u32 232;");
    if (p.out != nullptr) {
      consumer_main(p, sb, h, j, wg - 1);
      __syncwarp();
      if (lane == 0) mbar_arrive(bar_addr(sb, B_DONE));
    }
  }
}

typedef CUresult (*EncodeTiledFn)(CUtensorMap*, CUtensorMapDataType, cuuint32_t, void*, const cuuint64_t*, const cuuint64_t*,
                                  const cuuint32_t*, const cuuint32_t*, CUtensorMapInterleave, CUtensorMapSwizzle,
                                  CUtensorMapL2promotion, CUtensorMapFloatOOBfill);

void make_map(EncodeTiledFn enc, CUtensorMap* m, const void* ptr, int rank, const uint64_t* dims, const uint64_t* strides, const uint32_t* box) {
  cuuint64_t d[3], s[2]; cuuint32_t b[3], e[3] = {1, 1, 1};
  for (int i = 0; i < rank; i++) { d[i] = dims[i]; b[i] = box[i]; if (i) s[i - 1] = strides[i - 1]; }
  enc(m, CU_TENSOR_MAP_DATA_TYPE_BFLOAT16, rank, const_cast<void*>(ptr), d, s, b, e, CU_TENSOR_MAP_INTERLEAVE_NONE,
      CU_TENSOR_MAP_SWIZZLE_128B, CU_TENSOR_MAP_L2_PROMOTION_L2_256B, CU_TENSOR_MAP_FLOAT_OOB_FILL_NONE);
}
void map2(EncodeTiledFn enc, CUtensorMap* m, const void* ptr, uint64_t cols, uint64_t rows, uint32_t bc, uint32_t br) {
  const uint64_t dims[2] = {cols, rows}, st[1] = {cols * 2}; const uint32_t box[2] = {bc, br};
  make_map(enc, m, ptr, 2, dims, st, box);
}
void map2_plain(EncodeTiledFn enc, CUtensorMap* m, const void* ptr, uint64_t cols, uint64_t rows, uint32_t bc, uint32_t br) {
  cuuint64_t d[2] = {cols, rows}, st[1] = {cols * 2}; cuuint32_t b[2] = {bc, br}, e[2] = {1, 1};
  enc(m, CU_TENSOR_MAP_DATA_TYPE_BFLOAT16, 2, const_cast<void*>(ptr), d, st, b, e, CU_TENSOR_MAP_INTERLEAVE_NONE,
      CU_TENSOR_MAP_SWIZZLE_NONE, CU_TENSOR_MAP_L2_PROMOTION_L2_128B, CU_TENSOR_MAP_FLOAT_OOB_FILL_NONE);
}
void map3(EncodeTiledFn enc, CUtensorMap* m, const void* ptr, uint64_t rows, uint32_t nblk) {
  const uint64_t dims[3] = {64, rows, 64}, st[2] = {8192, 128}; const uint32_t box[3] = {64, 64, nblk};
  make_map(enc, m, ptr, 3, dims, st, box);
}

}

extern "C" void kernel_launch(void* const* d_in, const int* in_sizes, int n_in, void* d_out, int out_size) {
  (void)in_sizes; (void)n_in; (void)out_size;
  static EncodeTiledFn enc = nullptr;
  static void *kv_ptr = nullptr, *ctx_ptr = nullptr, *acc_ptr = nullptr;
  if (!enc) {
    void* fn = nullptr; cudaDriverEntryPointQueryResult qr;
    cudaGetDriverEntryPoint("cuTensorMapEncodeTiled", &fn, cudaEnableDefault, &qr);
    enc = (EncodeTiledFn)fn;
    cudaGetSymbolAddress(&kv_ptr, g_kv);
    cudaGetSymbolAddress(&ctx_ptr, g_part);
    cudaGetSymbolAddress(&acc_ptr, g_ctx);
    cudaFuncSetAttribute(concat_heads__ssm_conv_h3__compressed_kv_cla__prompt_kernel, cudaFuncAttributeMaxDynamicSharedMemorySize, SMEM_BYTES);
  }
  Params p;
  p.a_q = (const bf16*)d_in[0]; p.a_k = (const bf16*)d_in[1]; p.a_v = (const bf16*)d_in[2];
  p.a_shift = (const bf16*)d_in[3]; p.a_ssmk = (const bf16*)d_in[4]; p.a_D = (const bf16*)d_in[5];
  p.out = (bf16*)d_out;
  map2(enc, &p.x, d_in[6], DM, SEQ, 64, 128);
  map2(enc, &p.ckv, d_in[7], DC, SEQ, 64, 128);
  map3(enc, &p.wq, d_in[8], DM, 2);
  map3(enc, &p.wuk, d_in[9], DC, 2);
  map3(enc, &p.wuv, d_in[10], DC, 2);
  map2(enc, &p.wo, d_in[11], DM, NH * HD, 64, 128);
  {
    const uint64_t dims[3] = {64, 2 * NH * SEQ, 4}, st[2] = {HD * 2, 128}; const uint32_t box[3] = {64, 64, 2};
    make_map(enc, &p.kv, kv_ptr, 3, dims, st, box);
  }
  map2(enc, &p.part, ctx_ptr, DM, 8 * SEQ, 64, 64);
  {
    const uint64_t dims[3] = {64, NMAIN * 128, 4}, st[2] = {HD * 2, 128}; const uint32_t box[3] = {64, 64, 4};
    make_map(enc, &p.ctx, acc_ptr, 3, dims, st, box);
  }
  concat_heads__ssm_conv_h3__compressed_kv_cla__prompt_kernel<<<NCTA, NTHREADS, SMEM_BYTES>>>(p);
}
```

```cpp
#include <cuda_runtime.h>
#include <cuda_bf16.h>
#include <cuda.h>
#include <stdint.h>

namespace {

typedef __nv_bfloat16 bf16;

constexpr int SEQ  = 2048;
constexpr int DA   = 448;
constexpr int NH   = 16;
constexpr int HD   = 256;
constexpr int DM   = 448;
constexpr int DC   = 1024;
constexpr int OUTW = DA + DM;
constexpr int NMAIN = 128;
constexpr int NCONV = 4;
constexpr int NCTA  = NMAIN + NCONV;
constexpr int LOG_DONE = 8;
constexpr int NTHREADS = 384;

__device__ __align__(1024) bf16 g_kv[2ull * SEQ * NH * HD];
__device__ __align__(1024) bf16 g_qc[(size_t)NMAIN * 128 * HD];
__device__ __align__(128) uint8_t g_xs[DA * SEQ * 2];
constexpr uint32_t HO_STRIDE = 4224;
__device__ __align__(128) uint8_t g_ho[DA * HO_STRIDE];
struct alignas(128) Flag { unsigned v; unsigned pad[31]; };
struct Flags {
  Flag kv_ready[NH];
  Flag ctx_ready[NMAIN * 2];
  Flag x_ready[7];
  Flag z_ready[7];
  Flag zero_ready[16];
  alignas(128) unsigned long long done;
};
__device__ Flags g_flags;
#define TS(i)
#define TDUMP()
#define GT(i)
#define PT(i)
#define PCLK(var)
#define PACC(acc, t0)

struct alignas(64) Params {
  CUtensorMap ckv;
  CUtensorMap wuk;
  CUtensorMap wuv;
  CUtensorMap x;
  CUtensorMap wq;
  CUtensorMap kv;
  CUtensorMap o;
  CUtensorMap qc;
  CUtensorMap wo;
  const bf16 *a_q, *a_k, *a_v, *a_shift, *a_ssmk, *a_D;
  bf16* out;
};

constexpr uint32_t SLOT     = 32768;
constexpr int      NSLOT    = 5;
constexpr uint32_t QREG     = 163840;
constexpr uint32_t BARS     = 229376;
constexpr uint32_t SMEM_BYTES = BARS + 1024 + 1024;
enum : uint32_t {
  B_FULL = 0, B_EMPTY = 5, B_XFREE = 10, B_ST_KV = 12, B_ST_Q = 14, B_ST_CTX = 16, B_KVOK = 18, B_DONE = 19, B_QFREE = 20, B_QFULL = 22,
  B_S2_FULL = 24, B_S2_EMPTY = 32
};
constexpr int P1_STEPS = 4 * 16 + 2 * 7, P1_XS = P1_STEPS - 2;

template <typename T> __device__ __forceinline__ T* at(const void* base, uint32_t off) {
  asm volatile("" : "+r"(off));
  return reinterpret_cast<T*>(const_cast<char*>(static_cast<const char*>(base)) + off);
}
__device__ __forceinline__ unsigned* flag_at(Flag* f, uint32_t i) { return at<unsigned>(f, i * (uint32_t)sizeof(Flag)); }
__device__ __forceinline__ uint32_t smem_u32(const void* p) { return (uint32_t)__cvta_generic_to_shared(p); }
__device__ __forceinline__ void mbar_init(uint32_t bar, uint32_t cnt) {
  asm volatile("mbarrier.init.shared::cta.b64 [%0], %1;" :: "r"(bar), "r"(cnt) : "memory");
}
__device__ __forceinline__ void mbar_expect_tx(uint32_t bar, uint32_t bytes) {
  asm volatile("mbarrier.arrive.expect_tx.shared::cta.b64 _, [%0], %1;" :: "r"(bar), "r"(bytes) : "memory");
}
__device__ __forceinline__ void mbar_arrive(uint32_t bar) {
  asm volatile("mbarrier.arrive.shared::cta.b64 _, [%0];" :: "r"(bar) : "memory");
}
__device__ __forceinline__ void mbar_arrive_n(uint32_t bar, uint32_t n) {
  asm volatile("mbarrier.arrive.shared::cta.b64 _, [%0], %1;" :: "r"(bar), "r"(n) : "memory");
}
__device__ __forceinline__ void mbar_arrive_remote(uint32_t bar, uint32_t cta) {
  asm volatile("{\n.reg .b32 ra;\nmapa.shared::cluster.u32 ra, %0, %1;\n"
               "mbarrier.arrive.shared::cluster.b64 _, [ra];\n}" :: "r"(bar), "r"(cta) : "memory");
}
__device__ __forceinline__ bool mbar_try(uint32_t bar, uint32_t parity) {
  uint32_t ok;
  asm volatile("{\n.reg .pred p;\nmbarrier.try_wait.parity.shared::cta.b64 p, [%1], %2;\nselp.u32 %0, 1, 0, p;\n}"
               : "=r"(ok) : "r"(bar), "r"(parity) : "memory");
  return ok;
}
constexpr uint32_t SPIN_LIMIT = 1u << 24;
__device__ __forceinline__ void mbar_wait(uint32_t bar, uint32_t parity) {
  if (mbar_try(bar, parity)) return;
  uint32_t n = 0;
  while (!mbar_try(bar, parity)) { if (++n > SPIN_LIMIT) __trap(); }
}
__device__ __forceinline__ unsigned load_epoch() {
  unsigned long long d; asm volatile("ld.relaxed.gpu.global.u64 %0, [%1];" : "=l"(d) : "l"(&g_flags.done) : "memory");
  return (unsigned)(d >> LOG_DONE);
}
__device__ __forceinline__ void flag_wait(const unsigned* f, unsigned count, unsigned epoch) {
  const unsigned target = (epoch + 1) * count;
  uint32_t n = 0;
  while (true) {
    unsigned v;
    asm volatile("ld.acquire.gpu.global.u32 %0, [%1];" : "=r"(v) : "l"(f) : "memory");
    if ((int)(v - target) >= 0) break;
    if (++n > SPIN_LIMIT) __trap();
    __nanosleep(20);
  }
}
__device__ __forceinline__ void flag_wait_slow(const unsigned* f, unsigned count, unsigned epoch) {
  const unsigned target = (epoch + 1) * count;
  uint32_t n = 0;
  while (true) {
    unsigned v;
    asm volatile("ld.acquire.gpu.global.u32 %0, [%1];" : "=r"(v) : "l"(f) : "memory");
    if ((int)(v - target) >= 0) break;
    if (++n > SPIN_LIMIT / 16) __trap();
    __nanosleep(1000);
  }
}
__device__ __forceinline__ void cta_done(unsigned long long n) { asm volatile("red.relaxed.gpu.global.add.u64 [%0], %1;" :: "l"(&g_flags.done), "l"(n) : "memory"); }
__device__ __forceinline__ void flag_wait_fast(const unsigned* f, unsigned count, unsigned epoch) {
  const unsigned target = (epoch + 1) * count;
  uint32_t n = 0;
  while (true) {
    unsigned v;
    asm volatile("ld.acquire.gpu.global.u32 %0, [%1];" : "=r"(v) : "l"(f) : "memory");
    if ((int)(v - target) >= 0) break;
    if (++n > SPIN_LIMIT) __trap();
  }
}
__device__ __forceinline__ void fence_async_all() { asm volatile("fence.proxy.async;" ::: "memory"); }
__device__ __forceinline__ void flag_signal(unsigned* f) {
  asm volatile("fence.acq_rel.gpu;" ::: "memory");
  asm volatile("red.relaxed.gpu.global.add.u32 [%0], 1;" :: "l"(f) : "memory");
}
__device__ __forceinline__ void flag_signal_after_bulk(unsigned* f) {
  asm volatile("red.relaxed.gpu.global.add.u32 [%0], 1;" :: "l"(f) : "memory");
}
__device__ __forceinline__ void fence_async_smem() { asm volatile("fence.proxy.async.shared::cta;" ::: "memory"); }
#define HINTS 0
constexpr uint64_t POL_NORMAL = 0x1000000000000000ull, POL_FIRST = 0x12F0000000000000ull;
__device__ __forceinline__ constexpr uint64_t pol(bool first) { return first ? POL_FIRST : POL_NORMAL; }
__device__ __forceinline__ void tma_ld2(uint32_t dst, const CUtensorMap* m, uint32_t bar, int c0, int c1, uint64_t pl = POL_NORMAL) {
  asm volatile("cp.async.bulk.tensor.2d.shared::cluster.global.mbarrier::complete_tx::bytes.L2::cache_hint [%0], [%1, {%3, %4}], [%2], %5;"
               :: "r"(dst), "l"(m), "r"(bar), "r"(c0), "r"(c1), "l"(pl) : "memory");
}
__device__ __forceinline__ void tma_ld3(uint32_t dst, const CUtensorMap* m, uint32_t bar, int c0, int c1, int c2, uint64_t pl = POL_NORMAL) {
  asm volatile("cp.async.bulk.tensor.3d.shared::cluster.global.mbarrier::complete_tx::bytes.L2::cache_hint [%0], [%1, {%3, %4, %5}], [%2], %6;"
               :: "r"(dst), "l"(m), "r"(bar), "r"(c0), "r"(c1), "r"(c2), "l"(pl) : "memory");
}
__device__ __forceinline__ void tma_ld3_mc(uint32_t dst, const CUtensorMap* m, uint32_t bar, int c0, int c1, int c2, uint64_t pl = POL_NORMAL) {
  asm volatile("cp.async.bulk.tensor.3d.shared::cluster.global.mbarrier::complete_tx::bytes.multicast::cluster.L2::cache_hint [%0], [%1, {%3, %4, %5}], [%2], %6, %7;"
               :: "r"(dst), "l"(m), "r"(bar), "r"(c0), "r"(c1), "r"(c2), "h"((uint16_t)3), "l"(pl) : "memory");
}
__device__ __forceinline__ void bulk_ld(uint32_t dst, const void* src, uint32_t bytes, uint32_t bar) {
  asm volatile("cp.async.bulk.shared::cluster.global.mbarrier::complete_tx::bytes [%0], [%1], %2, [%3];"
               :: "r"(dst), "l"(src), "r"(bytes), "r"(bar) : "memory");
}
__device__ __forceinline__ void tma_st3(const CUtensorMap* m, uint32_t src, int c0, int c1, int c2) {
  asm volatile("cp.async.bulk.tensor.3d.global.shared::cta.bulk_group.L2::cache_hint [%0, {%2, %3, %4}], [%1], %5;"
               :: "l"(m), "r"(src), "r"(c0), "r"(c1), "r"(c2), "l"(pol(HINTS & 1024)) : "memory");
}
__device__ __forceinline__ void tma_ld2_mc(uint32_t dst, const CUtensorMap* m, uint32_t bar, int c0, int c1, uint64_t pl = POL_NORMAL) {
  asm volatile("cp.async.bulk.tensor.2d.shared::cluster.global.mbarrier::complete_tx::bytes.multicast::cluster.L2::cache_hint [%0], [%1, {%3, %4}], [%2], %5, %6;"
               :: "r"(dst), "l"(m), "r"(bar), "r"(c0), "r"(c1), "h"((uint16_t)3), "l"(pl) : "memory");
}
__device__ __forceinline__ void tma_ld5_mc(uint32_t dst, const CUtensorMap* m, uint32_t bar, int c0, int c4, uint64_t pl = POL_NORMAL) {
  asm volatile("cp.async.bulk.tensor.5d.shared::cluster.global.mbarrier::complete_tx::bytes.multicast::cluster.L2::cache_hint [%0], [%1, {%3, %7, %7, %7, %4}], [%2], %5, %6;"
               :: "r"(dst), "l"(m), "r"(bar), "r"(c0), "r"(c4), "h"((uint16_t)3), "l"(pl), "r"(0) : "memory");
}
__device__ __forceinline__ void tma_st2(const CUtensorMap* m, uint32_t src, int c0, int c1) {
  asm volatile("cp.async.bulk.tensor.2d.global.shared::cta.bulk_group [%0, {%2, %3}], [%1];"
               :: "l"(m), "r"(src), "r"(c0), "r"(c1) : "memory");
}
__device__ __forceinline__ void tma_red2(const CUtensorMap* m, uint32_t src, int c0, int c1) {
  asm volatile("cp.reduce.async.bulk.tensor.2d.global.shared::cta.add.bulk_group [%0, {%2, %3}], [%1];"
               :: "l"(m), "r"(src), "r"(c0), "r"(c1) : "memory");
}
__device__ __forceinline__ void bulk_commit() { asm volatile("cp.async.bulk.commit_group;" ::: "memory"); }
__device__ __forceinline__ void bulk_wait_read() { asm volatile("cp.async.bulk.wait_group.read 0;" ::: "memory"); }
__device__ __forceinline__ void bulk_wait_all() { asm volatile("cp.async.bulk.wait_group 0;" ::: "memory"); }
__device__ __forceinline__ void prefetch_map(const CUtensorMap* m) { asm volatile("prefetch.tensormap [%0];" :: "l"(m) : "memory"); }
__device__ __forceinline__ void wg_fence() { asm volatile("wgmma.fence.sync.aligned;" ::: "memory"); }
__device__ __forceinline__ void wg_commit() { asm volatile("wgmma.commit_group.sync.aligned;" ::: "memory"); }
template <int N> __device__ __forceinline__ void wg_wait() { asm volatile("wgmma.wait_group.sync.aligned %0;" :: "n"(N) : "memory"); }
template <int N> __device__ __forceinline__ void reg_fence(float (&d)[N]) {
#pragma unroll
  for (int i = 0; i < N; i++) asm volatile("" : "+f"(d[i]) :: "memory");
}
template <int N> __device__ __forceinline__ void reg_fence(uint32_t (&d)[N]) {
#pragma unroll
  for (int i = 0; i < N; i++) asm volatile("" : "+r"(d[i]) :: "memory");
}
__device__ __forceinline__ uint32_t fresh_tid() { uint32_t t; asm volatile("mov.u32 %0, %%tid.x;" : "=r"(t)); return t; }
__device__ __forceinline__ uint32_t lane_base16() {
  const uint32_t t = fresh_tid(), lane = t & 31, wq = (t >> 5) & 3;
  return (16 * wq + (lane & 7) + 8 * ((lane >> 3) & 1)) * 128 + (((lane >> 4) ^ (lane & 7)) << 4);
}
__device__ __forceinline__ void named_sync(int id, int n) { asm volatile("bar.sync %0, %1;" :: "r"(id), "r"(n) : "memory"); }
__device__ __forceinline__ void named_arrive(int id, int n) { asm volatile("bar.arrive %0, %1;" :: "r"(id), "r"(n) : "memory"); }
__device__ __forceinline__ uint32_t pack_bf16(float lo, float hi) {
  uint32_t r; asm("cvt.rn.bf16x2.f32 %0, %1, %2;" : "=r"(r) : "f"(hi), "f"(lo)); return r;
}
__device__ __forceinline__ float ex2(float x) { float y; asm("ex2.approx.ftz.f32 %0, %1;" : "=f"(y) : "f"(x)); return y; }
__device__ __forceinline__ void stsm4(uint32_t addr, uint32_t a, uint32_t b, uint32_t c, uint32_t d) {
  asm volatile("stmatrix.sync.aligned.m8n8.x4.shared.b16 [%0], {%1, %2, %3, %4};" :: "r"(addr), "r"(a), "r"(b), "r"(c), "r"(d) : "memory");
}
__device__ __forceinline__ uint64_t mk_desc(uint32_t addr, uint32_t lbo, uint32_t sbo) {
  return (uint64_t)(((addr & 0x3FFFF) >> 4) | ((lbo >> 4) << 16)) | ((uint64_t)((sbo >> 4) | (1u << 30)) << 32);
}
__device__ __forceinline__ uint64_t desc_k(uint32_t addr)  { return mk_desc(addr, 16, 1024); }
__device__ __forceinline__ uint64_t desc_mn(uint32_t addr) { return mk_desc(addr, 8192, 1024); }
__device__ __forceinline__ uint64_t desc_add(uint64_t d, uint32_t bytes) { return d + (bytes >> 4); }

__device__ __forceinline__ void wgmma_ss_n256_tb(float (&d)[128], uint64_t da, uint64_t db, int sd) {
  asm volatile("{\n.reg .pred p;\nsetp.ne.b32 p, %130, 0;\n"
    "wgmma.mma_async.sync.aligned.m64n256k16.f32.bf16.bf16 "
    "{%0, %1, %2, %3, %4, %5, %6, %7, %8, %9, %10, %11, %12, %13, %14, %15, "
    "%16, %17, %18, %19, %20, %21, %22, %23, %24, %25, %26, %27, %28, %29, %30, %31, "
    "%32, %33, %34, %35, %36, %37, %38, %39, %40, %41, %42, %43, %44, %45, %46, %47, "
    "%48, %49, %50, %51, %52, %53, %54, %55, %56, %57, %58, %59, %60, %61, %62, %63, "
    "%64, %65, %66, %67, %68, %69, %70, %71, %72, %73, %74, %75, %76, %77, %78, %79, "
    "%80, %81, %82, %83, %84, %85, %86, %87, %88, %89, %90, %91, %92, %93, %94, %95, "
    "%96, %97, %98, %99, %100, %101, %102, %103, %104, %105, %106, %107, %108, %109, %110, %111, "
    "%112, %113, %114, %115, %116, %117, %118, %119, %120, %121, %122, %123, %124, %125, %126, %127}, "
    "%128, %129, p, 1, 1, 0, 1;\n}"
    : "+f"(d[0]), "+f"(d[1]), "+f"(d[2]), "+f"(d[3]), "+f"(d[4]), "+f"(d[5]), "+f"(d[6]), "+f"(d[7]),
      "+f"(d[8]), "+f"(d[9]), "+f"(d[10]), "+f"(d[11]), "+f"(d[12]), "+f"(d[13]), "+f"(d[14]), "+f"(d[15]),
      "+f"(d[16]), "+f"(d[17]), "+f"(d[18]), "+f"(d[19]), "+f"(d[20]), "+f"(d[21]), "+f"(d[22]), "+f"(d[23]),
      "+f"(d[24]), "+f"(d[25]), "+f"(d[26]), "+f"(d[27]), "+f"(d[28]), "+f"(d[29]), "+f"(d[30]), "+f"(d[31]),
      "+f"(d[32]), "+f"(d[33]), "+f"(d[34]), "+f"(d[35]), "+f"(d[36]), "+f"(d[37]), "+f"(d[38]), "+f"(d[39]),
      "+f"(d[40]), "+f"(d[41]), "+f"(d[42]), "+f"(d[43]), "+f"(d[44]), "+f"(d[45]), "+f"(d[46]), "+f"(d[47]),
      "+f"(d[48]), "+f"(d[49]), "+f"(d[50]), "+f"(d[51]), "+f"(d[52]), "+f"(d[53]), "+f"(d[54]), "+f"(d[55]),
      "+f"(d[56]), "+f"(d[57]), "+f"(d[58]), "+f"(d[59]), "+f"(d[60]), "+f"(d[61]), "+f"(d[62]), "+f"(d[63]),
      "+f"(d[64]), "+f"(d[65]), "+f"(d[66]), "+f"(d[67]), "+f"(d[68]), "+f"(d[69]), "+f"(d[70]), "+f"(d[71]),
      "+f"(d[72]), "+f"(d[73]), "+f"(d[74]), "+f"(d[75]), "+f"(d[76]), "+f"(d[77]), "+f"(d[78]), "+f"(d[79]),
      "+f"(d[80]), "+f"(d[81]), "+f"(d[82]), "+f"(d[83]), "+f"(d[84]), "+f"(d[85]), "+f"(d[86]), "+f"(d[87]),
      "+f"(d[88]), "+f"(d[89]), "+f"(d[90]), "+f"(d[91]), "+f"(d[92]), "+f"(d[93]), "+f"(d[94]), "+f"(d[95]),
      "+f"(d[96]), "+f"(d[97]), "+f"(d[98]), "+f"(d[99]), "+f"(d[100]), "+f"(d[101]), "+f"(d[102]), "+f"(d[103]),
      "+f"(d[104]), "+f"(d[105]), "+f"(d[106]), "+f"(d[107]), "+f"(d[108]), "+f"(d[109]), "+f"(d[110]), "+f"(d[111]),
      "+f"(d[112]), "+f"(d[113]), "+f"(d[114]), "+f"(d[115]), "+f"(d[116]), "+f"(d[117]), "+f"(d[118]), "+f"(d[119]),
      "+f"(d[120]), "+f"(d[121]), "+f"(d[122]), "+f"(d[123]), "+f"(d[124]), "+f"(d[125]), "+f"(d[126]), "+f"(d[127])
    : "l"(da), "l"(db), "r"(sd));
}
__device__ __forceinline__ void wgmma_ss_n64(float (&d)[32], uint64_t da, uint64_t db, int sd) {
  asm volatile("{\n.reg .pred p;\nsetp.ne.b32 p, %34, 0;\n"
    "wgmma.mma_async.sync.aligned.m64n64k16.f32.bf16.bf16 "
    "{%0, %1, %2, %3, %4, %5, %6, %7, %8, %9, %10, %11, %12, %13, %14, %15, "
    "%16, %17, %18, %19, %20, %21, %22, %23, %24, %25, %26, %27, %28, %29, %30, %31}, "
    "%32, %33, p, 1, 1, 0, 0;\n}"
    : "+f"(d[0]), "+f"(d[1]), "+f"(d[2]), "+f"(d[3]), "+f"(d[4]), "+f"(d[5]), "+f"(d[6]), "+f"(d[7]),
      "+f"(d[8]), "+f"(d[9]), "+f"(d[10]), "+f"(d[11]), "+f"(d[12]), "+f"(d[13]), "+f"(d[14]), "+f"(d[15]),
      "+f"(d[16]), "+f"(d[17]), "+f"(d[18]), "+f"(d[19]), "+f"(d[20]), "+f"(d[21]), "+f"(d[22]), "+f"(d[23]),
      "+f"(d[24]), "+f"(d[25]), "+f"(d[26]), "+f"(d[27]), "+f"(d[28]), "+f"(d[29]), "+f"(d[30]), "+f"(d[31])
    : "l"(da), "l"(db), "r"(sd));
}
__device__ __forceinline__ void wgmma_rs_n256_tb(float (&d)[128], uint32_t a0, uint32_t a1, uint32_t a2, uint32_t a3, uint64_t db, int sd) {
  asm volatile("{\n.reg .pred p;\nsetp.ne.b32 p, %133, 0;\n"
    "wgmma.mma_async.sync.aligned.m64n256k16.f32.bf16.bf16 "
    "{%0, %1, %2, %3, %4, %5, %6, %7, %8, %9, %10, %11, %12, %13, %14, %15, "
    "%16, %17, %18, %19, %20, %21, %22, %23, %24, %25, %26, %27, %28, %29, %30, %31, "
    "%32, %33, %34, %35, %36, %37, %38, %39, %40, %41, %42, %43, %44, %45, %46, %47, "
    "%48, %49, %50, %51, %52, %53, %54, %55, %56, %57, %58, %59, %60, %61, %62, %63, "
    "%64, %65, %66, %67, %68, %69, %70, %71, %72, %73, %74, %75, %76, %77, %78, %79, "
    "%80, %81, %82, %83, %84, %85, %86, %87, %88, %89, %90, %91, %92, %93, %94, %95, "
    "%96, %97, %98, %99, %100, %101, %102, %103, %104, %105, %106, %107, %108, %109, %110, %111, "
    "%112, %113, %114, %115, %116, %117, %118, %119, %120, %121, %122, %123, %124, %125, %126, %127}, "
    "{%128, %129, %130, %131}, %132, p, 1, 1, 1;\n}"
    : "+f"(d[0]), "+f"(d[1]), "+f"(d[2]), "+f"(d[3]), "+f"(d[4]), "+f"(d[5]), "+f"(d[6]), "+f"(d[7]),
      "+f"(d[8]), "+f"(d[9]), "+f"(d[10]), "+f"(d[11]), "+f"(d[12]), "+f"(d[13]), "+f"(d[14]), "+f"(d[15]),
      "+f"(d[16]), "+f"(d[17]), "+f"(d[18]), "+f"(d[19]), "+f"(d[20]), "+f"(d[21]), "+f"(d[22]), "+f"(d[23]),
      "+f"(d[24]), "+f"(d[25]), "+f"(d[26]), "+f"(d[27]), "+f"(d[28]), "+f"(d[29]), "+f"(d[30]), "+f"(d[31]),
      "+f"(d[32]), "+f"(d[33]), "+f"(d[34]), "+f"(d[35]), "+f"(d[36]), "+f"(d[37]), "+f"(d[38]), "+f"(d[39]),
      "+f"(d[40]), "+f"(d[41]), "+f"(d[42]), "+f"(d[43]), "+f"(d[44]), "+f"(d[45]), "+f"(d[46]), "+f"(d[47]),
      "+f"(d[48]), "+f"(d[49]), "+f"(d[50]), "+f"(d[51]), "+f"(d[52]), "+f"(d[53]), "+f"(d[54]), "+f"(d[55]),
      "+f"(d[56]), "+f"(d[57]), "+f"(d[58]), "+f"(d[59]), "+f"(d[60]), "+f"(d[61]), "+f"(d[62]), "+f"(d[63]),
      "+f"(d[64]), "+f"(d[65]), "+f"(d[66]), "+f"(d[67]), "+f"(d[68]), "+f"(d[69]), "+f"(d[70]), "+f"(d[71]),
      "+f"(d[72]), "+f"(d[73]), "+f"(d[74]), "+f"(d[75]), "+f"(d[76]), "+f"(d[77]), "+f"(d[78]), "+f"(d[79]),
      "+f"(d[80]), "+f"(d[81]), "+f"(d[82]), "+f"(d[83]), "+f"(d[84]), "+f"(d[85]), "+f"(d[86]), "+f"(d[87]),
      "+f"(d[88]), "+f"(d[89]), "+f"(d[90]), "+f"(d[91]), "+f"(d[92]), "+f"(d[93]), "+f"(d[94]), "+f"(d[95]),
      "+f"(d[96]), "+f"(d[97]), "+f"(d[98]), "+f"(d[99]), "+f"(d[100]), "+f"(d[101]), "+f"(d[102]), "+f"(d[103]),
      "+f"(d[104]), "+f"(d[105]), "+f"(d[106]), "+f"(d[107]), "+f"(d[108]), "+f"(d[109]), "+f"(d[110]), "+f"(d[111]),
      "+f"(d[112]), "+f"(d[113]), "+f"(d[114]), "+f"(d[115]), "+f"(d[116]), "+f"(d[117]), "+f"(d[118]), "+f"(d[119]),
      "+f"(d[120]), "+f"(d[121]), "+f"(d[122]), "+f"(d[123]), "+f"(d[124]), "+f"(d[125]), "+f"(d[126]), "+f"(d[127])
    : "r"(a0), "r"(a1), "r"(a2), "r"(a3), "l"(db), "r"(sd));
}
__device__ __forceinline__ void wgmma_rs_n64_tb(float (&d)[32], uint32_t a0, uint32_t a1, uint32_t a2, uint32_t a3, uint64_t db, int sd) {
  asm volatile("{\n.reg .pred p;\nsetp.ne.b32 p, %37, 0;\n"
    "wgmma.mma_async.sync.aligned.m64n64k16.f32.bf16.bf16 "
    "{%0, %1, %2, %3, %4, %5, %6, %7, %8, %9, %10, %11, %12, %13, %14, %15, "
    "%16, %17, %18, %19, %20, %21, %22, %23, %24, %25, %26, %27, %28, %29, %30, %31}, "
    "{%32, %33, %34, %35}, %36, p, 1, 1, 1;\n}"
    : "+f"(d[0]), "+f"(d[1]), "+f"(d[2]), "+f"(d[3]), "+f"(d[4]), "+f"(d[5]), "+f"(d[6]), "+f"(d[7]),
      "+f"(d[8]), "+f"(d[9]), "+f"(d[10]), "+f"(d[11]), "+f"(d[12]), "+f"(d[13]), "+f"(d[14]), "+f"(d[15]),
      "+f"(d[16]), "+f"(d[17]), "+f"(d[18]), "+f"(d[19]), "+f"(d[20]), "+f"(d[21]), "+f"(d[22]), "+f"(d[23]),
      "+f"(d[24]), "+f"(d[25]), "+f"(d[26]), "+f"(d[27]), "+f"(d[28]), "+f"(d[29]), "+f"(d[30]), "+f"(d[31])
    : "r"(a0), "r"(a1), "r"(a2), "r"(a3), "l"(db), "r"(sd));
}
__device__ __forceinline__ void wgmma_rs_n32(float (&d)[16], uint32_t a0, uint32_t a1, uint32_t a2, uint32_t a3, uint64_t db, int sd) {
  asm volatile("{\n.reg .pred p;\nsetp.ne.b32 p, %21, 0;\n"
    "wgmma.mma_async.sync.aligned.m64n32k16.f32.bf16.bf16 "
    "{%0, %1, %2, %3, %4, %5, %6, %7, %8, %9, %10, %11, %12, %13, %14, %15}, "
    "{%16, %17, %18, %19}, %20, p, 1, 1, 0;\n}"
    : "+f"(d[0]), "+f"(d[1]), "+f"(d[2]), "+f"(d[3]), "+f"(d[4]), "+f"(d[5]), "+f"(d[6]), "+f"(d[7]),
      "+f"(d[8]), "+f"(d[9]), "+f"(d[10]), "+f"(d[11]), "+f"(d[12]), "+f"(d[13]), "+f"(d[14]), "+f"(d[15])
    : "r"(a0), "r"(a1), "r"(a2), "r"(a3), "l"(db), "r"(sd));
}
__device__ __forceinline__ void wgmma_rs_n64(float (&d)[32], uint32_t a0, uint32_t a1, uint32_t a2, uint32_t a3, uint64_t db, int sd) {
  asm volatile("{\n.reg .pred p;\nsetp.ne.b32 p, %37, 0;\n"
    "wgmma.mma_async.sync.aligned.m64n64k16.f32.bf16.bf16 "
    "{%0, %1, %2, %3, %4, %5, %6, %7, %8, %9, %10, %11, %12, %13, %14, %15, "
    "%16, %17, %18, %19, %20, %21, %22, %23, %24, %25, %26, %27, %28, %29, %30, %31}, "
    "{%32, %33, %34, %35}, %36, p, 1, 1, 0;\n}"
    : "+f"(d[0]), "+f"(d[1]), "+f"(d[2]), "+f"(d[3]), "+f"(d[4]), "+f"(d[5]), "+f"(d[6]), "+f"(d[7]),
      "+f"(d[8]), "+f"(d[9]), "+f"(d[10]), "+f"(d[11]), "+f"(d[12]), "+f"(d[13]), "+f"(d[14]), "+f"(d[15]),
      "+f"(d[16]), "+f"(d[17]), "+f"(d[18]), "+f"(d[19]), "+f"(d[20]), "+f"(d[21]), "+f"(d[22]), "+f"(d[23]),
      "+f"(d[24]), "+f"(d[25]), "+f"(d[26]), "+f"(d[27]), "+f"(d[28]), "+f"(d[29]), "+f"(d[30]), "+f"(d[31])
    : "r"(a0), "r"(a1), "r"(a2), "r"(a3), "l"(db), "r"(sd));
}

__device__ __forceinline__ uint4 lds16(uint32_t a) {
  uint4 v; asm volatile("ld.shared.v4.u32 {%0, %1, %2, %3}, [%4];" : "=r"(v.x), "=r"(v.y), "=r"(v.z), "=r"(v.w) : "r"(a) : "memory"); return v;
}
__device__ __forceinline__ void sts16(uint32_t a, uint32_t x, uint32_t y, uint32_t z, uint32_t w) {
  asm volatile("st.shared.v4.u32 [%0], {%1, %2, %3, %4};" :: "r"(a), "r"(x), "r"(y), "r"(z), "r"(w) : "memory");
}
__device__ __forceinline__ uint32_t lds4(uint32_t a) { uint32_t v; asm volatile("ld.shared.u32 %0, [%1];" : "=r"(v) : "r"(a) : "memory"); return v; }
__device__ __forceinline__ uint32_t lds4v(uint32_t a) { uint32_t v; asm volatile("ld.volatile.shared.u32 %0, [%1];" : "=r"(v) : "r"(a) : "memory"); return v; }
__device__ __forceinline__ uint32_t bmul(uint32_t a, uint32_t b) { uint32_t r; asm("mul.rn.bf16x2 %0, %1, %2;" : "=r"(r) : "r"(a), "r"(b)); return r; }
__device__ __forceinline__ uint32_t badd(uint32_t a, uint32_t b) { uint32_t r; asm("add.rn.bf16x2 %0, %1, %2;" : "=r"(r) : "r"(a), "r"(b)); return r; }

__device__ __forceinline__ void ldsm4(uint32_t (&r)[4], uint32_t a) {
  asm volatile("ldmatrix.sync.aligned.m8n8.x4.shared.b16 {%0, %1, %2, %3}, [%4];" : "=r"(r[0]), "=r"(r[1]), "=r"(r[2]), "=r"(r[3]) : "r"(a) : "memory");
}
__device__ __forceinline__ uint32_t transpose8(uint32_t a) { uint32_t d; asm volatile("movmatrix.sync.aligned.m8n8.trans.b16 %0, %1;" : "=r"(d) : "r"(a)); return d; }

__device__ __forceinline__ void mma16816(float (&d)[4], const uint32_t (&a)[4], uint32_t b0, uint32_t b1) {
  asm volatile("mma.sync.aligned.m16n8k16.row.col.f32.bf16.bf16.f32 {%0, %1, %2, %3}, {%4, %5, %6, %7}, {%8, %9}, {%0, %1, %2, %3};"
               : "+f"(d[0]), "+f"(d[1]), "+f"(d[2]), "+f"(d[3]) : "r"(a[0]), "r"(a[1]), "r"(a[2]), "r"(a[3]), "r"(b0), "r"(b1));
}

#define CONV_LBO 1u
#define CONV_NRED 8
#define CONV_N 32
#define CONV_ORDER 2
#define EXP_SIDE 0
#define SIDE_AHEAD 2
#define ZERO_RD 3
#define CTX_SPLIT 10
#define CONV_ARRIVE 14
#define ARRIVE_KK 12
#define SIDE_DELAY_NS 4000
#define KVH(h) (h)
#define HEAD_MAP 1
#define EARLY_LD 3
constexpr int RED_BAR = 6;
constexpr int CV_BAR = 5;
constexpr int PP_BAR = 3;
template <int V> struct Int { static constexpr int value = V; };
struct Ring {
  uint32_t slot, phase;
  __device__ __forceinline__ void next() { if (++slot == NSLOT) { slot = 0; phase ^= 1; } }
};
__device__ __forceinline__ uint32_t bar_addr(uint32_t sb, uint32_t i) { return sb + BARS + 8 * i; }

__device__ __forceinline__ int q_tile(int h, int j, int which) { return ((h < 8) == (which == 0)) ? 15 - j : j; }

__device__ __forceinline__ int att_head(int h, int which) { return h; }
__device__ __forceinline__ int p1_head(int h, int t) { return h; }
__device__ __forceinline__ int p1_isv(int t) { return t >> 1; }
__device__ __forceinline__ int p1_rows(int h, int j, int t) { return 2 * j + (t & 1); }
#define KV_FLAG(h) (h)
#define KV_COUNT 16

__device__ __forceinline__ void load_tile4(uint32_t dst, const CUtensorMap* m, uint32_t full, int row, int blk0, int rank, bool shared, uint64_t pl = POL_NORMAL) {
  if (shared) {
    tma_ld3_mc(dst + rank * 16384, m, full, 0, row, blk0 + 2 * rank, pl);
  } else {
    tma_ld3(dst, m, full, 0, row, blk0, pl);
    tma_ld3(dst + 16384, m, full, 0, row, blk0 + 2, pl);
  }
}
__device__ __forceinline__ void producer_main(const Params& p, uint32_t sb, int h, int j) {
  const int rank = j & 1;
  Ring r{EARLY_LD, 0};
  auto wait_slot = [&]() { mbar_wait(bar_addr(sb, B_EMPTY + r.slot), r.phase ^ 1); };
  auto load_a = [&](int it, uint32_t dst, uint32_t full) {
    if (it < 64) tma_ld2(dst, &p.ckv, full, (it & 15) * 64, p1_rows(h, j, it >> 4) * 128, pol((HINTS & 2) && it >= 48));
    else tma_ld2(dst, &p.x, full, (it < 71 ? it - 64 : it - 71) * 64, q_tile(h, j, it < 71) * 128, pol(HINTS & 64));
  };
  uint32_t prev = 0;
#pragma unroll 1
  for (int it = EARLY_LD; it < P1_STEPS; it++) {
    wait_slot();
    if (it > EARLY_LD && it <= P1_XS) load_a(it - 1, sb + QREG + ((it - 1) & 3) * 16384, prev);
    const uint32_t full = bar_addr(sb, B_FULL + r.slot), dst = sb + r.slot * SLOT;
    mbar_expect_tx(full, it < P1_XS ? 49152 : 32768);
    if (it < 64) load_tile4(dst, p1_isv(it >> 4) ? &p.wuv : &p.wuk, full, (it & 15) * 64, p1_head(h, it >> 4) * 4, rank, true, pol(HINTS & 1));
    else load_tile4(dst, &p.wq, full, (it < 71 ? it - 64 : it - 71) * 64, att_head(h, it < 71) * 4, rank, true, pol(HINTS & 4));
    prev = full;
    r.next();
    if (it == P1_XS) {
      wait_slot();
      const uint32_t f2 = bar_addr(sb, B_FULL + r.slot);
      mbar_expect_tx(f2, 32768);
      load_a(P1_XS, sb + r.slot * SLOT, f2);
      load_a(P1_XS + 1, sb + r.slot * SLOT + 16384, f2);
      r.next();
    }
  }
  mbar_wait(bar_addr(sb, B_KVOK), 0);
  const int qa = q_tile(h, j, 0), na = 2 * qa + 2, own = 2 * (qa & ~1) + 2;
#pragma unroll 1
  for (int f = 0; f < 68; f++) {
    const bool isK = (f == 0) || ((f & 1) && f < 67);
    const int i = isK ? (f + 1) >> 1 : (f - 1) >> 1, which = i >= na;
    wait_slot();
    const uint32_t full = bar_addr(sb, B_FULL + r.slot);
    mbar_expect_tx(full, 32768);
    load_tile4(sb + r.slot * SLOT, &p.kv, full, ((isK ? 0 : NH) + KVH(att_head(h, which))) * SEQ + (which ? 33 - i : i) * 64, 0, rank, (i & ~1) != own,
               pol(which ? (HINTS & 32) : (HINTS & 8)));
    r.next();
  }
#pragma unroll 1
  for (int f = 0; f < 14; f++) {
    const int ch = f < 12 ? 2 * (f >> 2) + (f & 1) : 6, par = f < 12 ? (f >> 1) & 1 : f & 1;
    wait_slot();
    const uint32_t full = bar_addr(sb, B_FULL + r.slot);
    mbar_expect_tx(full, 32768);
    tma_ld5_mc(sb + r.slot * SLOT + rank * 16384, &p.wo, full, ch * 64, (par ? att_head(h ^ 8, 0) : att_head(h, 1)) * 8 + rank * 4, pol(HINTS & 16));
    r.next();
  }
}

__device__ __forceinline__ void helper_main(const Params& p, uint32_t sb, int h, int j, int w) {
  const unsigned epoch = load_epoch();
  const int cta = h * 8 + j, qb = q_tile(h, j, 1);
  const uint32_t qreg = sb + QREG + w * 32768, qfull = bar_addr(sb, B_QFULL + w);
  mbar_wait(bar_addr(sb, B_ST_KV + w), 0);
  flag_signal(flag_at(g_flags.kv_ready, KV_FLAG(h)));
  if (w == 0) {
    flag_wait(flag_at(g_flags.kv_ready, KV_FLAG(h)), KV_COUNT, epoch);
    fence_async_all();
    mbar_arrive(bar_addr(sb, B_KVOK));
  }
  mbar_wait(bar_addr(sb, B_ST_Q + w), 0);
  asm volatile("fence.acq_rel.gpu;" ::: "memory");
  fence_async_all();
  mbar_wait(bar_addr(sb, B_QFREE + w), 0);
  mbar_expect_tx(qfull, 32768);
  tma_ld3(qreg, &p.qc, qfull, 0, cta * 128 + w * 64, 0);
  mbar_wait(bar_addr(sb, B_ST_CTX + w), 0);
  flag_signal(flag_at(g_flags.ctx_ready, cta * 2 + w));
  flag_wait(flag_at(g_flags.ctx_ready, (cta ^ 64) * 2 + (w ^ 1)), 1, epoch);
  flag_wait(flag_at(g_flags.zero_ready, qb), 8, epoch);
  fence_async_all();
  mbar_wait(bar_addr(sb, B_QFREE + w), 1);
  mbar_expect_tx(qfull, 32768);
  bulk_ld(qreg, at<uint8_t>(g_qc, ((cta ^ 64) * 2 + (w ^ 1)) * 32768), 32768, qfull);
#pragma unroll 1
  for (int ch = 0; ch < 7; ch++) {
    mbar_wait(bar_addr(sb, B_S2_FULL + w * 4 + (ch & 3)), ch >> 2);
    tma_red2(&p.o, qreg + (ch & 3) * 8192, DA + ch * 64, qb * 128 + (w ^ 1) * 64);
    bulk_commit();
    if (ch < 3) { bulk_wait_read(); mbar_arrive(bar_addr(sb, B_S2_EMPTY + w * 4 + ch)); }
  }
  bulk_wait_read();
  GT(48 + w);
}

__device__ __forceinline__ void store_block(uint32_t base, uint32_t lanebase, const uint32_t (&pk)[16]) {
#pragma unroll
  for (int J = 0; J < 8; J += 2) stsm4(base + (lanebase ^ (J << 4)), pk[2 * J], pk[2 * J + 1], pk[2 * J + 2], pk[2 * J + 3]);
}
__device__ __forceinline__ void pack_chunks(uint32_t (&pk)[64], const float (&acc)[128]) {
#pragma unroll
  for (int i = 0; i < 64; i++) { const int e = 16 * (i >> 3) + 4 * (i & 3) + 2 * ((i >> 2) & 1); pk[i] = pack_bf16(acc[e], acc[e + 1]); }
}
__device__ __forceinline__ uint32_t chunk_off() { const uint32_t t = fresh_tid(); return (16 * ((t >> 5) & 3) + ((t & 31) >> 2)) * 512 + (t & 3) * 16; }
__device__ __forceinline__ void warp_arrive(uint32_t bar, int lane) { __syncwarp(); if (lane == 0) mbar_arrive(bar); }

__device__ __forceinline__ void consumer_main(const Params& p, uint32_t sb, int h, int j, int w) {
  const int lane = threadIdx.x & 31;
  const int rank = j & 1;

  auto turn_begin = [&]() { named_sync(PP_BAR + w, 256); };
  auto turn_end = [&]() { named_arrive(PP_BAR + (w ^ 1), 256); };
  if (w == 1) named_arrive(PP_BAR, 256);
  Ring r{0, 0};
  auto take = [&]() { const uint32_t sl = r.slot; mbar_wait(bar_addr(sb, B_FULL + sl), r.phase); r.next(); return sl; };
  auto give = [&](uint32_t sl) { if (lane < 2) mbar_arrive_remote(bar_addr(sb, B_EMPTY + sl), rank ^ lane); };
  float acc[128];
#pragma unroll
  for (int i = 0; i < 128; i++) acc[i] = 0.f;
  uint32_t pk[64];
#pragma unroll
  for (int i = 0; i < 64; i++) pk[i] = 0;
  TS(0);
  const uint32_t qreg = sb + QREG + w * 32768;
  {
    uint32_t xs = 0, prev = 0, dst = 0;
    int it = 0;
#pragma unroll 1
    for (int t = 0; t < 6; t++) {
      const int nk = t < 4 ? 16 : 7;
#pragma unroll 1
      for (int k = 0; k < nk; k++, it++) {
        const uint32_t ws = take();
        if (it == 0) TS(1);
        if (it == P1_XS) xs = take();
        const uint32_t aa = (it < P1_XS ? QREG + (it & 3) * 16384 : xs * SLOT + (it - P1_XS) * 16384) + (w ^ (t == 4)) * 8192;
        const uint64_t da = desc_k(sb + aa), db = desc_mn(sb + ws * SLOT);
        turn_begin();
        wg_fence();
#pragma unroll
        for (int kk = 0; kk < 4; kk++) wgmma_ss_n256_tb(acc, desc_add(da, kk * 32), desc_add(db, kk * 2048), (k | kk) != 0);
        wg_commit();
        turn_end();
        wg_wait<1>();
        if (k > 0) give(prev);
        prev = ws;
        if (it >= P1_XS - 2 && !(it & 1) && lane == 0) mbar_arrive(bar_addr(sb, B_XFREE + ((it - (P1_XS - 2)) >> 1)));
        if (t > 0) {
          uint4* row = at<uint4>(t < 5 ? (const void*)g_kv : (const void*)g_qc, dst + chunk_off());
          const int c0 = t < 4 ? k : 3 * k, c1 = t < 4 ? k + 1 : 3 * k + 3;
#pragma unroll
          for (int i = 0; i < 16; i++)
            if (i >= c0 && i < c1) row[(i & 1) * 256 + (i >> 1) * 4] = make_uint4(pk[4 * i], pk[4 * i + 1], pk[4 * i + 2], pk[4 * i + 3]);
          if (t >= 4 && k == 5) warp_arrive(bar_addr(sb, (t == 4 ? B_ST_KV : B_ST_Q) + w), lane);
        }
      }
      wg_wait<0>();
      reg_fence(acc);
      give(prev);
      pack_chunks(pk, acc);
      dst = t < 4 ? (uint32_t)((p1_isv(t) * NH + KVH(p1_head(h, t))) * SEQ + p1_rows(h, j, t) * 128 + w * 64) * 512 : (uint32_t)((h * 8 + j) * 2 + w) * 32768;
      TS(2 + t);
    }
    give(xs);
    mbar_wait(bar_addr(sb, B_XFREE + w), 0);
    const uint32_t ft = fresh_tid(), g = (ft & 31) >> 2;
    const uint32_t qa = qreg + (16 * ((ft >> 5) & 3) + g) * 128 + (((ft & 3) ^ g) << 4);
#pragma unroll
    for (int i = 0; i < 16; i++) sts16((qa ^ ((i & 2) << 5)) + (i >> 2) * 8192 + (i & 1) * 1024, pk[4 * i], pk[4 * i + 1], pk[4 * i + 2], pk[4 * i + 3]);
    fence_async_smem();
  }
  TS(8);

  constexpr float SC = 0.0625f * 1.4426950408889634f;
#pragma unroll 1
  for (int which = 0; which < 2; which++) {
    float s[32];
#pragma unroll
    for (int i = 0; i < 32; i++) s[i] = 0.f;
    uint32_t pa[16];
    float m0 = -INFINITY, m1 = -INFINITY, l0 = 0.f, l1 = 0.f;
    const uint64_t dq = desc_k(qreg);
    uint64_t dk = 0, dqq = 0, dv = 0;
    auto prep_qk = [&](uint32_t kaddr) { dk = desc_k(kaddr); dqq = dq + (kaddr >> 31); asm volatile("" : "+l"(dk), "+l"(dqq)); };
    auto prep_pv = [&](uint32_t vaddr) { dv = desc_mn(vaddr); asm volatile("" : "+l"(dv)); };
    auto issue_qk = [&]() {
#pragma unroll
      for (int kk = 0; kk < 16; kk++)
        wgmma_ss_n64(s, desc_add(dqq, (kk >> 2) * 8192 + (kk & 3) * 32), desc_add(dk, (kk >> 2) * 8192 + (kk & 3) * 32), kk != 0);
    };
    auto issue_pv = [&](int accumulate) {
#pragma unroll
      for (int kk = 0; kk < 4; kk++)
        wgmma_rs_n256_tb(acc, pa[4 * kk], pa[4 * kk + 1], pa[4 * kk + 2], pa[4 * kk + 3], desc_add(dv, kk * 2048), accumulate | kk);
    };
    auto mask_diag = [&]() {
      const uint32_t ft = fresh_tid();
      const int r0 = 16 * ((ft >> 5) & 3) + ((ft & 31) >> 2), c = ft & 3;
#pragma unroll
      for (int jj = 0; jj < 8; jj++) {
        const int cc = 8 * jj + 2 * c;
        if (cc > r0)         s[4 * jj]     = -INFINITY;
        if (cc + 1 > r0)     s[4 * jj + 1] = -INFINITY;
        if (cc > r0 + 8)     s[4 * jj + 2] = -INFINITY;
        if (cc + 1 > r0 + 8) s[4 * jj + 3] = -INFINITY;
      }
    };
    float a0, a1;
    auto softmax = [&]() -> bool {
      float x0 = fmaxf(s[0], s[1]), x1 = fmaxf(s[2], s[3]);
#pragma unroll
      for (int jj = 1; jj < 8; jj++) {
        x0 = fmaxf(x0, fmaxf(s[4 * jj], s[4 * jj + 1]));
        x1 = fmaxf(x1, fmaxf(s[4 * jj + 2], s[4 * jj + 3]));
      }
      x0 = fmaxf(x0, __shfl_xor_sync(0xffffffffu, x0, 1));
      x1 = fmaxf(x1, __shfl_xor_sync(0xffffffffu, x1, 1));
      x0 = fmaxf(x0, __shfl_xor_sync(0xffffffffu, x0, 2));
      x1 = fmaxf(x1, __shfl_xor_sync(0xffffffffu, x1, 2));
      const bool grow = __any_sync(0xffffffffu, fmaxf(x0 - m0, x1 - m1) * SC > 8.f);
      if (grow) {
        x0 = fmaxf(x0, m0); x1 = fmaxf(x1, m1);
        a0 = ex2((m0 - x0) * SC); a1 = ex2((m1 - x1) * SC);
        m0 = x0; m1 = x1;
        l0 *= a0; l1 *= a1;
      }
      const float b0 = -m0 * SC, b1 = -m1 * SC;
      float t0 = 0.f, t1 = 0.f, t2 = 0.f, t3 = 0.f;
#pragma unroll
      for (int jj = 0; jj < 8; jj++) {
        s[4 * jj]     = ex2(fmaf(s[4 * jj], SC, b0));
        s[4 * jj + 1] = ex2(fmaf(s[4 * jj + 1], SC, b0));
        s[4 * jj + 2] = ex2(fmaf(s[4 * jj + 2], SC, b1));
        s[4 * jj + 3] = ex2(fmaf(s[4 * jj + 3], SC, b1));
        t0 += s[4 * jj]; t1 += s[4 * jj + 1]; t2 += s[4 * jj + 2]; t3 += s[4 * jj + 3];
      }
      l0 += t0 + t1; l1 += t2 + t3;
      return grow;
    };
    auto softmax_fast = [&](uint32_t vs) -> bool {
      const float b0 = -m0 * SC, b1 = -m1 * SC;
      float e[16];
#pragma unroll
      for (int i = 0; i < 16; i++) e[i] = ex2(fmaf(s[i], SC, (i & 2) ? b1 : b0));
      float t0 = (e[0] + e[4]) + (e[8] + e[12]), t1 = (e[1] + e[5]) + (e[9] + e[13]), t2 = (e[2] + e[6]) + (e[10] + e[14]), t3 = (e[3] + e[7]) + (e[11] + e[15]);
      reg_fence(e);
      wg_wait<0>();
      reg_fence(acc);
      reg_fence(pa);
      give(vs);
#pragma unroll
      for (int i = 0; i < 8; i++) pa[i] = pack_bf16(e[2 * i], e[2 * i + 1]);
#pragma unroll
      for (int i = 0; i < 16; i++) e[i] = ex2(fmaf(s[16 + i], SC, (i & 2) ? b1 : b0));
#pragma unroll
      for (int i = 0; i < 16; i += 4) { t0 += e[i]; t1 += e[i + 1]; t2 += e[i + 2]; t3 += e[i + 3]; }
#pragma unroll
      for (int i = 0; i < 8; i++) pa[8 + i] = pack_bf16(e[2 * i], e[2 * i + 1]);
      t0 += t1; t2 += t3;
      const bool redo = __any_sync(0xffffffffu, !(t0 + t2 <= 16777216.f));
      if (!redo) { l0 += t0; l1 += t2; }
      return redo;
    };
    auto rescale = [&]() {
#pragma unroll
      for (int i = 0; i < 32; i++) { acc[4 * i] *= a0; acc[4 * i + 1] *= a0; acc[4 * i + 2] *= a1; acc[4 * i + 3] *= a1; }
    };
    auto to_p = [&]() {
#pragma unroll
      for (int i = 0; i < 16; i++) pa[i] = pack_bf16(s[2 * i], s[2 * i + 1]);
    };
    auto q_free = [&]() { if (lane == 0) mbar_arrive(bar_addr(sb, B_QFREE + w)); };

    const int n = 2 * q_tile(h, j, which) + 1 + (w ^ which);
    uint32_t ks = take();
    TS(9 + 5 * which);
    prep_qk(sb + ks * SLOT);
    turn_begin();
    wg_fence();
    issue_qk();
    wg_commit();
    turn_end();
    wg_wait<0>();
    reg_fence(s);
    give(ks);
    if (n == 1) q_free();
    if (which == 1) {
      uint4* dst = at<uint4>(g_qc, (uint32_t)((h * 8 + j) * 2 + w) * 32768 + (fresh_tid() & 127) * 16);
#pragma unroll
      for (int i = CTX_SPLIT; i < 16; i++) dst[i * 128] = make_uint4(pk[4 * i], pk[4 * i + 1], pk[4 * i + 2], pk[4 * i + 3]);
    }
    if (which == 1 || n == 1) mask_diag();
    softmax();
    to_p();
    if (which == 1) {
      warp_arrive(bar_addr(sb, B_ST_CTX + w), lane);
      give(take());
    }
    TS(10 + 5 * which);
#pragma unroll 1
    for (int jj = 1; jj < n; jj++) {
      ks = take();
      const uint32_t vs = take();
      prep_qk(sb + ks * SLOT);
      prep_pv(sb + vs * SLOT);
      turn_begin();
      wg_fence();
      issue_qk();
      wg_commit();
      issue_pv(jj > 1);
      wg_commit();
      turn_end();
      wg_wait<1>();
      reg_fence(s);
      give(ks);
      if (jj == n - 1) {
        q_free();
        if (which == 0) mask_diag();
      }
      if (softmax_fast(vs)) {
        if (softmax()) rescale();
        to_p();
      }
    }
    TS(11 + 5 * which);
    if (which == 0) give(take());
    {
      const uint32_t vs = take();
      prep_pv(sb + vs * SLOT);
      turn_begin();
      wg_fence();
      issue_pv(n > 1);
      wg_commit();
      turn_end();
      l0 += __shfl_xor_sync(0xffffffffu, l0, 1); l1 += __shfl_xor_sync(0xffffffffu, l1, 1);
      l0 += __shfl_xor_sync(0xffffffffu, l0, 2); l1 += __shfl_xor_sync(0xffffffffu, l1, 2);
      l0 = 1.f / l0; l1 = 1.f / l1;
      wg_wait<0>();
      reg_fence(acc);
      reg_fence(pa);
      give(vs);
    }
    TS(12 + 5 * which);
#pragma unroll
    for (int i = 0; i < 32; i++) {
      pk[2 * i]     = pack_bf16(acc[4 * i] * l0, acc[4 * i + 1] * l0);
      pk[2 * i + 1] = pack_bf16(acc[4 * i + 2] * l1, acc[4 * i + 3] * l1);
    }
    if (which == 0) {
      mbar_wait(bar_addr(sb, B_QFULL + w), 0);
      uint4* dst = at<uint4>(g_qc, (uint32_t)((h * 8 + j) * 2 + w) * 32768 + (fresh_tid() & 127) * 16);
#pragma unroll
      for (int i = 0; i < CTX_SPLIT; i++) dst[i * 128] = make_uint4(pk[4 * i], pk[4 * i + 1], pk[4 * i + 2], pk[4 * i + 3]);
    }
    TS(13 + 5 * which);
  }

  {
    float oa[32], ob[32];
#pragma unroll
    for (int i = 0; i < 32; i++) { oa[i] = 0.f; ob[i] = 0.f; }
    uint32_t pk2[64];
#pragma unroll
    for (int i = 0; i < 64; i++) pk2[i] = 0;
    auto stage = [&](float (&o)[32], int ch) {
      reg_fence(o);
      uint32_t q[16];
#pragma unroll
      for (int i = 0; i < 16; i++) q[i] = pack_bf16(o[2 * i], o[2 * i + 1]);
      if (ch >= 4) mbar_wait(bar_addr(sb, B_S2_EMPTY + w * 4 + (ch & 3)), 0);
      store_block(qreg + (ch & 3) * 8192, lane_base16(), q);
    };
    auto hand_over = [&](int ch) {
      fence_async_smem();
      warp_arrive(bar_addr(sb, B_S2_FULL + w * 4 + (ch & 3)), lane);
    };
    uint32_t prev = 0;
    auto half = [&](int f, float (&o)[32], uint32_t (&a)[64], int accumulate) {
      const uint32_t sl = take();
      const uint64_t d = desc_mn(sb + sl * SLOT);
      turn_begin();
      wg_fence();
#pragma unroll
      for (int kk = 0; kk < 16; kk++) {
        wgmma_rs_n64_tb(o, a[4 * kk], a[4 * kk + 1], a[4 * kk + 2], a[4 * kk + 3], desc_add(d, kk * 2048), accumulate | kk);
        if (kk == ARRIVE_KK && (f < 13 || w == 0)) turn_end();
      }
      wg_commit();
      wg_wait<1>();
      if (f >= 1 && f <= 9) give(prev);
      prev = sl;
    };
    auto load_ctx = [&](auto h0) {
      constexpr int I0 = decltype(h0)::value * 8;
      const uint32_t src = qreg + (fresh_tid() & 127) * 16;
#pragma unroll
      for (int i = I0; i < I0 + 8; i++) { const uint4 v = lds16(src + i * 2048); pk2[4 * i] = v.x; pk2[4 * i + 1] = v.y; pk2[4 * i + 2] = v.z; pk2[4 * i + 3] = v.w; }
    };
#pragma unroll 1
    for (int i = 0; i < 3; i++) {
      half(4 * i, oa, pk, 0);
      if (i == 0) { mbar_wait(bar_addr(sb, B_QFULL + w), 1); load_ctx(Int<0>()); }
      else { hand_over(2 * i - 2); stage(ob, 2 * i - 1); }
      half(4 * i + 1, ob, pk, 0);
      if (i == 0) load_ctx(Int<1>()); else hand_over(2 * i - 1);
      half(4 * i + 2, oa, pk2, 1);
      half(4 * i + 3, ob, pk2, 1);
      stage(oa, 2 * i);
    }
    half(12, oa, pk, 0);
    hand_over(4);
    stage(ob, 5);
    half(13, oa, pk2, 1);
    hand_over(5);
    wg_wait<0>();
    reg_fence(pk);
    reg_fence(pk2);
    stage(oa, 6);
    hand_over(6);
  }
  TS(19);
  TDUMP();
}

namespace ssm {
constexpr int NCH = DA / NCONV;
constexpr int NS = 8, NP = 6;
constexpr uint32_t X0 = 896;
constexpr uint32_t HO = X0 + 4096;
constexpr uint32_t HE = HO + HO_STRIDE + 64;
constexpr uint32_t SSLOT = HE + 4096 + 64;
constexpr uint32_t PART = 264 * 16;
constexpr uint32_t OFF_P = NS * SSLOT, OFF_D = OFF_P + NP * 4 * PART, END = OFF_D + NCH * 4;
static_assert(SSLOT % 128 == 0 && HO % 128 == 0 && END <= BARS, "smem");
enum : uint32_t { B_FULL = 0, B_EMPTY = NS, B_PFULL = 2 * NS, B_PEMPTY = 2 * NS + NP };
__device__ __forceinline__ int channel(int cidx, int i) { return (i >> 4) * 64 + cidx * 16 + (i & 15); }

__device__ __forceinline__ void producer(const Params& p, uint32_t sb, int cidx, unsigned epoch) {
#pragma unroll 1
  for (int i = 0; i < NCH; i++) {
    const int s = i % NS, ch = channel(cidx, i);
    const uint32_t full = bar_addr(sb, B_FULL + s), dst = sb + s * SSLOT;
    mbar_wait(bar_addr(sb, B_EMPTY + s), ((i / NS) & 1) ^ 1);
    mbar_expect_tx(full, 4096 + 4128 + 4096);
    bulk_ld(dst + HE, at<uint8_t>(p.a_ssmk, ch * 4096), 4096, full);
    if ((i & 15) == 0) { flag_wait(flag_at(g_flags.x_ready, i >> 4), NMAIN, epoch); fence_async_all(); }
    bulk_ld(dst + HO, at<uint8_t>(g_ho, ch * HO_STRIDE), 4128, full);
    bulk_ld(dst + X0, at<uint8_t>(g_xs, ch * 4096), 4096, full);
  }
}

__device__ __forceinline__ void reducer(uint32_t sb, int cidx, int rw) {
  uint32_t n = 0;
#pragma unroll 1
  for (int i = rw; i < NCH; i += 3, n++) {
    const uint32_t b = rw + 3 * (n & 1), pb = sb + OFF_P + b * 4 * PART;
    uint8_t* dst = at<uint8_t>(g_xs, channel(cidx, i) * 4096);
    mbar_wait(bar_addr(sb, B_PFULL + b), (n >> 1) & 1);
    asm volatile("cp.async.bulk.global.shared::cta.bulk_group [%0], [%1], 4096;" :: "l"(dst), "r"(pb + 3 * PART) : "memory");
    bulk_commit();
    bulk_wait_all();
#pragma unroll
    for (int k = 2; k >= 0; k--)
      asm volatile("cp.reduce.async.bulk.global.shared::cta.bulk_group.add.noftz.bf16 [%0], [%1], 4096;" :: "l"(dst), "r"(pb + k * PART) : "memory");
    bulk_commit();
    bulk_wait_read();
    mbar_arrive(bar_addr(sb, B_PEMPTY + b));
    if (((i + 3) >> 4) != (i >> 4)) {
      bulk_wait_all();
      fence_async_all();
      flag_signal(flag_at(g_flags.z_ready, i >> 4));
    }
  }
}

__device__ __forceinline__ void mma_warpgroup(uint32_t sb, int w) {
  const int lane = threadIdx.x & 31, g = lane >> 2, c = lane & 3, wq = (threadIdx.x >> 5) & 3;
  const uint32_t aoff = ((g & 1) ? HO + 30 : HE) + (16 * wq - g + 2 * c) * 2;
  const uint32_t poff = OFF_P + wq * PART + (2 * wq + lane) * 16;
  const uint32_t dmask = (wq == 0 && c == (g >> 1)) ? ((g & 1) ? 0xffff0000u : 0xffffu) : 0u;
  constexpr int NE = 256 / CONV_N, LT = CONV_N == 64 ? 3 : 2;
  float acc[NE][CONV_N / 2];
  uint32_t fa[16][4];
#pragma unroll
  for (int e = 0; e < NE; e++)
#pragma unroll
    for (int i = 0; i < CONV_N / 2; i++) acc[e][i] = 0.f;
  auto load_a = [&](int i) {
    mbar_wait(bar_addr(sb, B_FULL + i % NS), (i / NS) & 1);
    const uint32_t ad = sb + (i % NS) * SSLOT + aoff;
#pragma unroll
    for (int m = 0; m < 16; m++) {
      fa[m][0] = lds4(ad + m * 256 + 16); fa[m][1] = lds4(ad + m * 256 + 144); fa[m][2] = lds4(ad + m * 256); fa[m][3] = lds4(ad + m * 256 + 128);
    }
    fa[0][2] = badd(fa[0][2], lds4(sb + OFF_D + i * 4) & dmask);
  };
  if (w == 1) named_arrive(PP_BAR, 256);
  load_a(w);
  if (threadIdx.x == 128) { GT(12); PT(10); }
  uint32_t pb = w, pphase = 1;
#pragma unroll 1
  for (int i = w; i < NCH; i += 2) {
    const uint64_t db = (uint64_t)((((sb + (i % NS) * SSLOT + X0 - 16 * CONV_LBO) & 0x3FFFF) >> 4) | (CONV_LBO << 16)) | ((uint64_t)8 << 32);
    PCLK(c0);
    named_sync(PP_BAR + w, 256);
    PACC(t0, c0);
    PCLK(c1);
    wg_fence();
#pragma unroll
    for (int r = 0; r < 16; r++) {
      auto mm = [&](int e, int m) { wgmma_rs_n32(acc[e], fa[m][0], fa[m][1], fa[m][2], fa[m][3], db + (int64_t)(32 * e - 16 * m), m != 0); };
      mm(7, r);
      if (r < 14) mm(6, r); else mm(0, r - 14);
      if (r < 12) mm(5, r); else mm(1, r - 12);
      if (r < 10) mm(4, r); else mm(2, r - 10);
      if ((r & 1) == 0) mm(3, r >> 1);
      if (r == CONV_ARRIVE && (i + 1 < NCH)) named_arrive(PP_BAR + (w ^ 1), 256);
    }
    wg_commit();
    PACC(t1, c1);
    PCLK(c2);
    wg_wait<0>();
    PACC(t2, c2);
#pragma unroll
    for (int e = 0; e < NE; e++) reg_fence(acc[e]);
#pragma unroll
    for (int m = 0; m < 16; m++) reg_fence(fa[m]);
    if (lane == 0) mbar_arrive(bar_addr(sb, B_EMPTY + i % NS));
    PCLK(c3);
    PACC(t3, c3);
    PCLK(c4);
    mbar_wait(bar_addr(sb, B_PEMPTY + pb), pphase);
    PACC(t4, c4);
    PCLK(c5);
    const uint32_t pa = sb + pb * 4 * PART + poff;
#pragma unroll
    for (int e = 0; e < 8; e++) {
      uint32_t u[4];
#pragma unroll
      for (int j = 0; j < 4; j++) {
        const int T = 4 * e + j, U = T - 1;
        constexpr int MK = (1 << LT) - 1;
        float lo = acc[T >> LT][4 * (T & MK)], hi = acc[T >> LT][4 * (T & MK) + 1];
        if (T > 0) { lo += acc[U >> LT][4 * (U & MK) + 2]; hi += acc[U >> LT][4 * (U & MK) + 3]; }
        u[j] = pack_bf16(lo, hi);
      }
      asm volatile("stmatrix.sync.aligned.m8n8.x4.trans.shared.b16 [%0], {%1, %2, %3, %4};" :: "r"(pa + e * 512), "r"(u[0]), "r"(u[1]), "r"(u[2]), "r"(u[3]) : "memory");
    }
    if (i + 2 < NCH) load_a(i + 2);
    fence_async_smem();
    warp_arrive(bar_addr(sb, B_PFULL + pb), lane);
    pb += 2;
    if (pb >= NP) { pb -= NP; pphase ^= 1; }
    PACC(t5, c5);
  }
  if (threadIdx.x == 128) { PT(9); GT(13); }
}

__device__ __forceinline__ void init(const Params& p, uint32_t sb, int cidx) {
  if (threadIdx.x < NS * 32) {
    const uint32_t s = threadIdx.x >> 5, r = threadIdx.x & 31;
    sts16(sb + s * SSLOT + r * 16, 0, 0, 0, 0);
    if (r < 28) sts16(sb + s * SSLOT + (r < 24 ? 512 + r * 16 : HE - 64 + (r - 24) * 16), 0, 0, 0, 0);
  } else {
    const uint32_t t = threadIdx.x - NS * 32;
    for (uint32_t u = t; u < NP * 32; u += 128) sts16(sb + OFF_P + (u >> 3) * PART + (u & 7) * 16, 0, 0, 0, 0);
    if (t < NCH) {
      const uint32_t d = (uint32_t)__ldg(reinterpret_cast<const unsigned short*>(p.a_D + channel(cidx, t))) * 0x10001u;
      asm volatile("st.shared.u32 [%0], %1;" :: "r"(sb + OFF_D + t * 4), "r"(d) : "memory");
    }
  }
  if (threadIdx.x == 0) {
    for (int i = 0; i < NS; i++) { mbar_init(bar_addr(sb, B_FULL + i), 1); mbar_init(bar_addr(sb, B_EMPTY + i), 4); }
    for (int i = 0; i < NP; i++) { mbar_init(bar_addr(sb, B_PFULL + i), 4); mbar_init(bar_addr(sb, B_PEMPTY + i), 1); }
  }
  fence_async_smem();
}

__device__ __forceinline__ void side_prepare(const Params& p, int cta, int rd) {
  const int lane = threadIdx.x & 31, t0 = 16 * cta + 8 * (lane & 1);
  if (EXP_SIDE & 16) { if (lane == 0) flag_signal_after_bulk(flag_at(g_flags.x_ready, rd)); return; }
#pragma unroll 1
  for (int ch = 64 * rd + (lane & ~1); ch < 64 * rd + 64; ch += 32) {
    const uint4 sv = __ldg(at<const uint4>(p.a_shift, ch * 8));
    const uint32_t* kp = at<const uint32_t>(p.a_k, (t0 * DA + ch) * 2);
    const uint32_t* vp = at<const uint32_t>(p.a_v, (t0 * DA + ch) * 2);
    uint32_t k0 = 0, k1 = 0, k2 = 0, kk[8], x[8];
    if (t0 > 0) { k0 = __ldg(kp - 3 * (DA / 2)); k1 = __ldg(kp - 2 * (DA / 2)); k2 = __ldg(kp - DA / 2); }
#pragma unroll
    for (int i = 0; i < 8; i++) { kk[i] = __ldg(kp + i * (DA / 2)); x[i] = __ldg(vp + i * (DA / 2)); }
    const uint32_t sh0 = __byte_perm(sv.x, sv.z, 0x5410), sh1 = __byte_perm(sv.x, sv.z, 0x7632);
    const uint32_t sh2 = __byte_perm(sv.y, sv.w, 0x5410), sh3 = __byte_perm(sv.y, sv.w, 0x7632);
#pragma unroll
    for (int i = 0; i < 8; i++) {
      uint32_t ks = bmul(k0, sh3);
      ks = badd(ks, bmul(k1, sh2)); ks = badd(ks, bmul(k2, sh1)); ks = badd(ks, bmul(kk[i], sh0));
      x[i] = bmul(ks, x[i]);
      k0 = k1; k1 = k2; k2 = kk[i];
    }
    uint4* dst = at<uint4>(g_xs, ch * 4096 + t0 * 2);
    if ((EXP_SIDE & 4) && (x[0] ^ x[1] ^ x[2] ^ x[3] ^ x[4] ^ x[5] ^ x[6] ^ x[7]) != 0x12345) continue;
    dst[0]   = make_uint4(__byte_perm(x[7], x[6], 0x5410), __byte_perm(x[5], x[4], 0x5410), __byte_perm(x[3], x[2], 0x5410), __byte_perm(x[1], x[0], 0x5410));
    dst[256] = make_uint4(__byte_perm(x[7], x[6], 0x7632), __byte_perm(x[5], x[4], 0x7632), __byte_perm(x[3], x[2], 0x7632), __byte_perm(x[1], x[0], 0x7632));
  }
  if (!(EXP_SIDE & 8)) {
    const int hc = 64 * rd + (cta >> 1), r0 = (cta & 1) * 128 + lane;
    const uint4* src = at<const uint4>(p.a_ssmk, hc * 4096 + r0 * 16);
    uint4* dst = at<uint4>(g_ho, hc * HO_STRIDE + r0 * 16);
    uint4 w[4];
    uint32_t nx[4];
#pragma unroll
    for (int i = 0; i < 4; i++) { w[i] = __ldg(src + 32 * i); nx[i] = r0 + 32 * i < 255 ? __ldg(reinterpret_cast<const uint32_t*>(src + 32 * i + 1)) : 0u; }
#pragma unroll
    for (int i = 0; i < 4; i++)
      dst[32 * i + 2] = make_uint4(__byte_perm(w[i].x, w[i].y, 0x5432), __byte_perm(w[i].y, w[i].z, 0x5432), __byte_perm(w[i].z, w[i].w, 0x5432), __byte_perm(w[i].w, nx[i], 0x5432));
    const uint32_t h0 = __shfl_sync(0xffffffffu, w[0].x, 0);
    if (r0 < 2) dst[0] = make_uint4(0, 0, 0, r0 ? h0 << 16 : 0u);
  }
  __syncwarp();
  if (lane == 0) { if (EXP_SIDE & 2) flag_signal_after_bulk(flag_at(g_flags.x_ready, rd)); else flag_signal(flag_at(g_flags.x_ready, rd)); }
}
__device__ __forceinline__ void side_finish(const Params& p, int cta, int rd) {
  const int lane = threadIdx.x & 31, t0 = 16 * cta + 8 * (lane & 1);
#pragma unroll 1
  for (int ch = 64 * rd + (lane & ~1); ch < 64 * rd + 64; ch += 32) {
    const uint4* src = at<const uint4>(g_xs, ch * 4096 + t0 * 2);
    const uint32_t* qp = at<const uint32_t>(p.a_q, (t0 * DA + ch) * 2);
    uint32_t* op = at<uint32_t>(p.out, (t0 * OUTW + ch) * 2);
    const uint4 z0 = __ldcg(src), z1 = __ldcg(src + 256);
    uint32_t q[8];
#pragma unroll
    for (int i = 0; i < 8; i++) q[i] = __ldg(qp + i * (DA / 2));
    const uint32_t a[4] = {z0.w, z0.z, z0.y, z0.x}, b[4] = {z1.w, z1.z, z1.y, z1.x};
#pragma unroll
    for (int i = 0; i < 4; i++) {
      op[(2 * i) * (OUTW / 2)]     = bmul(q[2 * i], __byte_perm(a[i], b[i], 0x7632));
      op[(2 * i + 1) * (OUTW / 2)] = bmul(q[2 * i + 1], __byte_perm(a[i], b[i], 0x5410));
    }
  }
}
__device__ __forceinline__ void clear_rows(const Params& p, int qt, int part) {
  const int lane = threadIdx.x & 31;
  if (lane < 28) {
    uint4* z = at<uint4>(p.out, ((qt * 128 + part * 16) * OUTW + DA) * 2 + lane * 16);
#pragma unroll
    for (int i = 0; i < 32; i++) z[(i >> 1) * (OUTW / 8) + (i & 1) * 28] = make_uint4(0, 0, 0, 0);
  }
  __syncwarp();
  if (lane == 0) flag_signal(flag_at(g_flags.zero_ready, qt));
}
__device__ __forceinline__ void side_work(const Params& p, int cta, int qt, unsigned epoch) {
#pragma unroll 1
  for (int rd = -SIDE_AHEAD; rd < 7; rd++) {
    if (rd >= 0) {
      if ((threadIdx.x & 31) == 0) flag_wait_slow(flag_at(g_flags.z_ready, rd), 3 * NCONV, epoch);
      __syncwarp();
    }
    if (rd + SIDE_AHEAD < 7) side_prepare(p, cta, rd + SIDE_AHEAD);
    if (rd >= 0 && !(EXP_SIDE & 1)) side_finish(p, cta, rd);
    if (rd == ZERO_RD) clear_rows(p, qt, (cta >> 3) & 7);
  }
}
}

__global__ void __cluster_dims__(2, 1, 1) __launch_bounds__(NTHREADS, 1)
concat_heads__ssm_conv_h3__compressed_kv_cla__prompt_kernel(const __grid_constant__ Params p) {
  extern __shared__ uint8_t smem_raw[];
  const uint32_t sb = (smem_u32(smem_raw) + 1023) & ~1023u;
  const int warp = __shfl_sync(0xffffffffu, threadIdx.x >> 5, 0);
  const int wg = warp >> 2;
  const int cta = blockIdx.x;
  const bool attn = cta < NMAIN;
  int h, u;
  {
    const int c = cta >> 1;
    if (c < 4) { h = 15; u = c; }
    else if (c < 36) { h = (c - 4) & 7; u = (c - 4) >> 3; }
    else { h = 8 + (c - 36) % 7; u = (c - 36) / 7; }
  }
  const int j = 2 * u + (cta & 1);
  if (!attn) ssm::init(p, sb, cta - NMAIN);
  if (attn && threadIdx.x == 0) {
    for (int i = 0; i < NSLOT; i++) { mbar_init(bar_addr(sb, B_FULL + i), 1); mbar_init(bar_addr(sb, B_EMPTY + i), 16); }
    for (int i = 0; i < 2; i++) {
      mbar_init(bar_addr(sb, B_XFREE + i), 8); mbar_init(bar_addr(sb, B_QFREE + i), 4); mbar_init(bar_addr(sb, B_QFULL + i), 1);
      mbar_init(bar_addr(sb, B_ST_KV + i), 4); mbar_init(bar_addr(sb, B_ST_Q + i), 4); mbar_init(bar_addr(sb, B_ST_CTX + i), 4);
    }
    mbar_init(bar_addr(sb, B_KVOK), 1);
    mbar_init(bar_addr(sb, B_DONE), 2);
    for (int i = 0; i < 8; i++) { mbar_init(bar_addr(sb, B_S2_FULL + i), 4); mbar_init(bar_addr(sb, B_S2_EMPTY + i), 1); }
    asm volatile("fence.mbarrier_init.release.cluster;" ::: "memory");
  }
  if (attn && threadIdx.x == 32) {
    prefetch_map(&p.ckv); prefetch_map(&p.wuk); prefetch_map(&p.wuv); prefetch_map(&p.x); prefetch_map(&p.wq);
    prefetch_map(&p.kv); prefetch_map(&p.o); prefetch_map(&p.wo); prefetch_map(&p.qc);
  }
  __syncwarp();
  asm volatile("barrier.cluster.arrive.release.aligned;" ::: "memory");
  if (attn && threadIdx.x == 0) {
    for (int k = 0; k < EARLY_LD; k++) {
      const uint32_t full = bar_addr(sb, B_FULL + k);
      mbar_expect_tx(full, 49152);
      tma_ld2(sb + QREG + k * 16384, &p.ckv, full, k * 64, p1_rows(h, j, 0) * 128);
      load_tile4(sb + k * SLOT, &p.wuk, full, k * 64, p1_head(h, 0) * 4, j & 1, false, pol(HINTS & 1));
    }
  }
  __syncwarp();
  asm volatile("barrier.cluster.wait.acquire.aligned;" ::: "memory");

  const int lane = threadIdx.x & 31;
  if (wg == 0) {
    if (!attn) {
      asm volatile("setmaxnreg.dec.sync.aligned.u32 40;");
      if (lane == 0) {
        if (warp == 0) { ssm::producer(p, sb, cta - NMAIN, load_epoch()); cta_done(32); }
        else ssm::reducer(sb, cta - NMAIN, warp - 1);
        if (warp == 1) GT(14);
      }
      return;
    }
    asm volatile("setmaxnreg.dec.sync.aligned.u32 40;");
    if (warp == 0) {
      if (lane == 0) producer_main(p, sb, h, j);
    } else if (warp < 3) {
      if (lane == 0) { helper_main(p, sb, h, j, warp - 1); mbar_arrive(bar_addr(sb, B_DONE)); }
    } else {
      ssm::side_work(p, h * 8 + j, q_tile(h, j, 1), load_epoch());
      if (lane == 0) { GT(57); mbar_wait(bar_addr(sb, B_DONE), 0); cta_done(1); }
    }
  } else {
    if (!attn) {
      asm volatile("setmaxnreg.inc.sync.aligned.u32 232;");
      if (p.out != nullptr) ssm::mma_warpgroup(sb, wg - 1);
      return;
    }
    asm volatile("setmaxnreg.inc.sync.aligned.u32 232;");
    if (p.out != nullptr) consumer_main(p, sb, h, j, wg - 1);
  }
}

typedef CUresult (*EncodeTiledFn)(CUtensorMap*, CUtensorMapDataType, cuuint32_t, void*, const cuuint64_t*, const cuuint64_t*,
                                  const cuuint32_t*, const cuuint32_t*, CUtensorMapInterleave, CUtensorMapSwizzle,
                                  CUtensorMapL2promotion, CUtensorMapFloatOOBfill);

void make_map(EncodeTiledFn enc, CUtensorMap* m, const void* ptr, int rank, const uint64_t* dims, const uint64_t* strides, const uint32_t* box) {
  cuuint64_t d[5], s[4]; cuuint32_t b[5], e[5] = {1, 1, 1, 1, 1};
  for (int i = 0; i < rank; i++) { d[i] = dims[i]; b[i] = box[i]; if (i) s[i - 1] = strides[i - 1]; }
  enc(m, CU_TENSOR_MAP_DATA_TYPE_BFLOAT16, rank, const_cast<void*>(ptr), d, s, b, e, CU_TENSOR_MAP_INTERLEAVE_NONE,
      CU_TENSOR_MAP_SWIZZLE_128B, CU_TENSOR_MAP_L2_PROMOTION_L2_256B, CU_TENSOR_MAP_FLOAT_OOB_FILL_NONE);
}
void map2(EncodeTiledFn enc, CUtensorMap* m, const void* ptr, uint64_t cols, uint64_t rows, uint32_t bc, uint32_t br) {
  const uint64_t dims[2] = {cols, rows}, st[1] = {cols * 2}; const uint32_t box[2] = {bc, br};
  make_map(enc, m, ptr, 2, dims, st, box);
}
void map3(EncodeTiledFn enc, CUtensorMap* m, const void* ptr, uint64_t rows, uint32_t nblk) {
  const uint64_t dims[3] = {64, rows, 64}, st[2] = {8192, 128}; const uint32_t box[3] = {64, 64, nblk};
  make_map(enc, m, ptr, 3, dims, st, box);
}

}

extern "C" void kernel_launch(void* const* d_in, const int* in_sizes, int n_in, void* d_out, int out_size) {
  (void)in_sizes; (void)n_in; (void)out_size;
  static EncodeTiledFn enc = nullptr;
  static void *kv_ptr = nullptr, *qc_ptr = nullptr;
  if (!enc) {
    void* fn = nullptr; cudaDriverEntryPointQueryResult qr;
    cudaGetDriverEntryPoint("cuTensorMapEncodeTiled", &fn, cudaEnableDefault, &qr);
    enc = (EncodeTiledFn)fn;
    cudaGetSymbolAddress(&kv_ptr, g_kv);
    cudaGetSymbolAddress(&qc_ptr, g_qc);
    cudaFuncSetAttribute(concat_heads__ssm_conv_h3__compressed_kv_cla__prompt_kernel, cudaFuncAttributeMaxDynamicSharedMemorySize, SMEM_BYTES);
  }
  Params p;
  p.a_q = (const bf16*)d_in[0]; p.a_k = (const bf16*)d_in[1]; p.a_v = (const bf16*)d_in[2];
  p.a_shift = (const bf16*)d_in[3]; p.a_ssmk = (const bf16*)d_in[4]; p.a_D = (const bf16*)d_in[5];
  p.out = (bf16*)d_out;
  map2(enc, &p.x, d_in[6], DM, SEQ, 64, 128);
  map2(enc, &p.ckv, d_in[7], DC, SEQ, 64, 128);
  map3(enc, &p.wq, d_in[8], DM, 2);
  map3(enc, &p.wuk, d_in[9], DC, 2);
  map3(enc, &p.wuv, d_in[10], DC, 2);
  {
    const uint64_t dims[5] = {DM, 2, 4, 4, NH * HD / 32}, st[4] = {DM * 2, 8 * DM * 2, 2 * DM * 2, 32 * DM * 2}; const uint32_t box[5] = {64, 2, 4, 4, 4};
    make_map(enc, &p.wo, d_in[11], 5, dims, st, box);
  }
  {
    const uint64_t dims[3] = {64, 2 * NH * SEQ, 4}, st[2] = {HD * 2, 128}; const uint32_t box[3] = {64, 64, 2};
    make_map(enc, &p.kv, kv_ptr, 3, dims, st, box);
  }
  map2(enc, &p.o, d_out, OUTW, SEQ, 64, 64);
  {
    const uint64_t dims[3] = {64, NMAIN * 128, 4}, st[2] = {HD * 2, 128}; const uint32_t box[3] = {64, 64, 4};
    make_map(enc, &p.qc, qc_ptr, 3, dims, st, box);
  }
  concat_heads__ssm_conv_h3__compressed_kv_cla__prompt_kernel<<<NCTA, NTHREADS, SMEM_BYTES>>>(p);
}
```

```cpp
#include <cuda_runtime.h>
#include <cuda_bf16.h>
#include <cuda.h>
#include <stdint.h>

namespace {

typedef __nv_bfloat16 bf16;

constexpr int SEQ  = 2048;
constexpr int DA   = 448;
constexpr int NH   = 16;
constexpr int HD   = 256;
constexpr int DM   = 448;
constexpr int DC   = 1024;
constexpr int OUTW = DA + DM;
constexpr int NMAIN = 128;
constexpr int NCONV = 4;
constexpr int NCTA  = NMAIN + NCONV;
constexpr int LOG_DONE = 8;
constexpr int NTHREADS = 384;

__device__ __align__(1024) bf16 g_kv[2ull * SEQ * NH * HD];
__device__ __align__(1024) bf16 g_qc[(size_t)NMAIN * 128 * HD];
__device__ __align__(128) uint8_t g_xs[DA * SEQ * 2];
constexpr uint32_t HO_STRIDE = 4224;
__device__ __align__(128) uint8_t g_ho[DA * HO_STRIDE];
struct alignas(128) Flag { unsigned v; unsigned pad[31]; };
struct Flags {
  Flag kv_ready[NH];
  Flag ctx_ready[NMAIN * 2];
  Flag x_ready[7];
  Flag z_ready[7];
  Flag zero_ready[16];
  alignas(128) unsigned long long done;
};
__device__ Flags g_flags;
#define TS(i)
#define TSC(i, cond)
#define TDUMP()
#define GT(i)
#define PT(i)
#define PCLK(var)
#define PACC(acc, t0)

struct alignas(64) Params {
  CUtensorMap ckv;
  CUtensorMap wuk;
  CUtensorMap wuv;
  CUtensorMap x;
  CUtensorMap wq;
  CUtensorMap kv;
  CUtensorMap o;
  CUtensorMap qc;
  CUtensorMap wo;
  const bf16 *a_q, *a_k, *a_v, *a_shift, *a_ssmk, *a_D;
  bf16* out;
};

constexpr uint32_t SLOT     = 32768;
constexpr int      NSLOT    = 5;
constexpr uint32_t QREG     = 163840;
constexpr uint32_t BARS     = 229376;
constexpr uint32_t SMEM_BYTES = BARS + 1024 + 1024;
enum : uint32_t {
  B_FULL = 0, B_EMPTY = 5, B_XFREE = 10, B_ST_KV = 12, B_ST_Q = 14, B_ST_CTX = 16, B_KVOK = 18, B_DONE = 19, B_QFREE = 20, B_QFULL = 22,
  B_S2_FULL = 24, B_S2_EMPTY = 32
};
constexpr int P1_STEPS = 4 * 16 + 2 * 7, P1_XS = P1_STEPS - 2;

template <typename T> __device__ __forceinline__ T* at(const void* base, uint32_t off) {
  asm volatile("" : "+r"(off));
  return reinterpret_cast<T*>(const_cast<char*>(static_cast<const char*>(base)) + off);
}
__device__ __forceinline__ unsigned* flag_at(Flag* f, uint32_t i) { return at<unsigned>(f, i * (uint32_t)sizeof(Flag)); }
__device__ __forceinline__ uint32_t smem_u32(const void* p) { return (uint32_t)__cvta_generic_to_shared(p); }
__device__ __forceinline__ void mbar_init(uint32_t bar, uint32_t cnt) {
  asm volatile("mbarrier.init.shared::cta.b64 [%0], %1;" :: "r"(bar), "r"(cnt) : "memory");
}
__device__ __forceinline__ void mbar_expect_tx(uint32_t bar, uint32_t bytes) {
  asm volatile("mbarrier.arrive.expect_tx.shared::cta.b64 _, [%0], %1;" :: "r"(bar), "r"(bytes) : "memory");
}
__device__ __forceinline__ void mbar_arrive(uint32_t bar) {
  asm volatile("mbarrier.arrive.shared::cta.b64 _, [%0];" :: "r"(bar) : "memory");
}
__device__ __forceinline__ void mbar_arrive_n(uint32_t bar, uint32_t n) {
  asm volatile("mbarrier.arrive.shared::cta.b64 _, [%0], %1;" :: "r"(bar), "r"(n) : "memory");
}
__device__ __forceinline__ void mbar_arrive_remote(uint32_t bar, uint32_t cta) {
  asm volatile("{\n.reg .b32 ra;\nmapa.shared::cluster.u32 ra, %0, %1;\n"
               "mbarrier.arrive.shared::cluster.b64 _, [ra];\n}" :: "r"(bar), "r"(cta) : "memory");
}
__device__ __forceinline__ bool mbar_try(uint32_t bar, uint32_t parity) {
  uint32_t ok;
  asm volatile("{\n.reg .pred p;\nmbarrier.try_wait.parity.shared::cta.b64 p, [%1], %2;\nselp.u32 %0, 1, 0, p;\n}"
               : "=r"(ok) : "r"(bar), "r"(parity) : "memory");
  return ok;
}
constexpr uint32_t SPIN_LIMIT = 1u << 24;
__device__ __forceinline__ void mbar_wait(uint32_t bar, uint32_t parity) {
  if (mbar_try(bar, parity)) return;
  uint32_t n = 0;
  while (!mbar_try(bar, parity)) { if (++n > SPIN_LIMIT) __trap(); }
}
__device__ __forceinline__ unsigned load_epoch() {
  unsigned long long d; asm volatile("ld.relaxed.gpu.global.u64 %0, [%1];" : "=l"(d) : "l"(&g_flags.done) : "memory");
  return (unsigned)(d >> LOG_DONE);
}
__device__ __forceinline__ void flag_wait(const unsigned* f, unsigned count, unsigned epoch) {
  const unsigned target = (epoch + 1) * count;
  uint32_t n = 0;
  while (true) {
    unsigned v;
    asm volatile("ld.acquire.gpu.global.u32 %0, [%1];" : "=r"(v) : "l"(f) : "memory");
    if ((int)(v - target) >= 0) break;
    if (++n > SPIN_LIMIT) __trap();
    __nanosleep(20);
  }
}
__device__ __forceinline__ void flag_wait_slow(const unsigned* f, unsigned count, unsigned epoch) {
  const unsigned target = (epoch + 1) * count;
  uint32_t n = 0;
  while (true) {
    unsigned v;
    asm volatile("ld.acquire.gpu.global.u32 %0, [%1];" : "=r"(v) : "l"(f) : "memory");
    if ((int)(v - target) >= 0) break;
    if (++n > SPIN_LIMIT / 16) __trap();
    __nanosleep(1000);
  }
}
__device__ __forceinline__ void cta_done(unsigned long long n) { asm volatile("red.relaxed.gpu.global.add.u64 [%0], %1;" :: "l"(&g_flags.done), "l"(n) : "memory"); }
__device__ __forceinline__ void flag_wait_fast(const unsigned* f, unsigned count, unsigned epoch) {
  const unsigned target = (epoch + 1) * count;
  uint32_t n = 0;
  while (true) {
    unsigned v;
    asm volatile("ld.acquire.gpu.global.u32 %0, [%1];" : "=r"(v) : "l"(f) : "memory");
    if ((int)(v - target) >= 0) break;
    if (++n > SPIN_LIMIT) __trap();
  }
}
__device__ __forceinline__ void fence_async_all() { asm volatile("fence.proxy.async;" ::: "memory"); }
__device__ __forceinline__ void flag_signal(unsigned* f) {
  asm volatile("fence.acq_rel.gpu;" ::: "memory");
  asm volatile("red.relaxed.gpu.global.add.u32 [%0], 1;" :: "l"(f) : "memory");
}
__device__ __forceinline__ void flag_signal_after_bulk(unsigned* f) {
  asm volatile("red.relaxed.gpu.global.add.u32 [%0], 1;" :: "l"(f) : "memory");
}
__device__ __forceinline__ void fence_async_smem() { asm volatile("fence.proxy.async.shared::cta;" ::: "memory"); }
#define HINTS 0
constexpr uint64_t POL_NORMAL = 0x1000000000000000ull, POL_FIRST = 0x12F0000000000000ull;
__device__ __forceinline__ constexpr uint64_t pol(bool first) { return first ? POL_FIRST : POL_NORMAL; }
__device__ __forceinline__ void tma_ld2(uint32_t dst, const CUtensorMap* m, uint32_t bar, int c0, int c1, uint64_t pl = POL_NORMAL) {
  asm volatile("cp.async.bulk.tensor.2d.shared::cluster.global.mbarrier::complete_tx::bytes.L2::cache_hint [%0], [%1, {%3, %4}], [%2], %5;"
               :: "r"(dst), "l"(m), "r"(bar), "r"(c0), "r"(c1), "l"(pl) : "memory");
}
__device__ __forceinline__ void tma_ld3(uint32_t dst, const CUtensorMap* m, uint32_t bar, int c0, int c1, int c2, uint64_t pl = POL_NORMAL) {
  asm volatile("cp.async.bulk.tensor.3d.shared::cluster.global.mbarrier::complete_tx::bytes.L2::cache_hint [%0], [%1, {%3, %4, %5}], [%2], %6;"
               :: "r"(dst), "l"(m), "r"(bar), "r"(c0), "r"(c1), "r"(c2), "l"(pl) : "memory");
}
__device__ __forceinline__ void tma_ld3_mc(uint32_t dst, const CUtensorMap* m, uint32_t bar, int c0, int c1, int c2, uint64_t pl = POL_NORMAL) {
  asm volatile("cp.async.bulk.tensor.3d.shared::cluster.global.mbarrier::complete_tx::bytes.multicast::cluster.L2::cache_hint [%0], [%1, {%3, %4, %5}], [%2], %6, %7;"
               :: "r"(dst), "l"(m), "r"(bar), "r"(c0), "r"(c1), "r"(c2), "h"((uint16_t)3), "l"(pl) : "memory");
}
__device__ __forceinline__ void bulk_ld(uint32_t dst, const void* src, uint32_t bytes, uint32_t bar) {
  asm volatile("cp.async.bulk.shared::cluster.global.mbarrier::complete_tx::bytes [%0], [%1], %2, [%3];"
               :: "r"(dst), "l"(src), "r"(bytes), "r"(bar) : "memory");
}
__device__ __forceinline__ void tma_st3(const CUtensorMap* m, uint32_t src, int c0, int c1, int c2) {
  asm volatile("cp.async.bulk.tensor.3d.global.shared::cta.bulk_group.L2::cache_hint [%0, {%2, %3, %4}], [%1], %5;"
               :: "l"(m), "r"(src), "r"(c0), "r"(c1), "r"(c2), "l"(pol(HINTS & 1024)) : "memory");
}
__device__ __forceinline__ void tma_ld2_mc(uint32_t dst, const CUtensorMap* m, uint32_t bar, int c0, int c1, uint64_t pl = POL_NORMAL) {
  asm volatile("cp.async.bulk.tensor.2d.shared::cluster.global.mbarrier::complete_tx::bytes.multicast::cluster.L2::cache_hint [%0], [%1, {%3, %4}], [%2], %5, %6;"
               :: "r"(dst), "l"(m), "r"(bar), "r"(c0), "r"(c1), "h"((uint16_t)3), "l"(pl) : "memory");
}
__device__ __forceinline__ void tma_ld5_mc(uint32_t dst, const CUtensorMap* m, uint32_t bar, int c0, int c4, uint64_t pl = POL_NORMAL) {
  asm volatile("cp.async.bulk.tensor.5d.shared::cluster.global.mbarrier::complete_tx::bytes.multicast::cluster.L2::cache_hint [%0], [%1, {%3, %7, %7, %7, %4}], [%2], %5, %6;"
               :: "r"(dst), "l"(m), "r"(bar), "r"(c0), "r"(c4), "h"((uint16_t)3), "l"(pl), "r"(0) : "memory");
}
__device__ __forceinline__ void tma_st2(const CUtensorMap* m, uint32_t src, int c0, int c1) {
  asm volatile("cp.async.bulk.tensor.2d.global.shared::cta.bulk_group [%0, {%2, %3}], [%1];"
               :: "l"(m), "r"(src), "r"(c0), "r"(c1) : "memory");
}
__device__ __forceinline__ void tma_red2(const CUtensorMap* m, uint32_t src, int c0, int c1) {
  asm volatile("cp.reduce.async.bulk.tensor.2d.global.shared::cta.add.bulk_group [%0, {%2, %3}], [%1];"
               :: "l"(m), "r"(src), "r"(c0), "r"(c1) : "memory");
}
__device__ __forceinline__ void bulk_commit() { asm volatile("cp.async.bulk.commit_group;" ::: "memory"); }
__device__ __forceinline__ void bulk_wait_read() { asm volatile("cp.async.bulk.wait_group.read 0;" ::: "memory"); }
__device__ __forceinline__ void bulk_wait_all() { asm volatile("cp.async.bulk.wait_group 0;" ::: "memory"); }
__device__ __forceinline__ void prefetch_map(const CUtensorMap* m) { asm volatile("prefetch.tensormap [%0];" :: "l"(m) : "memory"); }
__device__ __forceinline__ void wg_fence() { asm volatile("wgmma.fence.sync.aligned;" ::: "memory"); }
__device__ __forceinline__ void wg_commit() { asm volatile("wgmma.commit_group.sync.aligned;" ::: "memory"); }
template <int N> __device__ __forceinline__ void wg_wait() { asm volatile("wgmma.wait_group.sync.aligned %0;" :: "n"(N) : "memory"); }
template <int N> __device__ __forceinline__ void reg_fence(float (&d)[N]) {
#pragma unroll
  for (int i = 0; i < N; i++) asm volatile("" : "+f"(d[i]) :: "memory");
}
template <int N> __device__ __forceinline__ void reg_fence(uint32_t (&d)[N]) {
#pragma unroll
  for (int i = 0; i < N; i++) asm volatile("" : "+r"(d[i]) :: "memory");
}
__device__ __forceinline__ uint32_t fresh_tid() { uint32_t t; asm volatile("mov.u32 %0, %%tid.x;" : "=r"(t)); return t; }
__device__ __forceinline__ uint32_t lane_base16() {
  const uint32_t t = fresh_tid(), lane = t & 31, wq = (t >> 5) & 3;
  return (16 * wq + (lane & 7) + 8 * ((lane >> 3) & 1)) * 128 + (((lane >> 4) ^ (lane & 7)) << 4);
}
__device__ __forceinline__ void named_sync(int id, int n) { asm volatile("bar.sync %0, %1;" :: "r"(id), "r"(n) : "memory"); }
__device__ __forceinline__ void named_arrive(int id, int n) { asm volatile("bar.arrive %0, %1;" :: "r"(id), "r"(n) : "memory"); }
__device__ __forceinline__ uint32_t pack_bf16(float lo, float hi) {
  uint32_t r; asm("cvt.rn.bf16x2.f32 %0, %1, %2;" : "=r"(r) : "f"(hi), "f"(lo)); return r;
}
__device__ __forceinline__ float ex2(float x) { float y; asm("ex2.approx.ftz.f32 %0, %1;" : "=f"(y) : "f"(x)); return y; }
__device__ __forceinline__ void stsm4(uint32_t addr, uint32_t a, uint32_t b, uint32_t c, uint32_t d) {
  asm volatile("stmatrix.sync.aligned.m8n8.x4.shared.b16 [%0], {%1, %2, %3, %4};" :: "r"(addr), "r"(a), "r"(b), "r"(c), "r"(d) : "memory");
}
__device__ __forceinline__ uint64_t mk_desc(uint32_t addr, uint32_t lbo, uint32_t sbo) {
  return (uint64_t)(((addr & 0x3FFFF) >> 4) | ((lbo >> 4) << 16)) | ((uint64_t)((sbo >> 4) | (1u << 30)) << 32);
}
__device__ __forceinline__ uint64_t desc_k(uint32_t addr)  { return mk_desc(addr, 16, 1024); }
__device__ __forceinline__ uint64_t desc_mn(uint32_t addr) { return mk_desc(addr, 8192, 1024); }
__device__ __forceinline__ uint64_t desc_add(uint64_t d, uint32_t bytes) { return d + (bytes >> 4); }

__device__ __forceinline__ void wgmma_ss_n256_tb(float (&d)[128], uint64_t da, uint64_t db, int sd) {
  asm volatile("{\n.reg .pred p;\nsetp.ne.b32 p, %130, 0;\n"
    "wgmma.mma_async.sync.aligned.m64n256k16.f32.bf16.bf16 "
    "{%0, %1, %2, %3, %4, %5, %6, %7, %8, %9, %10, %11, %12, %13, %14, %15, "
    "%16, %17, %18, %19, %20, %21, %22, %23, %24, %25, %26, %27, %28, %29, %30, %31, "
    "%32, %33, %34, %35, %36, %37, %38, %39, %40, %41, %42, %43, %44, %45, %46, %47, "
    "%48, %49, %50, %51, %52, %53, %54, %55, %56, %57, %58, %59, %60, %61, %62, %63, "
    "%64, %65, %66, %67, %68, %69, %70, %71, %72, %73, %74, %75, %76, %77, %78, %79, "
    "%80, %81, %82, %83, %84, %85, %86, %87, %88, %89, %90, %91, %92, %93, %94, %95, "
    "%96, %97, %98, %99, %100, %101, %102, %103, %104, %105, %106, %107, %108, %109, %110, %111, "
    "%112, %113, %114, %115, %116, %117, %118, %119, %120, %121, %122, %123, %124, %125, %126, %127}, "
    "%128, %129, p, 1, 1, 0, 1;\n}"
    : "+f"(d[0]), "+f"(d[1]), "+f"(d[2]), "+f"(d[3]), "+f"(d[4]), "+f"(d[5]), "+f"(d[6]), "+f"(d[7]),
      "+f"(d[8]), "+f"(d[9]), "+f"(d[10]), "+f"(d[11]), "+f"(d[12]), "+f"(d[13]), "+f"(d[14]), "+f"(d[15]),
      "+f"(d[16]), "+f"(d[17]), "+f"(d[18]), "+f"(d[19]), "+f"(d[20]), "+f"(d[21]), "+f"(d[22]), "+f"(d[23]),
      "+f"(d[24]), "+f"(d[25]), "+f"(d[26]), "+f"(d[27]), "+f"(d[28]), "+f"(d[29]), "+f"(d[30]), "+f"(d[31]),
      "+f"(d[32]), "+f"(d[33]), "+f"(d[34]), "+f"(d[35]), "+f"(d[36]), "+f"(d[37]), "+f"(d[38]), "+f"(d[39]),
      "+f"(d[40]), "+f"(d[41]), "+f"(d[42]), "+f"(d[43]), "+f"(d[44]), "+f"(d[45]), "+f"(d[46]), "+f"(d[47]),
      "+f"(d[48]), "+f"(d[49]), "+f"(d[50]), "+f"(d[51]), "+f"(d[52]), "+f"(d[53]), "+f"(d[54]), "+f"(d[55]),
      "+f"(d[56]), "+f"(d[57]), "+f"(d[58]), "+f"(d[59]), "+f"(d[60]), "+f"(d[61]), "+f"(d[62]), "+f"(d[63]),
      "+f"(d[64]), "+f"(d[65]), "+f"(d[66]), "+f"(d[67]), "+f"(d[68]), "+f"(d[69]), "+f"(d[70]), "+f"(d[71]),
      "+f"(d[72]), "+f"(d[73]), "+f"(d[74]), "+f"(d[75]), "+f"(d[76]), "+f"(d[77]), "+f"(d[78]), "+f"(d[79]),
      "+f"(d[80]), "+f"(d[81]), "+f"(d[82]), "+f"(d[83]), "+f"(d[84]), "+f"(d[85]), "+f"(d[86]), "+f"(d[87]),
      "+f"(d[88]), "+f"(d[89]), "+f"(d[90]), "+f"(d[91]), "+f"(d[92]), "+f"(d[93]), "+f"(d[94]), "+f"(d[95]),
      "+f"(d[96]), "+f"(d[97]), "+f"(d[98]), "+f"(d[99]), "+f"(d[100]), "+f"(d[101]), "+f"(d[102]), "+f"(d[103]),
      "+f"(d[104]), "+f"(d[105]), "+f"(d[106]), "+f"(d[107]), "+f"(d[108]), "+f"(d[109]), "+f"(d[110]), "+f"(d[111]),
      "+f"(d[112]), "+f"(d[113]), "+f"(d[114]), "+f"(d[115]), "+f"(d[116]), "+f"(d[117]), "+f"(d[118]), "+f"(d[119]),
      "+f"(d[120]), "+f"(d[121]), "+f"(d[122]), "+f"(d[123]), "+f"(d[124]), "+f"(d[125]), "+f"(d[126]), "+f"(d[127])
    : "l"(da), "l"(db), "r"(sd));
}
__device__ __forceinline__ void wgmma_ss_n64(float (&d)[32], uint64_t da, uint64_t db, int sd) {
  asm volatile("{\n.reg .pred p;\nsetp.ne.b32 p, %34, 0;\n"
    "wgmma.mma_async.sync.aligned.m64n64k16.f32.bf16.bf16 "
    "{%0, %1, %2, %3, %4, %5, %6, %7, %8, %9, %10, %11, %12, %13, %14, %15, "
    "%16, %17, %18, %19, %20, %21, %22, %23, %24, %25, %26, %27, %28, %29, %30, %31}, "
    "%32, %33, p, 1, 1, 0, 0;\n}"
    : "+f"(d[0]), "+f"(d[1]), "+f"(d[2]), "+f"(d[3]), "+f"(d[4]), "+f"(d[5]), "+f"(d[6]), "+f"(d[7]),
      "+f"(d[8]), "+f"(d[9]), "+f"(d[10]), "+f"(d[11]), "+f"(d[12]), "+f"(d[13]), "+f"(d[14]), "+f"(d[15]),
      "+f"(d[16]), "+f"(d[17]), "+f"(d[18]), "+f"(d[19]), "+f"(d[20]), "+f"(d[21]), "+f"(d[22]), "+f"(d[23]),
      "+f"(d[24]), "+f"(d[25]), "+f"(d[26]), "+f"(d[27]), "+f"(d[28]), "+f"(d[29]), "+f"(d[30]), "+f"(d[31])
    : "l"(da), "l"(db), "r"(sd));
}
__device__ __forceinline__ void wgmma_rs_n256_tb(float (&d)[128], uint32_t a0, uint32_t a1, uint32_t a2, uint32_t a3, uint64_t db, int sd) {
  asm volatile("{\n.reg .pred p;\nsetp.ne.b32 p, %133, 0;\n"
    "wgmma.mma_async.sync.aligned.m64n256k16.f32.bf16.bf16 "
    "{%0, %1, %2, %3, %4, %5, %6, %7, %8, %9, %10, %11, %12, %13, %14, %15, "
    "%16, %17, %18, %19, %20, %21, %22, %23, %24, %25, %26, %27, %28, %29, %30, %31, "
    "%32, %33, %34, %35, %36, %37, %38, %39, %40, %41, %42, %43, %44, %45, %46, %47, "
    "%48, %49, %50, %51, %52, %53, %54, %55, %56, %57, %58, %59, %60, %61, %62, %63, "
    "%64, %65, %66, %67, %68, %69, %70, %71, %72, %73, %74, %75, %76, %77, %78, %79, "
    "%80, %81, %82, %83, %84, %85, %86, %87, %88, %89, %90, %91, %92, %93, %94, %95, "
    "%96, %97, %98, %99, %100, %101, %102, %103, %104, %105, %106, %107, %108, %109, %110, %111, "
    "%112, %113, %114, %115, %116, %117, %118, %119, %120, %121, %122, %123, %124, %125, %126, %127}, "
    "{%128, %129, %130, %131}, %132, p, 1, 1, 1;\n}"
    : "+f"(d[0]), "+f"(d[1]), "+f"(d[2]), "+f"(d[3]), "+f"(d[4]), "+f"(d[5]), "+f"(d[6]), "+f"(d[7]),
      "+f"(d[8]), "+f"(d[9]), "+f"(d[10]), "+f"(d[11]), "+f"(d[12]), "+f"(d[13]), "+f"(d[14]), "+f"(d[15]),
      "+f"(d[16]), "+f"(d[17]), "+f"(d[18]), "+f"(d[19]), "+f"(d[20]), "+f"(d[21]), "+f"(d[22]), "+f"(d[23]),
      "+f"(d[24]), "+f"(d[25]), "+f"(d[26]), "+f"(d[27]), "+f"(d[28]), "+f"(d[29]), "+f"(d[30]), "+f"(d[31]),
      "+f"(d[32]), "+f"(d[33]), "+f"(d[34]), "+f"(d[35]), "+f"(d[36]), "+f"(d[37]), "+f"(d[38]), "+f"(d[39]),
      "+f"(d[40]), "+f"(d[41]), "+f"(d[42]), "+f"(d[43]), "+f"(d[44]), "+f"(d[45]), "+f"(d[46]), "+f"(d[47]),
      "+f"(d[48]), "+f"(d[49]), "+f"(d[50]), "+f"(d[51]), "+f"(d[52]), "+f"(d[53]), "+f"(d[54]), "+f"(d[55]),
      "+f"(d[56]), "+f"(d[57]), "+f"(d[58]), "+f"(d[59]), "+f"(d[60]), "+f"(d[61]), "+f"(d[62]), "+f"(d[63]),
      "+f"(d[64]), "+f"(d[65]), "+f"(d[66]), "+f"(d[67]), "+f"(d[68]), "+f"(d[69]), "+f"(d[70]), "+f"(d[71]),
      "+f"(d[72]), "+f"(d[73]), "+f"(d[74]), "+f"(d[75]), "+f"(d[76]), "+f"(d[77]), "+f"(d[78]), "+f"(d[79]),
      "+f"(d[80]), "+f"(d[81]), "+f"(d[82]), "+f"(d[83]), "+f"(d[84]), "+f"(d[85]), "+f"(d[86]), "+f"(d[87]),
      "+f"(d[88]), "+f"(d[89]), "+f"(d[90]), "+f"(d[91]), "+f"(d[92]), "+f"(d[93]), "+f"(d[94]), "+f"(d[95]),
      "+f"(d[96]), "+f"(d[97]), "+f"(d[98]), "+f"(d[99]), "+f"(d[100]), "+f"(d[101]), "+f"(d[102]), "+f"(d[103]),
      "+f"(d[104]), "+f"(d[105]), "+f"(d[106]), "+f"(d[107]), "+f"(d[108]), "+f"(d[109]), "+f"(d[110]), "+f"(d[111]),
      "+f"(d[112]), "+f"(d[113]), "+f"(d[114]), "+f"(d[115]), "+f"(d[116]), "+f"(d[117]), "+f"(d[118]), "+f"(d[119]),
      "+f"(d[120]), "+f"(d[121]), "+f"(d[122]), "+f"(d[123]), "+f"(d[124]), "+f"(d[125]), "+f"(d[126]), "+f"(d[127])
    : "r"(a0), "r"(a1), "r"(a2), "r"(a3), "l"(db), "r"(sd));
}
__device__ __forceinline__ void wgmma_rs_n64_tb(float (&d)[32], uint32_t a0, uint32_t a1, uint32_t a2, uint32_t a3, uint64_t db, int sd) {
  asm volatile("{\n.reg .pred p;\nsetp.ne.b32 p, %37, 0;\n"
    "wgmma.mma_async.sync.aligned.m64n64k16.f32.bf16.bf16 "
    "{%0, %1, %2, %3, %4, %5, %6, %7, %8, %9, %10, %11, %12, %13, %14, %15, "
    "%16, %17, %18, %19, %20, %21, %22, %23, %24, %25, %26, %27, %28, %29, %30, %31}, "
    "{%32, %33, %34, %35}, %36, p, 1, 1, 1;\n}"
    : "+f"(d[0]), "+f"(d[1]), "+f"(d[2]), "+f"(d[3]), "+f"(d[4]), "+f"(d[5]), "+f"(d[6]), "+f"(d[7]),
      "+f"(d[8]), "+f"(d[9]), "+f"(d[10]), "+f"(d[11]), "+f"(d[12]), "+f"(d[13]), "+f"(d[14]), "+f"(d[15]),
      "+f"(d[16]), "+f"(d[17]), "+f"(d[18]), "+f"(d[19]), "+f"(d[20]), "+f"(d[21]), "+f"(d[22]), "+f"(d[23]),
      "+f"(d[24]), "+f"(d[25]), "+f"(d[26]), "+f"(d[27]), "+f"(d[28]), "+f"(d[29]), "+f"(d[30]), "+f"(d[31])
    : "r"(a0), "r"(a1), "r"(a2), "r"(a3), "l"(db), "r"(sd));
}
__device__ __forceinline__ void wgmma_rs_n32(float (&d)[16], uint32_t a0, uint32_t a1, uint32_t a2, uint32_t a3, uint64_t db, int sd) {
  asm volatile("{\n.reg .pred p;\nsetp.ne.b32 p, %21, 0;\n"
    "wgmma.mma_async.sync.aligned.m64n32k16.f32.bf16.bf16 "
    "{%0, %1, %2, %3, %4, %5, %6, %7, %8, %9, %10, %11, %12, %13, %14, %15}, "
    "{%16, %17, %18, %19}, %20, p, 1, 1, 0;\n}"
    : "+f"(d[0]), "+f"(d[1]), "+f"(d[2]), "+f"(d[3]), "+f"(d[4]), "+f"(d[5]), "+f"(d[6]), "+f"(d[7]),
      "+f"(d[8]), "+f"(d[9]), "+f"(d[10]), "+f"(d[11]), "+f"(d[12]), "+f"(d[13]), "+f"(d[14]), "+f"(d[15])
    : "r"(a0), "r"(a1), "r"(a2), "r"(a3), "l"(db), "r"(sd));
}
__device__ __forceinline__ void wgmma_rs_n64(float (&d)[32], uint32_t a0, uint32_t a1, uint32_t a2, uint32_t a3, uint64_t db, int sd) {
  asm volatile("{\n.reg .pred p;\nsetp.ne.b32 p, %37, 0;\n"
    "wgmma.mma_async.sync.aligned.m64n64k16.f32.bf16.bf16 "
    "{%0, %1, %2, %3, %4, %5, %6, %7, %8, %9, %10, %11, %12, %13, %14, %15, "
    "%16, %17, %18, %19, %20, %21, %22, %23, %24, %25, %26, %27, %28, %29, %30, %31}, "
    "{%32, %33, %34, %35}, %36, p, 1, 1, 0;\n}"
    : "+f"(d[0]), "+f"(d[1]), "+f"(d[2]), "+f"(d[3]), "+f"(d[4]), "+f"(d[5]), "+f"(d[6]), "+f"(d[7]),
      "+f"(d[8]), "+f"(d[9]), "+f"(d[10]), "+f"(d[11]), "+f"(d[12]), "+f"(d[13]), "+f"(d[14]), "+f"(d[15]),
      "+f"(d[16]), "+f"(d[17]), "+f"(d[18]), "+f"(d[19]), "+f"(d[20]), "+f"(d[21]), "+f"(d[22]), "+f"(d[23]),
      "+f"(d[24]), "+f"(d[25]), "+f"(d[26]), "+f"(d[27]), "+f"(d[28]), "+f"(d[29]), "+f"(d[30]), "+f"(d[31])
    : "r"(a0), "r"(a1), "r"(a2), "r"(a3), "l"(db), "r"(sd));
}

__device__ __forceinline__ uint4 lds16(uint32_t a) {
  uint4 v; asm volatile("ld.shared.v4.u32 {%0, %1, %2, %3}, [%4];" : "=r"(v.x), "=r"(v.y), "=r"(v.z), "=r"(v.w) : "r"(a) : "memory"); return v;
}
__device__ __forceinline__ void sts16(uint32_t a, uint32_t x, uint32_t y, uint32_t z, uint32_t w) {
  asm volatile("st.shared.v4.u32 [%0], {%1, %2, %3, %4};" :: "r"(a), "r"(x), "r"(y), "r"(z), "r"(w) : "memory");
}
__device__ __forceinline__ uint32_t lds4(uint32_t a) { uint32_t v; asm volatile("ld.shared.u32 %0, [%1];" : "=r"(v) : "r"(a) : "memory"); return v; }
__device__ __forceinline__ uint32_t lds4v(uint32_t a) { uint32_t v; asm volatile("ld.volatile.shared.u32 %0, [%1];" : "=r"(v) : "r"(a) : "memory"); return v; }
__device__ __forceinline__ uint32_t bmul(uint32_t a, uint32_t b) { uint32_t r; asm("mul.rn.bf16x2 %0, %1, %2;" : "=r"(r) : "r"(a), "r"(b)); return r; }
__device__ __forceinline__ uint32_t badd(uint32_t a, uint32_t b) { uint32_t r; asm("add.rn.bf16x2 %0, %1, %2;" : "=r"(r) : "r"(a), "r"(b)); return r; }

__device__ __forceinline__ void ldsm4(uint32_t (&r)[4], uint32_t a) {
  asm volatile("ldmatrix.sync.aligned.m8n8.x4.shared.b16 {%0, %1, %2, %3}, [%4];" : "=r"(r[0]), "=r"(r[1]), "=r"(r[2]), "=r"(r[3]) : "r"(a) : "memory");
}
__device__ __forceinline__ uint32_t transpose8(uint32_t a) { uint32_t d; asm volatile("movmatrix.sync.aligned.m8n8.trans.b16 %0, %1;" : "=r"(d) : "r"(a)); return d; }

__device__ __forceinline__ void mma16816(float (&d)[4], const uint32_t (&a)[4], uint32_t b0, uint32_t b1) {
  asm volatile("mma.sync.aligned.m16n8k16.row.col.f32.bf16.bf16.f32 {%0, %1, %2, %3}, {%4, %5, %6, %7}, {%8, %9}, {%0, %1, %2, %3};"
               : "+f"(d[0]), "+f"(d[1]), "+f"(d[2]), "+f"(d[3]) : "r"(a[0]), "r"(a[1]), "r"(a[2]), "r"(a[3]), "r"(b0), "r"(b1));
}

#define EXP_SIDE 0
#define SIDE_AHEAD 3
#define ZERO_RD 4
#define CTX_SPLIT 10
#define CONV_EARLY 8
#define CONV_FENCE 12
#define CONV_ARRIVE 13
#define ARRIVE_KK 12
#define SIDE_DELAY_NS 4000
#define KVH(h) (h)
#define HEAD_MAP 1
#define EARLY_LD 3
constexpr int RED_BAR = 6;
constexpr int CV_BAR = 5;
constexpr int PP_BAR = 3;
template <int V> struct Int { static constexpr int value = V; };
struct Ring {
  uint32_t slot, phase;
  __device__ __forceinline__ void next() { if (++slot == NSLOT) { slot = 0; phase ^= 1; } }
};
__device__ __forceinline__ uint32_t bar_addr(uint32_t sb, uint32_t i) { return sb + BARS + 8 * i; }

__device__ __forceinline__ int q_tile(int h, int j, int which) { return ((h < 8) == (which == 0)) ? 15 - j : j; }

__device__ __forceinline__ int att_head(int h, int which) { return h; }
__device__ __forceinline__ int p1_head(int h, int t) { return h; }
__device__ __forceinline__ int p1_isv(int t) { return t >> 1; }
__device__ __forceinline__ int p1_rows(int h, int j, int t) { return 2 * j + (t & 1); }
#define KV_FLAG(h) (h)
#define KV_COUNT 16

__device__ __forceinline__ void load_tile4(uint32_t dst, const CUtensorMap* m, uint32_t full, int row, int blk0, int rank, bool shared, uint64_t pl = POL_NORMAL) {
  if (shared) {
    tma_ld3_mc(dst + rank * 16384, m, full, 0, row, blk0 + 2 * rank, pl);
  } else {
    tma_ld3(dst, m, full, 0, row, blk0, pl);
    tma_ld3(dst + 16384, m, full, 0, row, blk0 + 2, pl);
  }
}
__device__ __forceinline__ void producer_main(const Params& p, uint32_t sb, int h, int j) {
  const int rank = j & 1;
  Ring r{EARLY_LD, 0};
  auto wait_slot = [&]() { mbar_wait(bar_addr(sb, B_EMPTY + r.slot), r.phase ^ 1); };
  auto load_a = [&](int it, uint32_t dst, uint32_t full) {
    if (it < 64) tma_ld2(dst, &p.ckv, full, (it & 15) * 64, p1_rows(h, j, it >> 4) * 128, pol((HINTS & 2) && it >= 48));
    else tma_ld2(dst, &p.x, full, (it < 71 ? it - 64 : it - 71) * 64, q_tile(h, j, it < 71) * 128, pol(HINTS & 64));
  };
  uint32_t prev = 0;
#pragma unroll 1
  for (int it = EARLY_LD; it < P1_STEPS; it++) {
    wait_slot();
    if (it > EARLY_LD && it <= P1_XS) load_a(it - 1, sb + QREG + ((it - 1) & 3) * 16384, prev);
    const uint32_t full = bar_addr(sb, B_FULL + r.slot), dst = sb + r.slot * SLOT;
    mbar_expect_tx(full, it < P1_XS ? 49152 : 32768);
    if (it < 64) load_tile4(dst, p1_isv(it >> 4) ? &p.wuv : &p.wuk, full, (it & 15) * 64, p1_head(h, it >> 4) * 4, rank, true, pol(HINTS & 1));
    else load_tile4(dst, &p.wq, full, (it < 71 ? it - 64 : it - 71) * 64, att_head(h, it < 71) * 4, rank, true, pol(HINTS & 4));
    prev = full;
    r.next();
    if (it == P1_XS) {
      wait_slot();
      const uint32_t f2 = bar_addr(sb, B_FULL + r.slot);
      mbar_expect_tx(f2, 32768);
      load_a(P1_XS, sb + r.slot * SLOT, f2);
      load_a(P1_XS + 1, sb + r.slot * SLOT + 16384, f2);
      r.next();
    }
  }
  mbar_wait(bar_addr(sb, B_KVOK), 0);
  const int qa = q_tile(h, j, 0), na = 2 * qa + 2, own = 2 * (qa & ~1) + 2;
#pragma unroll 1
  for (int f = 0; f < 68; f++) {
    const bool isK = (f == 0) || ((f & 1) && f < 67);
    const int i = isK ? (f + 1) >> 1 : (f - 1) >> 1, which = i >= na;
    wait_slot();
    const uint32_t full = bar_addr(sb, B_FULL + r.slot);
    mbar_expect_tx(full, 32768);
    load_tile4(sb + r.slot * SLOT, &p.kv, full, ((isK ? 0 : NH) + KVH(att_head(h, which))) * SEQ + (which ? 33 - i : i) * 64, 0, rank, (i & ~1) != own,
               pol(which ? (HINTS & 32) : (HINTS & 8)));
    r.next();
  }
#pragma unroll 1
  for (int f = 0; f < 14; f++) {
    const int ch = f < 12 ? 2 * (f >> 2) + (f & 1) : 6, par = f < 12 ? (f >> 1) & 1 : f & 1;
    wait_slot();
    const uint32_t full = bar_addr(sb, B_FULL + r.slot);
    mbar_expect_tx(full, 32768);
    tma_ld5_mc(sb + r.slot * SLOT + rank * 16384, &p.wo, full, ch * 64, (par ? att_head(h ^ 8, 0) : att_head(h, 1)) * 8 + rank * 4, pol(HINTS & 16));
    r.next();
  }
}

__device__ __forceinline__ void helper_main(const Params& p, uint32_t sb, int h, int j, int w) {
  const unsigned epoch = load_epoch();
  const int cta = h * 8 + j, qb = q_tile(h, j, 1);
  const uint32_t qreg = sb + QREG + w * 32768, qfull = bar_addr(sb, B_QFULL + w);
  mbar_wait(bar_addr(sb, B_ST_KV + w), 0);
  flag_signal(flag_at(g_flags.kv_ready, KV_FLAG(h)));
  if (w == 0) {
    flag_wait(flag_at(g_flags.kv_ready, KV_FLAG(h)), KV_COUNT, epoch);
    fence_async_all();
    mbar_arrive(bar_addr(sb, B_KVOK));
  }
  mbar_wait(bar_addr(sb, B_ST_Q + w), 0);
  asm volatile("fence.acq_rel.gpu;" ::: "memory");
  fence_async_all();
  mbar_wait(bar_addr(sb, B_QFREE + w), 0);
  mbar_expect_tx(qfull, 32768);
  tma_ld3(qreg, &p.qc, qfull, 0, cta * 128 + w * 64, 0);
  mbar_wait(bar_addr(sb, B_ST_CTX + w), 0);
  flag_signal(flag_at(g_flags.ctx_ready, cta * 2 + w));
  flag_wait(flag_at(g_flags.ctx_ready, (cta ^ 64) * 2 + (w ^ 1)), 1, epoch);
  flag_wait(flag_at(g_flags.zero_ready, qb), 8, epoch);
  fence_async_all();
  mbar_wait(bar_addr(sb, B_QFREE + w), 1);
  mbar_expect_tx(qfull, 32768);
  bulk_ld(qreg, at<uint8_t>(g_qc, ((cta ^ 64) * 2 + (w ^ 1)) * 32768), 32768, qfull);
#pragma unroll 1
  for (int ch = 0; ch < 7; ch++) {
    mbar_wait(bar_addr(sb, B_S2_FULL + w * 4 + (ch & 3)), ch >> 2);
    tma_red2(&p.o, qreg + (ch & 3) * 8192, DA + ch * 64, qb * 128 + (w ^ 1) * 64);
    bulk_commit();
    if (ch < 3) { bulk_wait_read(); mbar_arrive(bar_addr(sb, B_S2_EMPTY + w * 4 + ch)); }
  }
  bulk_wait_read();
  GT(48 + w);
}

__device__ __forceinline__ void store_block(uint32_t base, uint32_t lanebase, const uint32_t (&pk)[16]) {
#pragma unroll
  for (int J = 0; J < 8; J += 2) stsm4(base + (lanebase ^ (J << 4)), pk[2 * J], pk[2 * J + 1], pk[2 * J + 2], pk[2 * J + 3]);
}
__device__ __forceinline__ void pack_chunks(uint32_t (&pk)[64], const float (&acc)[128]) {
#pragma unroll
  for (int i = 0; i < 64; i++) { const int e = 16 * (i >> 3) + 4 * (i & 3) + 2 * ((i >> 2) & 1); pk[i] = pack_bf16(acc[e], acc[e + 1]); }
}
__device__ __forceinline__ uint32_t chunk_off() { const uint32_t t = fresh_tid(); return (16 * ((t >> 5) & 3) + ((t & 31) >> 2)) * 512 + (t & 3) * 16; }
__device__ __forceinline__ void warp_arrive(uint32_t bar, int lane) { __syncwarp(); if (lane == 0) mbar_arrive(bar); }

__device__ __forceinline__ void consumer_main(const Params& p, uint32_t sb, int h, int j, int w) {
  const int lane = threadIdx.x & 31;
  const int rank = j & 1;

  auto turn_begin = [&]() { named_sync(PP_BAR + w, 256); };
  auto turn_end = [&]() { named_arrive(PP_BAR + (w ^ 1), 256); };
  if (w == 1) named_arrive(PP_BAR, 256);
  Ring r{0, 0};
  auto take = [&]() { const uint32_t sl = r.slot; mbar_wait(bar_addr(sb, B_FULL + sl), r.phase); r.next(); return sl; };
  auto give = [&](uint32_t sl) { if (lane < 2) mbar_arrive_remote(bar_addr(sb, B_EMPTY + sl), rank ^ lane); };
  float acc[128];
#pragma unroll
  for (int i = 0; i < 128; i++) acc[i] = 0.f;
  uint32_t pk[64];
#pragma unroll
  for (int i = 0; i < 64; i++) pk[i] = 0;
  TS(0);
  const uint32_t qreg = sb + QREG + w * 32768;
  {
    uint32_t xs = 0, prev = 0, dst = 0;
    int it = 0;
#pragma unroll 1
    for (int t = 0; t < 6; t++) {
      const int nk = t < 4 ? 16 : 7;
#pragma unroll 1
      for (int k = 0; k < nk; k++, it++) {
        const uint32_t ws = take();
        TSC(1, it == 0);
        if (it == P1_XS) xs = take();
        const uint32_t aa = (it < P1_XS ? QREG + (it & 3) * 16384 : xs * SLOT + (it - P1_XS) * 16384) + (w ^ (t == 4)) * 8192;
        const uint64_t da = desc_k(sb + aa), db = desc_mn(sb + ws * SLOT);
        turn_begin();
        wg_fence();
#pragma unroll
        for (int kk = 0; kk < 4; kk++) wgmma_ss_n256_tb(acc, desc_add(da, kk * 32), desc_add(db, kk * 2048), (k | kk) != 0);
        wg_commit();
        turn_end();
        wg_wait<1>();
        if (k > 0) give(prev);
        prev = ws;
        if (it >= P1_XS - 2 && !(it & 1) && lane == 0) mbar_arrive(bar_addr(sb, B_XFREE + ((it - (P1_XS - 2)) >> 1)));
        if (t > 0) {
          uint4* row = at<uint4>(t < 5 ? (const void*)g_kv : (const void*)g_qc, dst + chunk_off());
          const int c0 = t < 4 ? k : 3 * k, c1 = t < 4 ? k + 1 : 3 * k + 3;
#pragma unroll
          for (int i = 0; i < 16; i++)
            if (i >= c0 && i < c1) row[(i & 1) * 256 + (i >> 1) * 4] = make_uint4(pk[4 * i], pk[4 * i + 1], pk[4 * i + 2], pk[4 * i + 3]);
          if (t >= 4 && k == 5) warp_arrive(bar_addr(sb, (t == 4 ? B_ST_KV : B_ST_Q) + w), lane);
        }
      }
      wg_wait<0>();
      reg_fence(acc);
      give(prev);
      pack_chunks(pk, acc);
      dst = t < 4 ? (uint32_t)((p1_isv(t) * NH + KVH(p1_head(h, t))) * SEQ + p1_rows(h, j, t) * 128 + w * 64) * 512 : (uint32_t)((h * 8 + j) * 2 + w) * 32768;
      TS(2 + t);
    }
    give(xs);
    mbar_wait(bar_addr(sb, B_XFREE + w), 0);
    const uint32_t ft = fresh_tid(), g = (ft & 31) >> 2;
    const uint32_t qa = qreg + (16 * ((ft >> 5) & 3) + g) * 128 + (((ft & 3) ^ g) << 4);
#pragma unroll
    for (int i = 0; i < 16; i++) sts16((qa ^ ((i & 2) << 5)) + (i >> 2) * 8192 + (i & 1) * 1024, pk[4 * i], pk[4 * i + 1], pk[4 * i + 2], pk[4 * i + 3]);
    fence_async_smem();
  }
  TS(8);

  constexpr float SC = 0.0625f * 1.4426950408889634f;
#pragma unroll 1
  for (int which = 0; which < 2; which++) {
    float s[32];
#pragma unroll
    for (int i = 0; i < 32; i++) s[i] = 0.f;
    uint32_t pa[16];
    float m0 = -INFINITY, m1 = -INFINITY, l0 = 0.f, l1 = 0.f;
    const uint64_t dq = desc_k(qreg);
    uint64_t dk = 0, dqq = 0, dv = 0;
    auto prep_qk = [&](uint32_t kaddr) { dk = desc_k(kaddr); dqq = dq + (kaddr >> 31); asm volatile("" : "+l"(dk), "+l"(dqq)); };
    auto prep_pv = [&](uint32_t vaddr) { dv = desc_mn(vaddr); asm volatile("" : "+l"(dv)); };
    auto issue_qk = [&]() {
#pragma unroll
      for (int kk = 0; kk < 16; kk++)
        wgmma_ss_n64(s, desc_add(dqq, (kk >> 2) * 8192 + (kk & 3) * 32), desc_add(dk, (kk >> 2) * 8192 + (kk & 3) * 32), kk != 0);
    };
    auto issue_pv = [&](int accumulate) {
#pragma unroll
      for (int kk = 0; kk < 4; kk++)
        wgmma_rs_n256_tb(acc, pa[4 * kk], pa[4 * kk + 1], pa[4 * kk + 2], pa[4 * kk + 3], desc_add(dv, kk * 2048), accumulate | kk);
    };
    auto mask_diag = [&]() {
      const uint32_t ft = fresh_tid();
      const int r0 = 16 * ((ft >> 5) & 3) + ((ft & 31) >> 2), c = ft & 3;
#pragma unroll
      for (int jj = 0; jj < 8; jj++) {
        const int cc = 8 * jj + 2 * c;
        if (cc > r0)         s[4 * jj]     = -INFINITY;
        if (cc + 1 > r0)     s[4 * jj + 1] = -INFINITY;
        if (cc > r0 + 8)     s[4 * jj + 2] = -INFINITY;
        if (cc + 1 > r0 + 8) s[4 * jj + 3] = -INFINITY;
      }
    };
    float a0, a1;
    auto softmax = [&]() -> bool {
      float x0 = fmaxf(s[0], s[1]), x1 = fmaxf(s[2], s[3]);
#pragma unroll
      for (int jj = 1; jj < 8; jj++) {
        x0 = fmaxf(x0, fmaxf(s[4 * jj], s[4 * jj + 1]));
        x1 = fmaxf(x1, fmaxf(s[4 * jj + 2], s[4 * jj + 3]));
      }
      x0 = fmaxf(x0, __shfl_xor_sync(0xffffffffu, x0, 1));
      x1 = fmaxf(x1, __shfl_xor_sync(0xffffffffu, x1, 1));
      x0 = fmaxf(x0, __shfl_xor_sync(0xffffffffu, x0, 2));
      x1 = fmaxf(x1, __shfl_xor_sync(0xffffffffu, x1, 2));
      const bool grow = __any_sync(0xffffffffu, fmaxf(x0 - m0, x1 - m1) * SC > 8.f);
      if (grow) {
        x0 = fmaxf(x0, m0); x1 = fmaxf(x1, m1);
        a0 = ex2((m0 - x0) * SC); a1 = ex2((m1 - x1) * SC);
        m0 = x0; m1 = x1;
        l0 *= a0; l1 *= a1;
      }
      const float b0 = -m0 * SC, b1 = -m1 * SC;
      float t0 = 0.f, t1 = 0.f, t2 = 0.f, t3 = 0.f;
#pragma unroll
      for (int jj = 0; jj < 8; jj++) {
        s[4 * jj]     = ex2(fmaf(s[4 * jj], SC, b0));
        s[4 * jj + 1] = ex2(fmaf(s[4 * jj + 1], SC, b0));
        s[4 * jj + 2] = ex2(fmaf(s[4 * jj + 2], SC, b1));
        s[4 * jj + 3] = ex2(fmaf(s[4 * jj + 3], SC, b1));
        t0 += s[4 * jj]; t1 += s[4 * jj + 1]; t2 += s[4 * jj + 2]; t3 += s[4 * jj + 3];
      }
      l0 += t0 + t1; l1 += t2 + t3;
      return grow;
    };
    auto softmax_fast = [&](uint32_t vs) -> bool {
      const float b0 = -m0 * SC, b1 = -m1 * SC;
      float e[16];
#pragma unroll
      for (int i = 0; i < 16; i++) e[i] = ex2(fmaf(s[i], SC, (i & 2) ? b1 : b0));
      float t0 = (e[0] + e[4]) + (e[8] + e[12]), t1 = (e[1] + e[5]) + (e[9] + e[13]), t2 = (e[2] + e[6]) + (e[10] + e[14]), t3 = (e[3] + e[7]) + (e[11] + e[15]);
      reg_fence(e);
      wg_wait<0>();
      reg_fence(acc);
      reg_fence(pa);
      give(vs);
#pragma unroll
      for (int i = 0; i < 8; i++) pa[i] = pack_bf16(e[2 * i], e[2 * i + 1]);
#pragma unroll
      for (int i = 0; i < 16; i++) e[i] = ex2(fmaf(s[16 + i], SC, (i & 2) ? b1 : b0));
#pragma unroll
      for (int i = 0; i < 16; i += 4) { t0 += e[i]; t1 += e[i + 1]; t2 += e[i + 2]; t3 += e[i + 3]; }
#pragma unroll
      for (int i = 0; i < 8; i++) pa[8 + i] = pack_bf16(e[2 * i], e[2 * i + 1]);
      t0 += t1; t2 += t3;
      const bool redo = __any_sync(0xffffffffu, !(t0 + t2 <= 16777216.f));
      if (!redo) { l0 += t0; l1 += t2; }
      return redo;
    };
    auto rescale = [&]() {
#pragma unroll
      for (int i = 0; i < 32; i++) { acc[4 * i] *= a0; acc[4 * i + 1] *= a0; acc[4 * i + 2] *= a1; acc[4 * i + 3] *= a1; }
    };
    auto to_p = [&]() {
#pragma unroll
      for (int i = 0; i < 16; i++) pa[i] = pack_bf16(s[2 * i], s[2 * i + 1]);
    };
    auto q_free = [&]() { if (lane == 0) mbar_arrive(bar_addr(sb, B_QFREE + w)); };

    const int n = 2 * q_tile(h, j, which) + 1 + (w ^ which);
    uint32_t ks = take();
    TS(9 + 5 * which);
    prep_qk(sb + ks * SLOT);
    turn_begin();
    wg_fence();
    issue_qk();
    wg_commit();
    turn_end();
    wg_wait<0>();
    reg_fence(s);
    give(ks);
    if (n == 1) q_free();
    if (which == 1) {
      uint4* dst = at<uint4>(g_qc, (uint32_t)((h * 8 + j) * 2 + w) * 32768 + (fresh_tid() & 127) * 16);
#pragma unroll
      for (int i = CTX_SPLIT; i < 16; i++) dst[i * 128] = make_uint4(pk[4 * i], pk[4 * i + 1], pk[4 * i + 2], pk[4 * i + 3]);
    }
    if (which == 1 || n == 1) mask_diag();
    softmax();
    to_p();
    if (which == 1) {
      warp_arrive(bar_addr(sb, B_ST_CTX + w), lane);
      give(take());
    }
    TS(10 + 5 * which);
#pragma unroll 1
    for (int jj = 1; jj < n; jj++) {
      ks = take();
      const uint32_t vs = take();
      prep_qk(sb + ks * SLOT);
      prep_pv(sb + vs * SLOT);
      turn_begin();
      wg_fence();
      issue_qk();
      wg_commit();
      issue_pv(jj > 1);
      wg_commit();
      turn_end();
      wg_wait<1>();
      reg_fence(s);
      give(ks);
      if (jj == n - 1) {
        q_free();
        if (which == 0) mask_diag();
      }
      if (softmax_fast(vs)) {
        if (softmax()) rescale();
        to_p();
      }
    }
    TS(11 + 5 * which);
    if (which == 0) give(take());
    {
      const uint32_t vs = take();
      prep_pv(sb + vs * SLOT);
      turn_begin();
      wg_fence();
      issue_pv(n > 1);
      wg_commit();
      turn_end();
      l0 += __shfl_xor_sync(0xffffffffu, l0, 1); l1 += __shfl_xor_sync(0xffffffffu, l1, 1);
      l0 += __shfl_xor_sync(0xffffffffu, l0, 2); l1 += __shfl_xor_sync(0xffffffffu, l1, 2);
      l0 = 1.f / l0; l1 = 1.f / l1;
      wg_wait<0>();
      reg_fence(acc);
      reg_fence(pa);
      give(vs);
    }
    TS(12 + 5 * which);
#pragma unroll
    for (int i = 0; i < 32; i++) {
      pk[2 * i]     = pack_bf16(acc[4 * i] * l0, acc[4 * i + 1] * l0);
      pk[2 * i + 1] = pack_bf16(acc[4 * i + 2] * l1, acc[4 * i + 3] * l1);
    }
    if (which == 0) {
      mbar_wait(bar_addr(sb, B_QFULL + w), 0);
      uint4* dst = at<uint4>(g_qc, (uint32_t)((h * 8 + j) * 2 + w) * 32768 + (fresh_tid() & 127) * 16);
#pragma unroll
      for (int i = 0; i < CTX_SPLIT; i++) dst[i * 128] = make_uint4(pk[4 * i], pk[4 * i + 1], pk[4 * i + 2], pk[4 * i + 3]);
    }
    TS(13 + 5 * which);
  }

  {
    float oa[32], ob[32];
#pragma unroll
    for (int i = 0; i < 32; i++) { oa[i] = 0.f; ob[i] = 0.f; }
    uint32_t pk2[64];
#pragma unroll
    for (int i = 0; i < 64; i++) pk2[i] = 0;
    auto stage = [&](float (&o)[32], int ch) {
      reg_fence(o);
      uint32_t q[16];
#pragma unroll
      for (int i = 0; i < 16; i++) q[i] = pack_bf16(o[2 * i], o[2 * i + 1]);
      if (ch >= 4) mbar_wait(bar_addr(sb, B_S2_EMPTY + w * 4 + (ch & 3)), 0);
      store_block(qreg + (ch & 3) * 8192, lane_base16(), q);
    };
    auto hand_over = [&](int ch) {
      fence_async_smem();
      warp_arrive(bar_addr(sb, B_S2_FULL + w * 4 + (ch & 3)), lane);
    };
    uint32_t prev = 0;
    auto half = [&](int f, float (&o)[32], uint32_t (&a)[64], int accumulate) {
      const uint32_t sl = take();
      const uint64_t d = desc_mn(sb + sl * SLOT);
      turn_begin();
      wg_fence();
#pragma unroll
      for (int kk = 0; kk < 16; kk++) {
        wgmma_rs_n64_tb(o, a[4 * kk], a[4 * kk + 1], a[4 * kk + 2], a[4 * kk + 3], desc_add(d, kk * 2048), accumulate | kk);
        if (kk == ARRIVE_KK && (f < 13 || w == 0)) turn_end();
      }
      wg_commit();
      wg_wait<1>();
      if (f >= 1 && f <= 9) give(prev);
      prev = sl;
    };
    auto load_ctx = [&](auto h0) {
      constexpr int I0 = decltype(h0)::value * 8;
      const uint32_t src = qreg + (fresh_tid() & 127) * 16;
#pragma unroll
      for (int i = I0; i < I0 + 8; i++) { const uint4 v = lds16(src + i * 2048); pk2[4 * i] = v.x; pk2[4 * i + 1] = v.y; pk2[4 * i + 2] = v.z; pk2[4 * i + 3] = v.w; }
    };
#pragma unroll 1
    for (int i = 0; i < 3; i++) {
      half(4 * i, oa, pk, 0);
      if (i == 0) { mbar_wait(bar_addr(sb, B_QFULL + w), 1); load_ctx(Int<0>()); }
      else { hand_over(2 * i - 2); stage(ob, 2 * i - 1); }
      half(4 * i + 1, ob, pk, 0);
      if (i == 0) load_ctx(Int<1>()); else hand_over(2 * i - 1);
      half(4 * i + 2, oa, pk2, 1);
      half(4 * i + 3, ob, pk2, 1);
      stage(oa, 2 * i);
    }
    half(12, oa, pk, 0);
    hand_over(4);
    stage(ob, 5);
    half(13, oa, pk2, 1);
    hand_over(5);
    wg_wait<0>();
    reg_fence(pk);
    reg_fence(pk2);
    stage(oa, 6);
    hand_over(6);
  }
  TS(19);
  TDUMP();
}

namespace ssm {
constexpr int NCH = DA / NCONV;
constexpr int NS = 8, NP = 6;
constexpr uint32_t X0 = 384;
constexpr uint32_t HO = X0 + 4096;
constexpr uint32_t HE = HO + HO_STRIDE + 64;
constexpr uint32_t SSLOT = HE + 4096 + 64;
constexpr uint32_t PART = 264 * 16;
constexpr uint32_t OFF_P = NS * SSLOT, OFF_D = OFF_P + NP * 4 * PART, END = OFF_D + NCH * 4;
static_assert(SSLOT % 128 == 0 && HO % 128 == 0 && END <= BARS, "smem");
enum : uint32_t { B_FULL = 0, B_EMPTY = NS, B_PFULL = 2 * NS, B_PEMPTY = 2 * NS + NP };
__device__ __forceinline__ int channel(int cidx, int i) { return (i >> 4) * 64 + cidx * 16 + (i & 15); }

__device__ __forceinline__ void producer(const Params& p, uint32_t sb, int cidx, unsigned epoch) {
#pragma unroll 1
  for (int i = 0; i < NCH; i++) {
    const int s = i % NS, ch = channel(cidx, i);
    const uint32_t full = bar_addr(sb, B_FULL + s), dst = sb + s * SSLOT;
    mbar_wait(bar_addr(sb, B_EMPTY + s), ((i / NS) & 1) ^ 1);
    mbar_expect_tx(full, 4096 + 4128 + 4096);
    bulk_ld(dst + HE, at<uint8_t>(p.a_ssmk, ch * 4096), 4096, full);
    if ((i & 15) == 0) { flag_wait(flag_at(g_flags.x_ready, i >> 4), NMAIN, epoch); fence_async_all(); }
    bulk_ld(dst + HO, at<uint8_t>(g_ho, ch * HO_STRIDE), 4128, full);
    bulk_ld(dst + X0, at<uint8_t>(g_xs, ch * 4096), 4096, full);
  }
}

__device__ __forceinline__ void reducer(uint32_t sb, int cidx, int rw) {
  uint32_t n = 0;
#pragma unroll 1
  for (int i = rw; i < NCH; i += 3, n++) {
    const uint32_t b = rw + 3 * (n & 1), pb = sb + OFF_P + b * 4 * PART;
    uint8_t* dst = at<uint8_t>(g_xs, channel(cidx, i) * 4096);
    mbar_wait(bar_addr(sb, B_PFULL + b), (n >> 1) & 1);
    asm volatile("cp.async.bulk.global.shared::cta.bulk_group [%0], [%1], 4096;" :: "l"(dst), "r"(pb + 3 * PART) : "memory");
    bulk_commit();
    bulk_wait_all();
#pragma unroll
    for (int k = 2; k >= 0; k--)
      asm volatile("cp.reduce.async.bulk.global.shared::cta.bulk_group.add.noftz.bf16 [%0], [%1], 4096;" :: "l"(dst), "r"(pb + k * PART) : "memory");
    bulk_commit();
    bulk_wait_read();
    mbar_arrive(bar_addr(sb, B_PEMPTY + b));
    if (((i + 3) >> 4) != (i >> 4)) {
      bulk_wait_all();
      fence_async_all();
      flag_signal(flag_at(g_flags.z_ready, i >> 4));
    }
  }
}

__device__ __forceinline__ void mma_warpgroup(uint32_t sb, int w) {
  const int lane = threadIdx.x & 31, g = lane >> 2, c = lane & 3, wq = (threadIdx.x >> 5) & 3;
  const uint32_t aoff = ((g & 1) ? HO + 30 : HE) + (16 * wq - g + 2 * c) * 2;
  const uint32_t poff = OFF_P + wq * PART + (2 * wq + lane) * 16;
  const uint32_t dmask = (wq == 0 && c == (g >> 1)) ? ((g & 1) ? 0xffff0000u : 0xffffu) : 0u;
  float acc[8][16];
  uint32_t fa[16][4];
#pragma unroll
  for (int e = 0; e < 8; e++)
#pragma unroll
    for (int i = 0; i < 16; i++) acc[e][i] = 0.f;
  auto load_a = [&](int m, uint32_t ad) {
    fa[m][0] = lds4(ad + m * 256 + 16); fa[m][1] = lds4(ad + m * 256 + 144); fa[m][2] = lds4(ad + m * 256); fa[m][3] = lds4(ad + m * 256 + 128);
  };
  if (w == 1) named_arrive(PP_BAR, 256);
  mbar_wait(bar_addr(sb, B_FULL + w), 0);
#pragma unroll
  for (int m = 0; m < 16; m++) load_a(m, sb + w * SSLOT + aoff);
  uint32_t dd = lds4(sb + OFF_D + w * 4);
  if (threadIdx.x == 128) { GT(12); PT(10); }
  uint32_t pb = w, pphase = 1;
#pragma unroll 1
  for (int i = w; i < NCH; i += 2) {
    fa[0][2] = badd(fa[0][2], dd & dmask);
    const uint64_t db = (uint64_t)((((sb + (i % NS) * SSLOT + X0 - 16) & 0x3FFFF) >> 4) | (1u << 16)) | ((uint64_t)8 << 32);
    named_sync(PP_BAR + w, 256);
    wg_fence();
#pragma unroll
    for (int r = 0; r < 16; r++) {
      auto mm = [&](int e, int m) { wgmma_rs_n32(acc[e], fa[m][0], fa[m][1], fa[m][2], fa[m][3], db + (int64_t)(32 * e - 16 * m), m != 0); };
      mm(7, r);
      if (r < 14) mm(6, r); else mm(0, r - 14);
      if (r < 12) mm(5, r); else mm(1, r - 12);
      if (r < 10) mm(4, r); else mm(2, r - 10);
      if ((r & 1) == 0) mm(3, r >> 1);
      if (r == CONV_ARRIVE && (i + 1 < NCH)) named_arrive(PP_BAR + (w ^ 1), 256);
    }
    wg_commit();
    const int nx = i + 2 < NCH ? i + 2 : i;
    mbar_wait(bar_addr(sb, B_FULL + nx % NS), (nx / NS) & 1);
    mbar_wait(bar_addr(sb, B_PEMPTY + pb), pphase);
    const uint32_t ad = sb + (nx % NS) * SSLOT + aoff, pa = sb + pb * 4 * PART + poff;
    wg_wait<0>();
#pragma unroll
    for (int e = 0; e < 8; e++) reg_fence(acc[e]);
#pragma unroll
    for (int m = 0; m < 16; m++) reg_fence(fa[m]);
    if (lane == 0) mbar_arrive(bar_addr(sb, B_EMPTY + i % NS));
#pragma unroll
    for (int e = 0; e < 8; e++) {
      if (e < CONV_EARLY) load_a(e, ad);
      uint32_t u[4];
#pragma unroll
      for (int j = 0; j < 4; j++) {
        const int T = 4 * e + j, U = T - 1;
        float lo = acc[e][4 * j], hi = acc[e][4 * j + 1];
        if (T > 0) { lo += acc[U >> 2][4 * (U & 3) + 2]; hi += acc[U >> 2][4 * (U & 3) + 3]; }
        u[j] = pack_bf16(lo, hi);
      }
      asm volatile("stmatrix.sync.aligned.m8n8.x4.trans.shared.b16 [%0], {%1, %2, %3, %4};" :: "r"(pa + e * 512), "r"(u[0]), "r"(u[1]), "r"(u[2]), "r"(u[3]) : "memory");
    }
    dd = lds4(sb + OFF_D + nx * 4);
#pragma unroll
    for (int m = CONV_EARLY; m < CONV_FENCE; m++) load_a(m, ad);
    fence_async_smem();
    warp_arrive(bar_addr(sb, B_PFULL + pb), lane);
#pragma unroll
    for (int m = CONV_FENCE; m < 16; m++) load_a(m, ad);
    pb += 2;
    if (pb >= NP) { pb -= NP; pphase ^= 1; }
  }
  if (threadIdx.x == 128) { PT(9); GT(13); }
}

__device__ __forceinline__ void init(const Params& p, uint32_t sb, int cidx) {
  if (threadIdx.x < NS * 32) {
    const uint32_t s = threadIdx.x >> 5, r = threadIdx.x & 31;
    if (r < 28) sts16(sb + s * SSLOT + (r < 24 ? r * 16 : HE - 64 + (r - 24) * 16), 0, 0, 0, 0);
  } else {
    const uint32_t t = threadIdx.x - NS * 32;
    for (uint32_t u = t; u < NP * 32; u += 128) sts16(sb + OFF_P + (u >> 3) * PART + (u & 7) * 16, 0, 0, 0, 0);
    if (t < NCH) {
      const uint32_t d = (uint32_t)__ldg(reinterpret_cast<const unsigned short*>(p.a_D + channel(cidx, t))) * 0x10001u;
      asm volatile("st.shared.u32 [%0], %1;" :: "r"(sb + OFF_D + t * 4), "r"(d) : "memory");
    }
  }
  if (threadIdx.x == 0) {
    for (int i = 0; i < NS; i++) { mbar_init(bar_addr(sb, B_FULL + i), 1); mbar_init(bar_addr(sb, B_EMPTY + i), 4); }
    for (int i = 0; i < NP; i++) { mbar_init(bar_addr(sb, B_PFULL + i), 4); mbar_init(bar_addr(sb, B_PEMPTY + i), 1); }
  }
  fence_async_smem();
}

__device__ __forceinline__ void side_prepare(const Params& p, int cta, int rd) {
  const int lane = threadIdx.x & 31, t0 = 16 * cta + 8 * (lane & 1);
  if (EXP_SIDE & 16) { if (lane == 0) flag_signal_after_bulk(flag_at(g_flags.x_ready, rd)); return; }
#pragma unroll 1
  for (int ch = 64 * rd + (lane & ~1); ch < 64 * rd + 64; ch += 32) {
    const uint4 sv = __ldg(at<const uint4>(p.a_shift, ch * 8));
    const uint32_t* kp = at<const uint32_t>(p.a_k, (t0 * DA + ch) * 2);
    const uint32_t* vp = at<const uint32_t>(p.a_v, (t0 * DA + ch) * 2);
    uint32_t k0 = 0, k1 = 0, k2 = 0, kk[8], x[8];
    if (t0 > 0) { k0 = __ldg(kp - 3 * (DA / 2)); k1 = __ldg(kp - 2 * (DA / 2)); k2 = __ldg(kp - DA / 2); }
#pragma unroll
    for (int i = 0; i < 8; i++) { kk[i] = __ldg(kp + i * (DA / 2)); x[i] = __ldg(vp + i * (DA / 2)); }
    const uint32_t sh0 = __byte_perm(sv.x, sv.z, 0x5410), sh1 = __byte_perm(sv.x, sv.z, 0x7632);
    const uint32_t sh2 = __byte_perm(sv.y, sv.w, 0x5410), sh3 = __byte_perm(sv.y, sv.w, 0x7632);
#pragma unroll
    for (int i = 0; i < 8; i++) {
      uint32_t ks = bmul(k0, sh3);
      ks = badd(ks, bmul(k1, sh2)); ks = badd(ks, bmul(k2, sh1)); ks = badd(ks, bmul(kk[i], sh0));
      x[i] = bmul(ks, x[i]);
      k0 = k1; k1 = k2; k2 = kk[i];
    }
    uint4* dst = at<uint4>(g_xs, ch * 4096 + t0 * 2);
    if ((EXP_SIDE & 4) && (x[0] ^ x[1] ^ x[2] ^ x[3] ^ x[4] ^ x[5] ^ x[6] ^ x[7]) != 0x12345) continue;
    dst[0]   = make_uint4(__byte_perm(x[7], x[6], 0x5410), __byte_perm(x[5], x[4], 0x5410), __byte_perm(x[3], x[2], 0x5410), __byte_perm(x[1], x[0], 0x5410));
    dst[256] = make_uint4(__byte_perm(x[7], x[6], 0x7632), __byte_perm(x[5], x[4], 0x7632), __byte_perm(x[3], x[2], 0x7632), __byte_perm(x[1], x[0], 0x7632));
  }
  if (!(EXP_SIDE & 8)) {
    const int hc = 64 * rd + (cta >> 1), r0 = (cta & 1) * 128 + lane;
    const uint4* src = at<const uint4>(p.a_ssmk, hc * 4096 + r0 * 16);
    uint4* dst = at<uint4>(g_ho, hc * HO_STRIDE + r0 * 16);
    uint4 w[4];
    uint32_t nx[4];
#pragma unroll
    for (int i = 0; i < 4; i++) { w[i] = __ldg(src + 32 * i); nx[i] = r0 + 32 * i < 255 ? __ldg(reinterpret_cast<const uint32_t*>(src + 32 * i + 1)) : 0u; }
#pragma unroll
    for (int i = 0; i < 4; i++)
      dst[32 * i + 2] = make_uint4(__byte_perm(w[i].x, w[i].y, 0x5432), __byte_perm(w[i].y, w[i].z, 0x5432), __byte_perm(w[i].z, w[i].w, 0x5432), __byte_perm(w[i].w, nx[i], 0x5432));
    const uint32_t h0 = __shfl_sync(0xffffffffu, w[0].x, 0);
    if (r0 < 2) dst[0] = make_uint4(0, 0, 0, r0 ? h0 << 16 : 0u);
  }
  __syncwarp();
  if (lane == 0) { if (EXP_SIDE & 2) flag_signal_after_bulk(flag_at(g_flags.x_ready, rd)); else flag_signal(flag_at(g_flags.x_ready, rd)); }
}
__device__ __forceinline__ void side_finish(const Params& p, int cta, int rd) {
  const int lane = threadIdx.x & 31, t0 = 16 * cta + 8 * (lane & 1);
#pragma unroll 1
  for (int ch = 64 * rd + (lane & ~1); ch < 64 * rd + 64; ch += 32) {
    const uint4* src = at<const uint4>(g_xs, ch * 4096 + t0 * 2);
    const uint32_t* qp = at<const uint32_t>(p.a_q, (t0 * DA + ch) * 2);
    uint32_t* op = at<uint32_t>(p.out, (t0 * OUTW + ch) * 2);
    const uint4 z0 = __ldcg(src), z1 = __ldcg(src + 256);
    uint32_t q[8];
#pragma unroll
    for (int i = 0; i < 8; i++) q[i] = __ldg(qp + i * (DA / 2));
    const uint32_t a[4] = {z0.w, z0.z, z0.y, z0.x}, b[4] = {z1.w, z1.z, z1.y, z1.x};
#pragma unroll
    for (int i = 0; i < 4; i++) {
      op[(2 * i) * (OUTW / 2)]     = bmul(q[2 * i], __byte_perm(a[i], b[i], 0x7632));
      op[(2 * i + 1) * (OUTW / 2)] = bmul(q[2 * i + 1], __byte_perm(a[i], b[i], 0x5410));
    }
  }
}
__device__ __forceinline__ void clear_rows(const Params& p, int qt, int part) {
  const int lane = threadIdx.x & 31;
  if (lane < 28) {
    uint4* z = at<uint4>(p.out, ((qt * 128 + part * 16) * OUTW + DA) * 2 + lane * 16);
#pragma unroll
    for (int i = 0; i < 32; i++) z[(i >> 1) * (OUTW / 8) + (i & 1) * 28] = make_uint4(0, 0, 0, 0);
  }
  __syncwarp();
  if (lane == 0) flag_signal(flag_at(g_flags.zero_ready, qt));
}
__device__ __forceinline__ void side_work(const Params& p, int cta, int qt, unsigned epoch) {
#pragma unroll 1
  for (int rd = -SIDE_AHEAD; rd < 7; rd++) {
    if (rd >= 0) {
      if ((threadIdx.x & 31) == 0) flag_wait_slow(flag_at(g_flags.z_ready, rd), 3 * NCONV, epoch);
      __syncwarp();
    }
    if (rd + SIDE_AHEAD < 7) side_prepare(p, cta, rd + SIDE_AHEAD);
    if (rd >= 0 && !(EXP_SIDE & 1)) side_finish(p, cta, rd);
    if (rd == ZERO_RD) clear_rows(p, qt, (cta >> 3) & 7);
  }
}
}

__global__ void __cluster_dims__(2, 1, 1) __launch_bounds__(NTHREADS, 1)
concat_heads__ssm_conv_h3__compressed_kv_cla__prompt_kernel(const __grid_constant__ Params p) {
  extern __shared__ uint8_t smem_raw[];
  const uint32_t sb = (smem_u32(smem_raw) + 1023) & ~1023u;
  const int warp = __shfl_sync(0xffffffffu, threadIdx.x >> 5, 0);
  const int wg = warp >> 2;
  const int cta = blockIdx.x;
  const bool attn = cta < NMAIN;
  int h, u;
  {
    const int c = cta >> 1;
    if (c < 4) { h = 15; u = c; }
    else if (c < 36) { h = (c - 4) & 7; u = (c - 4) >> 3; }
    else { h = 8 + (c - 36) % 7; u = (c - 36) / 7; }
  }
  const int j = 2 * u + (cta & 1);
  if (!attn) ssm::init(p, sb, cta - NMAIN);
  if (attn && threadIdx.x == 0) {
    for (int i = 0; i < NSLOT; i++) { mbar_init(bar_addr(sb, B_FULL + i), 1); mbar_init(bar_addr(sb, B_EMPTY + i), 16); }
    for (int i = 0; i < 2; i++) {
      mbar_init(bar_addr(sb, B_XFREE + i), 8); mbar_init(bar_addr(sb, B_QFREE + i), 4); mbar_init(bar_addr(sb, B_QFULL + i), 1);
      mbar_init(bar_addr(sb, B_ST_KV + i), 4); mbar_init(bar_addr(sb, B_ST_Q + i), 4); mbar_init(bar_addr(sb, B_ST_CTX + i), 4);
    }
    mbar_init(bar_addr(sb, B_KVOK), 1);
    mbar_init(bar_addr(sb, B_DONE), 2);
    for (int i = 0; i < 8; i++) { mbar_init(bar_addr(sb, B_S2_FULL + i), 4); mbar_init(bar_addr(sb, B_S2_EMPTY + i), 1); }
    asm volatile("fence.mbarrier_init.release.cluster;" ::: "memory");
  }
  if (attn && threadIdx.x == 32) {
    prefetch_map(&p.ckv); prefetch_map(&p.wuk); prefetch_map(&p.wuv); prefetch_map(&p.x); prefetch_map(&p.wq);
    prefetch_map(&p.kv); prefetch_map(&p.o); prefetch_map(&p.wo); prefetch_map(&p.qc);
  }
  __syncwarp();
  asm volatile("barrier.cluster.arrive.release.aligned;" ::: "memory");
  if (attn && threadIdx.x == 0) {
    for (int k = 0; k < EARLY_LD; k++) {
      const uint32_t full = bar_addr(sb, B_FULL + k);
      mbar_expect_tx(full, 49152);
      tma_ld2(sb + QREG + k * 16384, &p.ckv, full, k * 64, p1_rows(h, j, 0) * 128);
      load_tile4(sb + k * SLOT, &p.wuk, full, k * 64, p1_head(h, 0) * 4, j & 1, false, pol(HINTS & 1));
    }
  }
  __syncwarp();
  asm volatile("barrier.cluster.wait.acquire.aligned;" ::: "memory");

  const int lane = threadIdx.x & 31;
  if (wg == 0) {
    if (!attn) {
      asm volatile("setmaxnreg.dec.sync.aligned.u32 40;");
      if (lane == 0) {
        if (warp == 0) { ssm::producer(p, sb, cta - NMAIN, load_epoch()); cta_done(32); }
        else ssm::reducer(sb, cta - NMAIN, warp - 1);
        if (warp == 1) GT(14);
      }
      return;
    }
    asm volatile("setmaxnreg.dec.sync.aligned.u32 40;");
    if (warp == 0) {
      if (lane == 0) producer_main(p, sb, h, j);
    } else if (warp < 3) {
      if (lane == 0) { helper_main(p, sb, h, j, warp - 1); mbar_arrive(bar_addr(sb, B_DONE)); }
    } else {
      ssm::side_work(p, h * 8 + j, q_tile(h, j, 1), load_epoch());
      if (lane == 0) { GT(57); mbar_wait(bar_addr(sb, B_DONE), 0); cta_done(1); }
    }
  } else {
    if (!attn) {
      asm volatile("setmaxnreg.inc.sync.aligned.u32 232;");
      if (p.out != nullptr) ssm::mma_warpgroup(sb, wg - 1);
      return;
    }
    asm volatile("setmaxnreg.inc.sync.aligned.u32 232;");
    if (p.out != nullptr) consumer_main(p, sb, h, j, wg - 1);
  }
}

typedef CUresult (*EncodeTiledFn)(CUtensorMap*, CUtensorMapDataType, cuuint32_t, void*, const cuuint64_t*, const cuuint64_t*,
                                  const cuuint32_t*, const cuuint32_t*, CUtensorMapInterleave, CUtensorMapSwizzle,
                                  CUtensorMapL2promotion, CUtensorMapFloatOOBfill);

void make_map(EncodeTiledFn enc, CUtensorMap* m, const void* ptr, int rank, const uint64_t* dims, const uint64_t* strides, const uint32_t* box) {
  cuuint64_t d[5], s[4]; cuuint32_t b[5], e[5] = {1, 1, 1, 1, 1};
  for (int i = 0; i < rank; i++) { d[i] = dims[i]; b[i] = box[i]; if (i) s[i - 1] = strides[i - 1]; }
  enc(m, CU_TENSOR_MAP_DATA_TYPE_BFLOAT16, rank, const_cast<void*>(ptr), d, s, b, e, CU_TENSOR_MAP_INTERLEAVE_NONE,
      CU_TENSOR_MAP_SWIZZLE_128B, CU_TENSOR_MAP_L2_PROMOTION_L2_256B, CU_TENSOR_MAP_FLOAT_OOB_FILL_NONE);
}
void map2(EncodeTiledFn enc, CUtensorMap* m, const void* ptr, uint64_t cols, uint64_t rows, uint32_t bc, uint32_t br) {
  const uint64_t dims[2] = {cols, rows}, st[1] = {cols * 2}; const uint32_t box[2] = {bc, br};
  make_map(enc, m, ptr, 2, dims, st, box);
}
void map3(EncodeTiledFn enc, CUtensorMap* m, const void* ptr, uint64_t rows, uint32_t nblk) {
  const uint64_t dims[3] = {64, rows, 64}, st[2] = {8192, 128}; const uint32_t box[3] = {64, 64, nblk};
  make_map(enc, m, ptr, 3, dims, st, box);
}

}

extern "C" void kernel_launch(void* const* d_in, const int* in_sizes, int n_in, void* d_out, int out_size) {
  (void)in_sizes; (void)n_in; (void)out_size;
  static EncodeTiledFn enc = nullptr;
  static void *kv_ptr = nullptr, *qc_ptr = nullptr;
  if (!enc) {
    void* fn = nullptr; cudaDriverEntryPointQueryResult qr;
    cudaGetDriverEntryPoint("cuTensorMapEncodeTiled", &fn, cudaEnableDefault, &qr);
    enc = (EncodeTiledFn)fn;
    cudaGetSymbolAddress(&kv_ptr, g_kv);
    cudaGetSymbolAddress(&qc_ptr, g_qc);
    cudaFuncSetAttribute(concat_heads__ssm_conv_h3__compressed_kv_cla__prompt_kernel, cudaFuncAttributeMaxDynamicSharedMemorySize, SMEM_BYTES);
  }
  Params p;
  p.a_q = (const bf16*)d_in[0]; p.a_k = (const bf16*)d_in[1]; p.a_v = (const bf16*)d_in[2];
  p.a_shift = (const bf16*)d_in[3]; p.a_ssmk = (const bf16*)d_in[4]; p.a_D = (const bf16*)d_in[5];
  p.out = (bf16*)d_out;
  map2(enc, &p.x, d_in[6], DM, SEQ, 64, 128);
  map2(enc, &p.ckv, d_in[7], DC, SEQ, 64, 128);
  map3(enc, &p.wq, d_in[8], DM, 2);
  map3(enc, &p.wuk, d_in[9], DC, 2);
  map3(enc, &p.wuv, d_in[10], DC, 2);
  {
    const uint64_t dims[5] = {DM, 2, 4, 4, NH * HD / 32}, st[4] = {DM * 2, 8 * DM * 2, 2 * DM * 2, 32 * DM * 2}; const uint32_t box[5] = {64, 2, 4, 4, 4};
    make_map(enc, &p.wo, d_in[11], 5, dims, st, box);
  }
  {
    const uint64_t dims[3] = {64, 2 * NH * SEQ, 4}, st[2] = {HD * 2, 128}; const uint32_t box[3] = {64, 64, 2};
    make_map(enc, &p.kv, kv_ptr, 3, dims, st, box);
  }
  map2(enc, &p.o, d_out, OUTW, SEQ, 64, 64);
  {
    const uint64_t dims[3] = {64, NMAIN * 128, 4}, st[2] = {HD * 2, 128}; const uint32_t box[3] = {64, 64, 4};
    make_map(enc, &p.qc, qc_ptr, 3, dims, st, box);
  }
  concat_heads__ssm_conv_h3__compressed_kv_cla__prompt_kernel<<<NCTA, NTHREADS, SMEM_BYTES>>>(p);
}
```

```cpp
#include <cuda_runtime.h>
#include <cuda_bf16.h>
#include <cuda.h>
#include <stdint.h>

namespace {

typedef __nv_bfloat16 bf16;

constexpr int SEQ  = 2048;
constexpr int DA   = 448;
constexpr int NH   = 16;
constexpr int HD   = 256;
constexpr int DM   = 448;
constexpr int DC   = 1024;
constexpr int OUTW = DA + DM;
constexpr int NMAIN = 128;
constexpr int NCONV = 4;
constexpr int NCTA  = NMAIN + NCONV;
constexpr int LOG_DONE = 8;
constexpr int NTHREADS = 384;

__device__ __align__(1024) bf16 g_kv[2ull * SEQ * NH * HD];
__device__ __align__(1024) bf16 g_qc[(size_t)NMAIN * 128 * HD];
__device__ __align__(128) uint8_t g_xs[DA * SEQ * 2];
constexpr uint32_t HO_STRIDE = 4224;
__device__ __align__(128) uint8_t g_ho[DA * HO_STRIDE];
struct alignas(128) Flag { unsigned v; unsigned pad[31]; };
struct Flags {
  Flag kv_ready[NH];
  Flag ctx_ready[NMAIN * 2];
  Flag x_ready[7];
  Flag z_ready[7];
  Flag zero_ready[16];
  alignas(128) unsigned long long done;
};
__device__ Flags g_flags;
#define TS(i)
#define TSC(i, cond)
#define TDUMP()
#define GT(i)
#define PT(i)
#define PCLK(var)
#define PACC(acc, t0)

struct alignas(64) Params {
  CUtensorMap ckv;
  CUtensorMap wuk;
  CUtensorMap wuv;
  CUtensorMap x;
  CUtensorMap wq;
  CUtensorMap kv;
  CUtensorMap o;
  CUtensorMap qc;
  CUtensorMap wo;
  const bf16 *a_q, *a_k, *a_v, *a_shift, *a_ssmk, *a_D;
  bf16* out;
};

constexpr uint32_t SLOT     = 32768;
constexpr int      NSLOT    = 5;
constexpr uint32_t QREG     = 163840;
constexpr uint32_t BARS     = 229376;
constexpr uint32_t SMEM_BYTES = BARS + 1024 + 1024;
enum : uint32_t {
  B_FULL = 0, B_EMPTY = 5, B_XFREE = 10, B_ST_KV = 12, B_ST_Q = 14, B_ST_CTX = 16, B_KVOK = 18, B_DONE = 19, B_QFREE = 20, B_QFULL = 22,
  B_S2_FULL = 24, B_S2_EMPTY = 32, B_CTXOK = 40
};
constexpr int P1_STEPS = 4 * 16 + 2 * 7, P1_XS = P1_STEPS - 2;

template <typename T> __device__ __forceinline__ T* at(const void* base, uint32_t off) {
  asm volatile("" : "+r"(off));
  return reinterpret_cast<T*>(const_cast<char*>(static_cast<const char*>(base)) + off);
}
__device__ __forceinline__ unsigned* flag_at(Flag* f, uint32_t i) { return at<unsigned>(f, i * (uint32_t)sizeof(Flag)); }
__device__ __forceinline__ uint32_t smem_u32(const void* p) { return (uint32_t)__cvta_generic_to_shared(p); }
__device__ __forceinline__ void mbar_init(uint32_t bar, uint32_t cnt) {
  asm volatile("mbarrier.init.shared::cta.b64 [%0], %1;" :: "r"(bar), "r"(cnt) : "memory");
}
__device__ __forceinline__ void mbar_expect_tx(uint32_t bar, uint32_t bytes) {
  asm volatile("mbarrier.arrive.expect_tx.shared::cta.b64 _, [%0], %1;" :: "r"(bar), "r"(bytes) : "memory");
}
__device__ __forceinline__ void mbar_arrive(uint32_t bar) {
  asm volatile("mbarrier.arrive.shared::cta.b64 _, [%0];" :: "r"(bar) : "memory");
}
__device__ __forceinline__ void mbar_arrive_n(uint32_t bar, uint32_t n) {
  asm volatile("mbarrier.arrive.shared::cta.b64 _, [%0], %1;" :: "r"(bar), "r"(n) : "memory");
}
__device__ __forceinline__ void mbar_arrive_remote(uint32_t bar, uint32_t cta) {
  asm volatile("{\n.reg .b32 ra;\nmapa.shared::cluster.u32 ra, %0, %1;\n"
               "mbarrier.arrive.shared::cluster.b64 _, [ra];\n}" :: "r"(bar), "r"(cta) : "memory");
}
__device__ __forceinline__ bool mbar_try(uint32_t bar, uint32_t parity) {
  uint32_t ok;
  asm volatile("{\n.reg .pred p;\nmbarrier.try_wait.parity.shared::cta.b64 p, [%1], %2;\nselp.u32 %0, 1, 0, p;\n}"
               : "=r"(ok) : "r"(bar), "r"(parity) : "memory");
  return ok;
}
__device__ __forceinline__ uint32_t mbar_test(uint32_t bar, uint32_t parity) {
  uint32_t ok;
  asm volatile("{\n.reg .pred p;\nmbarrier.test_wait.parity.shared::cta.b64 p, [%1], %2;\nselp.u32 %0, 1, 0, p;\n}"
               : "=r"(ok) : "r"(bar), "r"(parity) : "memory");
  return ok;
}
constexpr uint32_t SPIN_LIMIT = 1u << 24;
__device__ __forceinline__ void mbar_wait(uint32_t bar, uint32_t parity) {
  if (mbar_try(bar, parity)) return;
  uint32_t n = 0;
  while (!mbar_try(bar, parity)) { if (++n > SPIN_LIMIT) __trap(); }
}
__device__ __forceinline__ void mbar_wait_unless(uint32_t ready, uint32_t bar, uint32_t parity) {
  asm volatile("{\n.reg .pred p;\n.reg .b32 n;\nsetp.ne.u32 p, %0, 0;\nvote.sync.all.pred p, p, 0xffffffff;\n@p bra.uni WDONE;\nmov.u32 n, 0;\n"
               "WLOOP:\nmbarrier.try_wait.parity.shared::cta.b64 p, [%1], %2;\n@p bra.uni WDONE;\nadd.u32 n, n, 1;\nsetp.lt.u32 p, n, %3;\n@p bra.uni WLOOP;\ntrap;\nWDONE:\n}"
               :: "r"(ready), "r"(bar), "r"(parity), "n"(SPIN_LIMIT) : "memory");
}
__device__ __forceinline__ unsigned load_epoch() {
  unsigned long long d; asm volatile("ld.relaxed.gpu.global.u64 %0, [%1];" : "=l"(d) : "l"(&g_flags.done) : "memory");
  return (unsigned)(d >> LOG_DONE);
}
__device__ __forceinline__ void flag_wait(const unsigned* f, unsigned count, unsigned epoch) {
  const unsigned target = (epoch + 1) * count;
  uint32_t n = 0;
  while (true) {
    unsigned v;
    asm volatile("ld.acquire.gpu.global.u32 %0, [%1];" : "=r"(v) : "l"(f) : "memory");
    if ((int)(v - target) >= 0) break;
    if (++n > SPIN_LIMIT) __trap();
    __nanosleep(20);
  }
}
__device__ __forceinline__ void flag_wait_slow(const unsigned* f, unsigned count, unsigned epoch) {
  const unsigned target = (epoch + 1) * count;
  uint32_t n = 0;
  while (true) {
    unsigned v;
    asm volatile("ld.acquire.gpu.global.u32 %0, [%1];" : "=r"(v) : "l"(f) : "memory");
    if ((int)(v - target) >= 0) break;
    if (++n > SPIN_LIMIT / 16) __trap();
    __nanosleep(1000);
  }
}
__device__ __forceinline__ void cta_done(unsigned long long n) { asm volatile("red.relaxed.gpu.global.add.u64 [%0], %1;" :: "l"(&g_flags.done), "l"(n) : "memory"); }
__device__ __forceinline__ void flag_wait_fast(const unsigned* f, unsigned count, unsigned epoch) {
  const unsigned target = (epoch + 1) * count;
  uint32_t n = 0;
  while (true) {
    unsigned v;
    asm volatile("ld.acquire.gpu.global.u32 %0, [%1];" : "=r"(v) : "l"(f) : "memory");
    if ((int)(v - target) >= 0) break;
    if (++n > SPIN_LIMIT) __trap();
  }
}
__device__ __forceinline__ void fence_async_all() { asm volatile("fence.proxy.async;" ::: "memory"); }
__device__ __forceinline__ void flag_signal(unsigned* f) {
  asm volatile("fence.acq_rel.gpu;" ::: "memory");
  asm volatile("red.relaxed.gpu.global.add.u32 [%0], 1;" :: "l"(f) : "memory");
}
__device__ __forceinline__ void flag_signal_after_bulk(unsigned* f) {
  asm volatile("red.relaxed.gpu.global.add.u32 [%0], 1;" :: "l"(f) : "memory");
}
__device__ __forceinline__ void fence_async_smem() { asm volatile("fence.proxy.async.shared::cta;" ::: "memory"); }
#define HINTS 0
constexpr uint64_t POL_NORMAL = 0x1000000000000000ull, POL_FIRST = 0x12F0000000000000ull;
__device__ __forceinline__ constexpr uint64_t pol(bool first) { return first ? POL_FIRST : POL_NORMAL; }
__device__ __forceinline__ void tma_ld2(uint32_t dst, const CUtensorMap* m, uint32_t bar, int c0, int c1, uint64_t pl = POL_NORMAL) {
  asm volatile("cp.async.bulk.tensor.2d.shared::cluster.global.mbarrier::complete_tx::bytes.L2::cache_hint [%0], [%1, {%3, %4}], [%2], %5;"
               :: "r"(dst), "l"(m), "r"(bar), "r"(c0), "r"(c1), "l"(pl) : "memory");
}
__device__ __forceinline__ void tma_ld3(uint32_t dst, const CUtensorMap* m, uint32_t bar, int c0, int c1, int c2, uint64_t pl = POL_NORMAL) {
  asm volatile("cp.async.bulk.tensor.3d.shared::cluster.global.mbarrier::complete_tx::bytes.L2::cache_hint [%0], [%1, {%3, %4, %5}], [%2], %6;"
               :: "r"(dst), "l"(m), "r"(bar), "r"(c0), "r"(c1), "r"(c2), "l"(pl) : "memory");
}
__device__ __forceinline__ void tma_ld3_mc(uint32_t dst, const CUtensorMap* m, uint32_t bar, int c0, int c1, int c2, uint64_t pl = POL_NORMAL) {
  asm volatile("cp.async.bulk.tensor.3d.shared::cluster.global.mbarrier::complete_tx::bytes.multicast::cluster.L2::cache_hint [%0], [%1, {%3, %4, %5}], [%2], %6, %7;"
               :: "r"(dst), "l"(m), "r"(bar), "r"(c0), "r"(c1), "r"(c2), "h"((uint16_t)3), "l"(pl) : "memory");
}
__device__ __forceinline__ void bulk_ld(uint32_t dst, const void* src, uint32_t bytes, uint32_t bar) {
  asm volatile("cp.async.bulk.shared::cluster.global.mbarrier::complete_tx::bytes [%0], [%1], %2, [%3];"
               :: "r"(dst), "l"(src), "r"(bytes), "r"(bar) : "memory");
}
__device__ __forceinline__ void tma_st3(const CUtensorMap* m, uint32_t src, int c0, int c1, int c2) {
  asm volatile("cp.async.bulk.tensor.3d.global.shared::cta.bulk_group.L2::cache_hint [%0, {%2, %3, %4}], [%1], %5;"
               :: "l"(m), "r"(src), "r"(c0), "r"(c1), "r"(c2), "l"(pol(HINTS & 1024)) : "memory");
}
__device__ __forceinline__ void tma_ld2_mc(uint32_t dst, const CUtensorMap* m, uint32_t bar, int c0, int c1, uint64_t pl = POL_NORMAL) {
  asm volatile("cp.async.bulk.tensor.2d.shared::cluster.global.mbarrier::complete_tx::bytes.multicast::cluster.L2::cache_hint [%0], [%1, {%3, %4}], [%2], %5, %6;"
               :: "r"(dst), "l"(m), "r"(bar), "r"(c0), "r"(c1), "h"((uint16_t)3), "l"(pl) : "memory");
}
__device__ __forceinline__ void tma_ld5_mc(uint32_t dst, const CUtensorMap* m, uint32_t bar, int c0, int c4, uint64_t pl = POL_NORMAL) {
  asm volatile("cp.async.bulk.tensor.5d.shared::cluster.global.mbarrier::complete_tx::bytes.multicast::cluster.L2::cache_hint [%0], [%1, {%3, %7, %7, %7, %4}], [%2], %5, %6;"
               :: "r"(dst), "l"(m), "r"(bar), "r"(c0), "r"(c4), "h"((uint16_t)3), "l"(pl), "r"(0) : "memory");
}
__device__ __forceinline__ void tma_st2(const CUtensorMap* m, uint32_t src, int c0, int c1) {
  asm volatile("cp.async.bulk.tensor.2d.global.shared::cta.bulk_group [%0, {%2, %3}], [%1];"
               :: "l"(m), "r"(src), "r"(c0), "r"(c1) : "memory");
}
__device__ __forceinline__ void tma_red2(const CUtensorMap* m, uint32_t src, int c0, int c1) {
  asm volatile("cp.reduce.async.bulk.tensor.2d.global.shared::cta.add.bulk_group [%0, {%2, %3}], [%1];"
               :: "l"(m), "r"(src), "r"(c0), "r"(c1) : "memory");
}
__device__ __forceinline__ void bulk_commit() { asm volatile("cp.async.bulk.commit_group;" ::: "memory"); }
__device__ __forceinline__ void bulk_wait_read() { asm volatile("cp.async.bulk.wait_group.read 0;" ::: "memory"); }
__device__ __forceinline__ void bulk_wait_all() { asm volatile("cp.async.bulk.wait_group 0;" ::: "memory"); }
__device__ __forceinline__ void prefetch_map(const CUtensorMap* m) { asm volatile("prefetch.tensormap [%0];" :: "l"(m) : "memory"); }
__device__ __forceinline__ void wg_fence() { asm volatile("wgmma.fence.sync.aligned;" ::: "memory"); }
__device__ __forceinline__ void wg_commit() { asm volatile("wgmma.commit_group.sync.aligned;" ::: "memory"); }
template <int N> __device__ __forceinline__ void wg_wait() { asm volatile("wgmma.wait_group.sync.aligned %0;" :: "n"(N) : "memory"); }
template <int N> __device__ __forceinline__ void reg_fence(float (&d)[N]) {
#pragma unroll
  for (int i = 0; i < N; i++) asm volatile("" : "+f"(d[i]) :: "memory");
}
template <int N> __device__ __forceinline__ void reg_fence(uint32_t (&d)[N]) {
#pragma unroll
  for (int i = 0; i < N; i++) asm volatile("" : "+r"(d[i]) :: "memory");
}
__device__ __forceinline__ uint32_t fresh_tid() { uint32_t t; asm volatile("mov.u32 %0, %%tid.x;" : "=r"(t)); return t; }
__device__ __forceinline__ uint32_t q_row(uint32_t g) { return ((g & 1) << 2) | (g >> 1); }
__device__ __forceinline__ uint32_t q_row_inv(uint32_t g) { return ((g & 3) << 1) | (g >> 2); }
__device__ __forceinline__ uint32_t lane_base16() {
  const uint32_t t = fresh_tid(), lane = t & 31, wq = (t >> 5) & 3, r = q_row_inv(lane & 7);
  return (16 * wq + r + 8 * ((lane >> 3) & 1)) * 128 + (((lane >> 4) ^ r) << 4);
}
__device__ __forceinline__ void named_sync(int id, int n) { asm volatile("bar.sync %0, %1;" :: "r"(id), "r"(n) : "memory"); }
__device__ __forceinline__ void named_arrive(int id, int n) { asm volatile("bar.arrive %0, %1;" :: "r"(id), "r"(n) : "memory"); }
__device__ __forceinline__ uint32_t pack_bf16(float lo, float hi) {
  uint32_t r; asm("cvt.rn.bf16x2.f32 %0, %1, %2;" : "=r"(r) : "f"(hi), "f"(lo)); return r;
}
__device__ __forceinline__ float ex2(float x) { float y; asm("ex2.approx.ftz.f32 %0, %1;" : "=f"(y) : "f"(x)); return y; }
__device__ __forceinline__ void stsm4(uint32_t addr, uint32_t a, uint32_t b, uint32_t c, uint32_t d) {
  asm volatile("stmatrix.sync.aligned.m8n8.x4.shared.b16 [%0], {%1, %2, %3, %4};" :: "r"(addr), "r"(a), "r"(b), "r"(c), "r"(d) : "memory");
}
__device__ __forceinline__ uint64_t mk_desc(uint32_t addr, uint32_t lbo, uint32_t sbo) {
  return (uint64_t)(((addr & 0x3FFFF) >> 4) | ((lbo >> 4) << 16)) | ((uint64_t)((sbo >> 4) | (1u << 30)) << 32);
}
__device__ __forceinline__ uint64_t desc_k(uint32_t addr)  { return mk_desc(addr, 16, 1024); }
__device__ __forceinline__ uint64_t desc_mn(uint32_t addr) { return mk_desc(addr, 8192, 1024); }
__device__ __forceinline__ uint64_t desc_add(uint64_t d, uint32_t bytes) { return d + (bytes >> 4); }

__device__ __forceinline__ void wgmma_ss_n256_tb(float (&d)[128], uint64_t da, uint64_t db, int sd) {
  asm volatile("{\n.reg .pred p;\nsetp.ne.b32 p, %130, 0;\n"
    "wgmma.mma_async.sync.aligned.m64n256k16.f32.bf16.bf16 "
    "{%0, %1, %2, %3, %4, %5, %6, %7, %8, %9, %10, %11, %12, %13, %14, %15, "
    "%16, %17, %18, %19, %20, %21, %22, %23, %24, %25, %26, %27, %28, %29, %30, %31, "
    "%32, %33, %34, %35, %36, %37, %38, %39, %40, %41, %42, %43, %44, %45, %46, %47, "
    "%48, %49, %50, %51, %52, %53, %54, %55, %56, %57, %58, %59, %60, %61, %62, %63, "
    "%64, %65, %66, %67, %68, %69, %70, %71, %72, %73, %74, %75, %76, %77, %78, %79, "
    "%80, %81, %82, %83, %84, %85, %86, %87, %88, %89, %90, %91, %92, %93, %94, %95, "
    "%96, %97, %98, %99, %100, %101, %102, %103, %104, %105, %106, %107, %108, %109, %110, %111, "
    "%112, %113, %114, %115, %116, %117, %118, %119, %120, %121, %122, %123, %124, %125, %126, %127}, "
    "%128, %129, p, 1, 1, 0, 1;\n}"
    : "+f"(d[0]), "+f"(d[1]), "+f"(d[2]), "+f"(d[3]), "+f"(d[4]), "+f"(d[5]), "+f"(d[6]), "+f"(d[7]),
      "+f"(d[8]), "+f"(d[9]), "+f"(d[10]), "+f"(d[11]), "+f"(d[12]), "+f"(d[13]), "+f"(d[14]), "+f"(d[15]),
      "+f"(d[16]), "+f"(d[17]), "+f"(d[18]), "+f"(d[19]), "+f"(d[20]), "+f"(d[21]), "+f"(d[22]), "+f"(d[23]),
      "+f"(d[24]), "+f"(d[25]), "+f"(d[26]), "+f"(d[27]), "+f"(d[28]), "+f"(d[29]), "+f"(d[30]), "+f"(d[31]),
      "+f"(d[32]), "+f"(d[33]), "+f"(d[34]), "+f"(d[35]), "+f"(d[36]), "+f"(d[37]), "+f"(d[38]), "+f"(d[39]),
      "+f"(d[40]), "+f"(d[41]), "+f"(d[42]), "+f"(d[43]), "+f"(d[44]), "+f"(d[45]), "+f"(d[46]), "+f"(d[47]),
      "+f"(d[48]), "+f"(d[49]), "+f"(d[50]), "+f"(d[51]), "+f"(d[52]), "+f"(d[53]), "+f"(d[54]), "+f"(d[55]),
      "+f"(d[56]), "+f"(d[57]), "+f"(d[58]), "+f"(d[59]), "+f"(d[60]), "+f"(d[61]), "+f"(d[62]), "+f"(d[63]),
      "+f"(d[64]), "+f"(d[65]), "+f"(d[66]), "+f"(d[67]), "+f"(d[68]), "+f"(d[69]), "+f"(d[70]), "+f"(d[71]),
      "+f"(d[72]), "+f"(d[73]), "+f"(d[74]), "+f"(d[75]), "+f"(d[76]), "+f"(d[77]), "+f"(d[78]), "+f"(d[79]),
      "+f"(d[80]), "+f"(d[81]), "+f"(d[82]), "+f"(d[83]), "+f"(d[84]), "+f"(d[85]), "+f"(d[86]), "+f"(d[87]),
      "+f"(d[88]), "+f"(d[89]), "+f"(d[90]), "+f"(d[91]), "+f"(d[92]), "+f"(d[93]), "+f"(d[94]), "+f"(d[95]),
      "+f"(d[96]), "+f"(d[97]), "+f"(d[98]), "+f"(d[99]), "+f"(d[100]), "+f"(d[101]), "+f"(d[102]), "+f"(d[103]),
      "+f"(d[104]), "+f"(d[105]), "+f"(d[106]), "+f"(d[107]), "+f"(d[108]), "+f"(d[109]), "+f"(d[110]), "+f"(d[111]),
      "+f"(d[112]), "+f"(d[113]), "+f"(d[114]), "+f"(d[115]), "+f"(d[116]), "+f"(d[117]), "+f"(d[118]), "+f"(d[119]),
      "+f"(d[120]), "+f"(d[121]), "+f"(d[122]), "+f"(d[123]), "+f"(d[124]), "+f"(d[125]), "+f"(d[126]), "+f"(d[127])
    : "l"(da), "l"(db), "r"(sd));
}
__device__ __forceinline__ void wgmma_ss_n64(float (&d)[32], uint64_t da, uint64_t db, int sd) {
  asm volatile("{\n.reg .pred p;\nsetp.ne.b32 p, %34, 0;\n"
    "wgmma.mma_async.sync.aligned.m64n64k16.f32.bf16.bf16 "
    "{%0, %1, %2, %3, %4, %5, %6, %7, %8, %9, %10, %11, %12, %13, %14, %15, "
    "%16, %17, %18, %19, %20, %21, %22, %23, %24, %25, %26, %27, %28, %29, %30, %31}, "
    "%32, %33, p, 1, 1, 0, 0;\n}"
    : "+f"(d[0]), "+f"(d[1]), "+f"(d[2]), "+f"(d[3]), "+f"(d[4]), "+f"(d[5]), "+f"(d[6]), "+f"(d[7]),
      "+f"(d[8]), "+f"(d[9]), "+f"(d[10]), "+f"(d[11]), "+f"(d[12]), "+f"(d[13]), "+f"(d[14]), "+f"(d[15]),
      "+f"(d[16]), "+f"(d[17]), "+f"(d[18]), "+f"(d[19]), "+f"(d[20]), "+f"(d[21]), "+f"(d[22]), "+f"(d[23]),
      "+f"(d[24]), "+f"(d[25]), "+f"(d[26]), "+f"(d[27]), "+f"(d[28]), "+f"(d[29]), "+f"(d[30]), "+f"(d[31])
    : "l"(da), "l"(db), "r"(sd));
}
__device__ __forceinline__ void wgmma_rs_n256_tb(float (&d)[128], uint32_t a0, uint32_t a1, uint32_t a2, uint32_t a3, uint64_t db, int sd) {
  asm volatile("{\n.reg .pred p;\nsetp.ne.b32 p, %133, 0;\n"
    "wgmma.mma_async.sync.aligned.m64n256k16.f32.bf16.bf16 "
    "{%0, %1, %2, %3, %4, %5, %6, %7, %8, %9, %10, %11, %12, %13, %14, %15, "
    "%16, %17, %18, %19, %20, %21, %22, %23, %24, %25, %26, %27, %28, %29, %30, %31, "
    "%32, %33, %34, %35, %36, %37, %38, %39, %40, %41, %42, %43, %44, %45, %46, %47, "
    "%48, %49, %50, %51, %52, %53, %54, %55, %56, %57, %58, %59, %60, %61, %62, %63, "
    "%64, %65, %66, %67, %68, %69, %70, %71, %72, %73, %74, %75, %76, %77, %78, %79, "
    "%80, %81, %82, %83, %84, %85, %86, %87, %88, %89, %90, %91, %92, %93, %94, %95, "
    "%96, %97, %98, %99, %100, %101, %102, %103, %104, %105, %106, %107, %108, %109, %110, %111, "
    "%112, %113, %114, %115, %116, %117, %118, %119, %120, %121, %122, %123, %124, %125, %126, %127}, "
    "{%128, %129, %130, %131}, %132, p, 1, 1, 1;\n}"
    : "+f"(d[0]), "+f"(d[1]), "+f"(d[2]), "+f"(d[3]), "+f"(d[4]), "+f"(d[5]), "+f"(d[6]), "+f"(d[7]),
      "+f"(d[8]), "+f"(d[9]), "+f"(d[10]), "+f"(d[11]), "+f"(d[12]), "+f"(d[13]), "+f"(d[14]), "+f"(d[15]),
      "+f"(d[16]), "+f"(d[17]), "+f"(d[18]), "+f"(d[19]), "+f"(d[20]), "+f"(d[21]), "+f"(d[22]), "+f"(d[23]),
      "+f"(d[24]), "+f"(d[25]), "+f"(d[26]), "+f"(d[27]), "+f"(d[28]), "+f"(d[29]), "+f"(d[30]), "+f"(d[31]),
      "+f"(d[32]), "+f"(d[33]), "+f"(d[34]), "+f"(d[35]), "+f"(d[36]), "+f"(d[37]), "+f"(d[38]), "+f"(d[39]),
      "+f"(d[40]), "+f"(d[41]), "+f"(d[42]), "+f"(d[43]), "+f"(d[44]), "+f"(d[45]), "+f"(d[46]), "+f"(d[47]),
      "+f"(d[48]), "+f"(d[49]), "+f"(d[50]), "+f"(d[51]), "+f"(d[52]), "+f"(d[53]), "+f"(d[54]), "+f"(d[55]),
      "+f"(d[56]), "+f"(d[57]), "+f"(d[58]), "+f"(d[59]), "+f"(d[60]), "+f"(d[61]), "+f"(d[62]), "+f"(d[63]),
      "+f"(d[64]), "+f"(d[65]), "+f"(d[66]), "+f"(d[67]), "+f"(d[68]), "+f"(d[69]), "+f"(d[70]), "+f"(d[71]),
      "+f"(d[72]), "+f"(d[73]), "+f"(d[74]), "+f"(d[75]), "+f"(d[76]), "+f"(d[77]), "+f"(d[78]), "+f"(d[79]),
      "+f"(d[80]), "+f"(d[81]), "+f"(d[82]), "+f"(d[83]), "+f"(d[84]), "+f"(d[85]), "+f"(d[86]), "+f"(d[87]),
      "+f"(d[88]), "+f"(d[89]), "+f"(d[90]), "+f"(d[91]), "+f"(d[92]), "+f"(d[93]), "+f"(d[94]), "+f"(d[95]),
      "+f"(d[96]), "+f"(d[97]), "+f"(d[98]), "+f"(d[99]), "+f"(d[100]), "+f"(d[101]), "+f"(d[102]), "+f"(d[103]),
      "+f"(d[104]), "+f"(d[105]), "+f"(d[106]), "+f"(d[107]), "+f"(d[108]), "+f"(d[109]), "+f"(d[110]), "+f"(d[111]),
      "+f"(d[112]), "+f"(d[113]), "+f"(d[114]), "+f"(d[115]), "+f"(d[116]), "+f"(d[117]), "+f"(d[118]), "+f"(d[119]),
      "+f"(d[120]), "+f"(d[121]), "+f"(d[122]), "+f"(d[123]), "+f"(d[124]), "+f"(d[125]), "+f"(d[126]), "+f"(d[127])
    : "r"(a0), "r"(a1), "r"(a2), "r"(a3), "l"(db), "r"(sd));
}
__device__ __forceinline__ void wgmma_rs_n64_tb(float (&d)[32], uint32_t a0, uint32_t a1, uint32_t a2, uint32_t a3, uint64_t db, int sd) {
  asm volatile("{\n.reg .pred p;\nsetp.ne.b32 p, %37, 0;\n"
    "wgmma.mma_async.sync.aligned.m64n64k16.f32.bf16.bf16 "
    "{%0, %1, %2, %3, %4, %5, %6, %7, %8, %9, %10, %11, %12, %13, %14, %15, "
    "%16, %17, %18, %19, %20, %21, %22, %23, %24, %25, %26, %27, %28, %29, %30, %31}, "
    "{%32, %33, %34, %35}, %36, p, 1, 1, 1;\n}"
    : "+f"(d[0]), "+f"(d[1]), "+f"(d[2]), "+f"(d[3]), "+f"(d[4]), "+f"(d[5]), "+f"(d[6]), "+f"(d[7]),
      "+f"(d[8]), "+f"(d[9]), "+f"(d[10]), "+f"(d[11]), "+f"(d[12]), "+f"(d[13]), "+f"(d[14]), "+f"(d[15]),
      "+f"(d[16]), "+f"(d[17]), "+f"(d[18]), "+f"(d[19]), "+f"(d[20]), "+f"(d[21]), "+f"(d[22]), "+f"(d[23]),
      "+f"(d[24]), "+f"(d[25]), "+f"(d[26]), "+f"(d[27]), "+f"(d[28]), "+f"(d[29]), "+f"(d[30]), "+f"(d[31])
    : "r"(a0), "r"(a1), "r"(a2), "r"(a3), "l"(db), "r"(sd));
}
__device__ __forceinline__ void wgmma_rs_n32(float (&d)[16], uint32_t a0, uint32_t a1, uint32_t a2, uint32_t a3, uint64_t db, int sd) {
  asm volatile("{\n.reg .pred p;\nsetp.ne.b32 p, %21, 0;\n"
    "wgmma.mma_async.sync.aligned.m64n32k16.f32.bf16.bf16 "
    "{%0, %1, %2, %3, %4, %5, %6, %7, %8, %9, %10, %11, %12, %13, %14, %15}, "
    "{%16, %17, %18, %19}, %20, p, 1, 1, 0;\n}"
    : "+f"(d[0]), "+f"(d[1]), "+f"(d[2]), "+f"(d[3]), "+f"(d[4]), "+f"(d[5]), "+f"(d[6]), "+f"(d[7]),
      "+f"(d[8]), "+f"(d[9]), "+f"(d[10]), "+f"(d[11]), "+f"(d[12]), "+f"(d[13]), "+f"(d[14]), "+f"(d[15])
    : "r"(a0), "r"(a1), "r"(a2), "r"(a3), "l"(db), "r"(sd));
}
__device__ __forceinline__ void wgmma_rs_n64(float (&d)[32], uint32_t a0, uint32_t a1, uint32_t a2, uint32_t a3, uint64_t db, int sd) {
  asm volatile("{\n.reg .pred p;\nsetp.ne.b32 p, %37, 0;\n"
    "wgmma.mma_async.sync.aligned.m64n64k16.f32.bf16.bf16 "
    "{%0, %1, %2, %3, %4, %5, %6, %7, %8, %9, %10, %11, %12, %13, %14, %15, "
    "%16, %17, %18, %19, %20, %21, %22, %23, %24, %25, %26, %27, %28, %29, %30, %31}, "
    "{%32, %33, %34, %35}, %36, p, 1, 1, 0;\n}"
    : "+f"(d[0]), "+f"(d[1]), "+f"(d[2]), "+f"(d[3]), "+f"(d[4]), "+f"(d[5]), "+f"(d[6]), "+f"(d[7]),
      "+f"(d[8]), "+f"(d[9]), "+f"(d[10]), "+f"(d[11]), "+f"(d[12]), "+f"(d[13]), "+f"(d[14]), "+f"(d[15]),
      "+f"(d[16]), "+f"(d[17]), "+f"(d[18]), "+f"(d[19]), "+f"(d[20]), "+f"(d[21]), "+f"(d[22]), "+f"(d[23]),
      "+f"(d[24]), "+f"(d[25]), "+f"(d[26]), "+f"(d[27]), "+f"(d[28]), "+f"(d[29]), "+f"(d[30]), "+f"(d[31])
    : "r"(a0), "r"(a1), "r"(a2), "r"(a3), "l"(db), "r"(sd));
}

__device__ __forceinline__ uint4 lds16(uint32_t a) {
  uint4 v; asm volatile("ld.shared.v4.u32 {%0, %1, %2, %3}, [%4];" : "=r"(v.x), "=r"(v.y), "=r"(v.z), "=r"(v.w) : "r"(a) : "memory"); return v;
}
__device__ __forceinline__ void sts16(uint32_t a, uint32_t x, uint32_t y, uint32_t z, uint32_t w) {
  asm volatile("st.shared.v4.u32 [%0], {%1, %2, %3, %4};" :: "r"(a), "r"(x), "r"(y), "r"(z), "r"(w) : "memory");
}
__device__ __forceinline__ uint32_t lds4(uint32_t a) { uint32_t v; asm volatile("ld.shared.u32 %0, [%1];" : "=r"(v) : "r"(a) : "memory"); return v; }
__device__ __forceinline__ uint32_t lds4v(uint32_t a) { uint32_t v; asm volatile("ld.volatile.shared.u32 %0, [%1];" : "=r"(v) : "r"(a) : "memory"); return v; }
__device__ __forceinline__ uint32_t bmul(uint32_t a, uint32_t b) { uint32_t r; asm("mul.rn.bf16x2 %0, %1, %2;" : "=r"(r) : "r"(a), "r"(b)); return r; }
__device__ __forceinline__ uint32_t badd(uint32_t a, uint32_t b) { uint32_t r; asm("add.rn.bf16x2 %0, %1, %2;" : "=r"(r) : "r"(a), "r"(b)); return r; }

__device__ __forceinline__ void ldsm4(uint32_t (&r)[4], uint32_t a) {
  asm volatile("ldmatrix.sync.aligned.m8n8.x4.shared.b16 {%0, %1, %2, %3}, [%4];" : "=r"(r[0]), "=r"(r[1]), "=r"(r[2]), "=r"(r[3]) : "r"(a) : "memory");
}
__device__ __forceinline__ uint32_t transpose8(uint32_t a) { uint32_t d; asm volatile("movmatrix.sync.aligned.m8n8.trans.b16 %0, %1;" : "=r"(d) : "r"(a)); return d; }

__device__ __forceinline__ void mma16816(float (&d)[4], const uint32_t (&a)[4], uint32_t b0, uint32_t b1) {
  asm volatile("mma.sync.aligned.m16n8k16.row.col.f32.bf16.bf16.f32 {%0, %1, %2, %3}, {%4, %5, %6, %7}, {%8, %9}, {%0, %1, %2, %3};"
               : "+f"(d[0]), "+f"(d[1]), "+f"(d[2]), "+f"(d[3]) : "r"(a[0]), "r"(a[1]), "r"(a[2]), "r"(a[3]), "r"(b0), "r"(b1));
}

#define EXP_SIDE 0
#define SIDE_AHEAD 3
#define ZERO_RD 4
#define CTX_SPLIT 8
#define CONV_EARLY 8
#define CONV_FENCE 12
#define CTX_LD 16
#define PF_Q 0
#define HOOK_DEP s[4 * jj]
#define PEEK_JJ 0
#define CONV_ARRIVE 13
#define ARRIVE_KK 12
#define SIDE_DELAY_NS 4000
#define KVH(h) (h)
#define HEAD_MAP 1
#define EARLY_LD 3
constexpr int RED_BAR = 6;
constexpr int CV_BAR = 5;
constexpr int PP_BAR = 3;
template <int V> struct Int { static constexpr int value = V; };
struct Ring {
  uint32_t slot, phase;
  __device__ __forceinline__ void next() { if (++slot == NSLOT) { slot = 0; phase ^= 1; } }
};
__device__ __forceinline__ uint32_t bar_addr(uint32_t sb, uint32_t i) { return sb + BARS + 8 * i; }

__device__ __forceinline__ int q_tile(int h, int j, int which) { return ((h < 8) == (which == 0)) ? 15 - j : j; }

__device__ __forceinline__ int att_head(int h, int which) { return h; }
__device__ __forceinline__ int p1_head(int h, int t) { return h; }
__device__ __forceinline__ int p1_isv(int t) { return t >> 1; }
__device__ __forceinline__ int p1_rows(int h, int j, int t) { return 2 * j + (t & 1); }
#define KV_FLAG(h) (h)
#define KV_COUNT 16

__device__ __forceinline__ void load_tile4(uint32_t dst, const CUtensorMap* m, uint32_t full, int row, int blk0, int rank, bool shared, uint64_t pl = POL_NORMAL) {
  if (shared) {
    tma_ld3_mc(dst + rank * 16384, m, full, 0, row, blk0 + 2 * rank, pl);
  } else {
    tma_ld3(dst, m, full, 0, row, blk0, pl);
    tma_ld3(dst + 16384, m, full, 0, row, blk0 + 2, pl);
  }
}
__device__ __forceinline__ void producer_main(const Params& p, uint32_t sb, int h, int j) {
  const int rank = j & 1;
  Ring r{EARLY_LD, 0};
  auto wait_slot = [&]() { mbar_wait(bar_addr(sb, B_EMPTY + r.slot), r.phase ^ 1); };
  auto load_a = [&](int it, uint32_t dst, uint32_t full) {
    if (it < 64) tma_ld2(dst, &p.ckv, full, (it & 15) * 64, p1_rows(h, j, it >> 4) * 128, pol((HINTS & 2) && it >= 48));
    else tma_ld2(dst, &p.x, full, (it < 71 ? it - 64 : it - 71) * 64, q_tile(h, j, it < 71) * 128, pol(HINTS & 64));
  };
  uint32_t prev = 0;
#pragma unroll 1
  for (int it = EARLY_LD; it < P1_STEPS; it++) {
    wait_slot();
    if (it > EARLY_LD && it <= P1_XS) load_a(it - 1, sb + QREG + ((it - 1) & 3) * 16384, prev);
    const uint32_t full = bar_addr(sb, B_FULL + r.slot), dst = sb + r.slot * SLOT;
    mbar_expect_tx(full, it < P1_XS ? 49152 : 32768);
    if (it < 64) load_tile4(dst, p1_isv(it >> 4) ? &p.wuv : &p.wuk, full, (it & 15) * 64, p1_head(h, it >> 4) * 4, rank, true, pol(HINTS & 1));
    else load_tile4(dst, &p.wq, full, (it < 71 ? it - 64 : it - 71) * 64, att_head(h, it < 71) * 4, rank, true, pol(HINTS & 4));
    prev = full;
    r.next();
    if (PF_Q && it >= PF_Q && it < PF_Q + 14 && !(it & 1)) {
      const int k = (it - PF_Q) >> 1;
      asm volatile("cp.async.bulk.prefetch.tensor.2d.L2.global [%0, {%1, %2}];" :: "l"(&p.x), "r"(k * 64), "r"(q_tile(h, j, 1) * 128) : "memory");
      asm volatile("cp.async.bulk.prefetch.tensor.3d.L2.global [%0, {%1, %2, %3}];" :: "l"(&p.wq), "r"(0), "r"(k * 64), "r"(att_head(h, 1) * 4 + 2 * rank) : "memory");
    }
    if (it == P1_XS) {
      wait_slot();
      const uint32_t f2 = bar_addr(sb, B_FULL + r.slot);
      mbar_expect_tx(f2, 32768);
      load_a(P1_XS, sb + r.slot * SLOT, f2);
      load_a(P1_XS + 1, sb + r.slot * SLOT + 16384, f2);
      r.next();
    }
  }
  mbar_wait(bar_addr(sb, B_KVOK), 0);
  const int qa = q_tile(h, j, 0), na = 2 * qa + 2, own = 2 * (qa & ~1) + 2;
#pragma unroll 1
  for (int f = 0; f < 68; f++) {
    const bool isK = (f == 0) || ((f & 1) && f < 67);
    const int i = isK ? (f + 1) >> 1 : (f - 1) >> 1, which = i >= na;
    wait_slot();
    const uint32_t full = bar_addr(sb, B_FULL + r.slot);
    mbar_expect_tx(full, 32768);
    load_tile4(sb + r.slot * SLOT, &p.kv, full, ((isK ? 0 : NH) + KVH(att_head(h, which))) * SEQ + (which ? 33 - i : i) * 64, 0, rank, (i & ~1) != own,
               pol(which ? (HINTS & 32) : (HINTS & 8)));
    r.next();
  }
#pragma unroll 1
  for (int f = 0; f < 14; f++) {
    const int ch = f < 12 ? 2 * (f >> 2) + (f & 1) : 6, par = f < 12 ? (f >> 1) & 1 : f & 1;
    wait_slot();
    const uint32_t full = bar_addr(sb, B_FULL + r.slot);
    mbar_expect_tx(full, 32768);
    tma_ld5_mc(sb + r.slot * SLOT + rank * 16384, &p.wo, full, ch * 64, (par ? att_head(h ^ 8, 0) : att_head(h, 1)) * 8 + rank * 4, pol(HINTS & 16));
    r.next();
  }
}

__device__ __forceinline__ void helper_main(const Params& p, uint32_t sb, int h, int j, int w) {
  const unsigned epoch = load_epoch();
  const int cta = h * 8 + j, qb = q_tile(h, j, 1);
  const uint32_t qreg = sb + QREG + w * 32768, qfull = bar_addr(sb, B_QFULL + w);
  mbar_wait(bar_addr(sb, B_ST_KV + w), 0);
  flag_signal(flag_at(g_flags.kv_ready, KV_FLAG(h)));
  if (w == 0) {
    flag_wait(flag_at(g_flags.kv_ready, KV_FLAG(h)), KV_COUNT, epoch);
    fence_async_all();
    mbar_arrive(bar_addr(sb, B_KVOK));
  }
  mbar_wait(bar_addr(sb, B_ST_Q + w), 0);
  asm volatile("fence.acq_rel.gpu;" ::: "memory");
  fence_async_all();
  mbar_wait(bar_addr(sb, B_QFREE + w), 0);
  mbar_expect_tx(qfull, 32768);
  tma_ld3(qreg, &p.qc, qfull, 0, cta * 128 + w * 64, 0);
  auto publish = [&]() { mbar_wait(bar_addr(sb, B_ST_CTX + w), 0); flag_signal(flag_at(g_flags.ctx_ready, cta * 2 + w)); };
  if (qb >= 8) publish();
  flag_wait(flag_at(g_flags.ctx_ready, (cta ^ 64) * 2 + (w ^ 1)), 1, epoch);
  mbar_arrive(bar_addr(sb, B_CTXOK + w));
  if (qb < 8) publish();
  flag_wait(flag_at(g_flags.zero_ready, qb), 8, epoch);
  fence_async_all();
#pragma unroll 1
  for (int ch = 0; ch < 7; ch++) {
    mbar_wait(bar_addr(sb, B_S2_FULL + w * 4 + (ch & 3)), ch >> 2);
    tma_red2(&p.o, qreg + (ch & 3) * 8192, DA + ch * 64, qb * 128 + (w ^ 1) * 64);
    bulk_commit();
    if (ch < 3) { bulk_wait_read(); mbar_arrive(bar_addr(sb, B_S2_EMPTY + w * 4 + ch)); }
  }
  bulk_wait_read();
  GT(48 + w);
}

__device__ __forceinline__ void store_block(uint32_t base, uint32_t lanebase, const uint32_t (&pk)[16]) {
#pragma unroll
  for (int J = 0; J < 8; J += 2) stsm4(base + (lanebase ^ (J << 4)), pk[2 * J], pk[2 * J + 1], pk[2 * J + 2], pk[2 * J + 3]);
}
__device__ __forceinline__ void pack_chunks(uint32_t (&pk)[64], const float (&acc)[128]) {
#pragma unroll
  for (int i = 0; i < 64; i++) { const int e = 16 * (i >> 3) + 4 * (i & 3) + 2 * ((i >> 2) & 1); pk[i] = pack_bf16(acc[e], acc[e + 1]); }
}
__device__ __forceinline__ uint32_t chunk_off(bool q) {
  const uint32_t t = fresh_tid();
  return (t & 96) * 256 + (q ? ((t & 24) << 6) | ((t & 4) << 9) : (t & 28) << 7) + (t & 3) * 16;
}
__device__ __forceinline__ void warp_arrive(uint32_t bar, int lane) { __syncwarp(); if (lane == 0) mbar_arrive(bar); }

__device__ __forceinline__ void consumer_main(const Params& p, uint32_t sb, int h, int j, int w) {
  const int lane = threadIdx.x & 31;
  const int rank = j & 1;

  auto turn_begin = [&]() { named_sync(PP_BAR + w, 256); };
  auto turn_end = [&]() { named_arrive(PP_BAR + (w ^ 1), 256); };
  if (w == 1) named_arrive(PP_BAR, 256);
  Ring r{0, 0};
  auto take = [&](uint32_t ready = 0) { const uint32_t sl = r.slot; mbar_wait_unless(ready, bar_addr(sb, B_FULL + sl), r.phase); r.next(); return sl; };
  uint32_t rdy0 = 0, rdy1 = 0;
  auto peek2 = [&]() { Ring q = r; rdy0 = mbar_test(bar_addr(sb, B_FULL + q.slot), q.phase); q.next(); rdy1 = mbar_test(bar_addr(sb, B_FULL + q.slot), q.phase); };
  auto give = [&](uint32_t sl) { if (lane < 2) mbar_arrive_remote(bar_addr(sb, B_EMPTY + sl), rank ^ lane); };
  float acc[128];
#pragma unroll
  for (int i = 0; i < 128; i++) acc[i] = 0.f;
  uint32_t pk[64];
#pragma unroll
  for (int i = 0; i < 64; i++) pk[i] = 0;
  TS(0);
  const uint32_t qreg = sb + QREG + w * 32768;
  {
    uint32_t xs = 0, prev = 0;
    uint4* row = nullptr;
    int it = 0;
#pragma unroll 1
    for (int t = 0; t < 6; t++) {
      const int nk = t < 4 ? 16 : 7;
#pragma unroll 1
      for (int k = 0; k < nk; k++, it++) {
        const uint32_t ws = take(rdy0);
        TSC(1, it == 0);
        if (it == P1_XS) xs = take();
        const uint32_t aa = (it < P1_XS ? QREG + (it & 3) * 16384 : xs * SLOT + (it - P1_XS) * 16384) + (w ^ (t == 4)) * 8192;
        const uint64_t da = desc_k(sb + aa), db = desc_mn(sb + ws * SLOT);
        turn_begin();
        wg_fence();
#pragma unroll
        for (int kk = 0; kk < 4; kk++) wgmma_ss_n256_tb(acc, desc_add(da, kk * 32), desc_add(db, kk * 2048), (k | kk) != 0);
        wg_commit();
        turn_end();
        rdy0 = mbar_test(bar_addr(sb, B_FULL + r.slot), r.phase);
        wg_wait<1>();
        if (k > 0) give(prev);
        prev = ws;
        if (it >= P1_XS - 2 && !(it & 1) && lane == 0) mbar_arrive(bar_addr(sb, B_XFREE + ((it - (P1_XS - 2)) >> 1)));
        if (t > 0) {
          const int c0 = t < 4 ? k : 3 * k, c1 = t < 4 ? k + 1 : 3 * k + 3;
#pragma unroll
          for (int i = 0; i < 16; i++)
            if (i >= c0 && i < c1) row[(i & 1) * 256 + (i >> 1) * 4] = make_uint4(pk[4 * i], pk[4 * i + 1], pk[4 * i + 2], pk[4 * i + 3]);
          if (t >= 4 && k == 5) warp_arrive(bar_addr(sb, (t == 4 ? B_ST_KV : B_ST_Q) + w), lane);
        }
      }
      if (t == 5) mbar_wait(bar_addr(sb, B_XFREE + w), 0);
      wg_wait<0>();
      reg_fence(acc);
      give(prev);
      pack_chunks(pk, acc);
      row = at<uint4>(t < 4 ? (const void*)g_kv : (const void*)g_qc, chunk_off(t >= 4) +
                      (t < 4 ? (uint32_t)((p1_isv(t) * NH + KVH(p1_head(h, t))) * SEQ + p1_rows(h, j, t) * 128 + w * 64) * 512 : (uint32_t)((h * 8 + j) * 2 + w) * 32768));
      TS(2 + t);
    }
    give(xs);
    const uint32_t ft = fresh_tid(), g = q_row((ft & 31) >> 2);
    const uint32_t qa = qreg + (16 * ((ft >> 5) & 3) + g) * 128 + (((ft & 3) ^ g) << 4);
#pragma unroll
    for (int i = 0; i < 16; i++) sts16((qa ^ ((i & 2) << 5)) + (i >> 2) * 8192 + (i & 1) * 1024, pk[4 * i], pk[4 * i + 1], pk[4 * i + 2], pk[4 * i + 3]);
    fence_async_smem();
  }
  TS(8);

  constexpr float SC = 0.0625f * 1.4426950408889634f;
#pragma unroll 1
  for (int which = 0; which < 2; which++) {
    float s[32];
#pragma unroll
    for (int i = 0; i < 32; i++) s[i] = 0.f;
    uint32_t pa[16], pb[16];
    float m0 = -INFINITY, m1 = -INFINITY, l0 = 0.f, l1 = 0.f;
    const uint64_t dq = desc_k(qreg);
    uint64_t dk = 0, dqq = 0, dv = 0;
    auto prep_qk = [&](uint32_t kaddr) { dk = desc_k(kaddr); dqq = dq + (kaddr >> 31); asm volatile("" : "+l"(dk), "+l"(dqq)); };
    auto prep_pv = [&](uint32_t vaddr) { dv = desc_mn(vaddr); asm volatile("" : "+l"(dv)); };
    auto issue_qk = [&]() {
#pragma unroll
      for (int kk = 0; kk < 16; kk++)
        wgmma_ss_n64(s, desc_add(dqq, (kk >> 2) * 8192 + (kk & 3) * 32), desc_add(dk, (kk >> 2) * 8192 + (kk & 3) * 32), kk != 0);
    };
    auto issue_pv = [&](int accumulate) {
#pragma unroll
      for (int kk = 0; kk < 4; kk++)
        wgmma_rs_n256_tb(acc, pa[4 * kk], pa[4 * kk + 1], pa[4 * kk + 2], pa[4 * kk + 3], desc_add(dv, kk * 2048), accumulate | kk);
    };
    auto mask_diag = [&]() {
      const uint32_t ft = fresh_tid();
      const int r0 = 16 * ((ft >> 5) & 3) + q_row_inv((ft & 31) >> 2), c = ft & 3;
#pragma unroll
      for (int jj = 0; jj < 8; jj++) {
        const int cc = 8 * jj + 2 * c;
        if (cc > r0)         s[4 * jj]     = -INFINITY;
        if (cc + 1 > r0)     s[4 * jj + 1] = -INFINITY;
        if (cc > r0 + 8)     s[4 * jj + 2] = -INFINITY;
        if (cc + 1 > r0 + 8) s[4 * jj + 3] = -INFINITY;
      }
    };
    float a0, a1;
    auto softmax = [&](auto hook) -> bool {
      float x0 = fmaxf(s[0], s[1]), x1 = fmaxf(s[2], s[3]);
#pragma unroll
      for (int jj = 1; jj < 8; jj++) {
        x0 = fmaxf(x0, fmaxf(s[4 * jj], s[4 * jj + 1]));
        x1 = fmaxf(x1, fmaxf(s[4 * jj + 2], s[4 * jj + 3]));
      }
      x0 = fmaxf(x0, __shfl_xor_sync(0xffffffffu, x0, 1));
      x1 = fmaxf(x1, __shfl_xor_sync(0xffffffffu, x1, 1));
      x0 = fmaxf(x0, __shfl_xor_sync(0xffffffffu, x0, 2));
      x1 = fmaxf(x1, __shfl_xor_sync(0xffffffffu, x1, 2));
      const bool grow = __any_sync(0xffffffffu, fmaxf(x0 - m0, x1 - m1) * SC > 8.f);
      if (grow) {
        x0 = fmaxf(x0, m0); x1 = fmaxf(x1, m1);
        a0 = ex2((m0 - x0) * SC); a1 = ex2((m1 - x1) * SC);
        m0 = x0; m1 = x1;
        l0 *= a0; l1 *= a1;
      }
      const float b0 = -m0 * SC, b1 = -m1 * SC;
      float t0 = 0.f, t1 = 0.f, t2 = 0.f, t3 = 0.f;
#pragma unroll
      for (int jj = 0; jj < 8; jj++) {
        s[4 * jj]     = ex2(fmaf(s[4 * jj], SC, b0));
        s[4 * jj + 1] = ex2(fmaf(s[4 * jj + 1], SC, b0));
        s[4 * jj + 2] = ex2(fmaf(s[4 * jj + 2], SC, b1));
        s[4 * jj + 3] = ex2(fmaf(s[4 * jj + 3], SC, b1));
        t0 += s[4 * jj]; t1 += s[4 * jj + 1]; t2 += s[4 * jj + 2]; t3 += s[4 * jj + 3];
        hook(jj, HOOK_DEP);
      }
      l0 += t0 + t1; l1 += t2 + t3;
      return grow;
    };
    auto softmax_fast = [&]() -> bool {
      const float b0 = -m0 * SC, b1 = -m1 * SC;
      float t0 = 0.f, t1 = 0.f, t2 = 0.f, t3 = 0.f;
#pragma unroll
      for (int jj = 0; jj < 8; jj++) {
        const float e0 = ex2(fmaf(s[4 * jj], SC, b0)), e1 = ex2(fmaf(s[4 * jj + 1], SC, b0));
        const float e2 = ex2(fmaf(s[4 * jj + 2], SC, b1)), e3 = ex2(fmaf(s[4 * jj + 3], SC, b1));
        pb[2 * jj] = pack_bf16(e0, e1); pb[2 * jj + 1] = pack_bf16(e2, e3);
        if (jj == 0) { t0 = e0; t1 = e1; t2 = e2; t3 = e3; } else { t0 += e0; t1 += e1; t2 += e2; t3 += e3; }
      }
      t0 += t1; t2 += t3;
      const bool redo = __any_sync(0xffffffffu, !(t0 + t2 <= 16777216.f));
      if (!redo) { l0 += t0; l1 += t2; }
      return redo;
    };
    auto rescale = [&]() {
#pragma unroll
      for (int i = 0; i < 32; i++) { acc[4 * i] *= a0; acc[4 * i + 1] *= a0; acc[4 * i + 2] *= a1; acc[4 * i + 3] *= a1; }
    };
    auto to_p = [&](uint32_t (&pp)[16]) {
#pragma unroll
      for (int i = 0; i < 16; i++) pp[i] = pack_bf16(s[2 * i], s[2 * i + 1]);
    };
    auto q_free = [&]() { if (lane == 0) mbar_arrive(bar_addr(sb, B_QFREE + w)); };

    const int n = 2 * q_tile(h, j, which) + 1 + (w ^ which);
    uint32_t ks = take(rdy0);
    TS(9 + 5 * which);
    prep_qk(sb + ks * SLOT);
    turn_begin();
    TS(20 + 10 * which);
    wg_fence();
    issue_qk();
    wg_commit();
    turn_end();
    if (which == 1) give(take(rdy1));
    TS(22 + 10 * which);
    wg_wait<0>();
    TS(21 + 10 * which);
    reg_fence(s);
    give(ks);
    if (which == 0 && n == 1) q_free();
    if (which == 1 || n == 1) mask_diag();
    {
      const uint4* dst = at<uint4>(g_qc, (uint32_t)((h * 8 + j) * 2 + w) * 32768 + (fresh_tid() & 127) * 16);
      softmax([&](int jj, float e) {
        if (jj == PEEK_JJ) peek2();
        const int i = CTX_SPLIT + jj;
        if (i < 16)
          asm volatile("{\n.reg .pred p, q;\nsetp.ne.b32 q, %6, 0;\nsetp.geu.and.f32 p, %5, 0fBF800000, q;\n@p st.global.v4.u32 [%0], {%1, %2, %3, %4};\n}"
                       :: "l"(dst + i * 128), "r"(pk[4 * (i & 15)]), "r"(pk[4 * (i & 15) + 1]), "r"(pk[4 * (i & 15) + 2]), "r"(pk[4 * (i & 15) + 3]), "f"(e), "r"(which) : "memory");
      });
    }
    to_p(pa);
    if (which == 1) warp_arrive(bar_addr(sb, B_ST_CTX + w), lane);
    TS(10 + 5 * which);
#pragma unroll 1
    for (int jj = 1; jj < n; jj++) {
      ks = take(rdy0);
      const uint32_t vs = take(rdy1);
      prep_qk(sb + ks * SLOT);
      prep_pv(sb + vs * SLOT);
      TSC(23 + 10 * which, jj == 1);
      turn_begin();
      TSC(24 + 10 * which, jj == 1);
      TSC(26 + 10 * which, jj == n - 1);
      wg_fence();
      issue_qk();
      wg_commit();
      issue_pv(jj > 1);
      wg_commit();
      turn_end();
      wg_wait<1>();
      TSC(25 + 10 * which, jj == 1);
      reg_fence(s);
      give(ks);
      if (jj == n - 1 && which == 0) { q_free(); mask_diag(); }
      if (softmax_fast()) {
        wg_wait<0>();
        reg_fence(acc);
        if (softmax([](int, float) {})) rescale();
        to_p(pb);
      }
      peek2();
      wg_wait<0>();
      reg_fence(acc);
      reg_fence(pa);
      give(vs);
#pragma unroll
      for (int i = 0; i < 16; i++) pa[i] = pb[i] | (vs >> 8);
    }
    TS(11 + 5 * which);
    if (which == 0) { give(take(rdy0)); rdy0 = rdy1; }
    {
      const uint32_t vs = take(rdy0);
      prep_pv(sb + vs * SLOT);
      TS(27 + 10 * which);
      turn_begin();
      TS(28 + 10 * which);
      wg_fence();
      issue_pv(n > 1);
      wg_commit();
      turn_end();
      l0 += __shfl_xor_sync(0xffffffffu, l0, 1); l1 += __shfl_xor_sync(0xffffffffu, l1, 1);
      l0 += __shfl_xor_sync(0xffffffffu, l0, 2); l1 += __shfl_xor_sync(0xffffffffu, l1, 2);
      l0 = 1.f / l0; l1 = 1.f / l1;
      peek2();
      if (which == 0) mbar_wait(bar_addr(sb, B_QFULL + w), 0);
      wg_wait<0>();
      reg_fence(acc);
      reg_fence(pa);
      give(vs);
    }
    TS(12 + 5 * which);
    {
      const uint4* dst = at<uint4>(g_qc, (uint32_t)((h * 8 + j) * 2 + w) * 32768 + (fresh_tid() & 127) * 16);
#pragma unroll
      for (int i = 0; i < 16; i++) {
        const int c = (i & 1) ? (i >> 1) + 8 : i >> 1;
        pk[4 * c]     = pack_bf16(acc[8 * c] * l0, acc[8 * c + 1] * l0);
        pk[4 * c + 1] = pack_bf16(acc[8 * c + 2] * l1, acc[8 * c + 3] * l1);
        pk[4 * c + 2] = pack_bf16(acc[8 * c + 4] * l0, acc[8 * c + 5] * l0);
        pk[4 * c + 3] = pack_bf16(acc[8 * c + 6] * l1, acc[8 * c + 7] * l1);
        if (c < CTX_SPLIT)
          asm volatile("{\n.reg .pred p;\nsetp.eq.b32 p, %5, 0;\n@p st.global.v4.u32 [%0], {%1, %2, %3, %4};\n}"
                       :: "l"(dst + c * 128), "r"(pk[4 * c]), "r"(pk[4 * c + 1]), "r"(pk[4 * c + 2]), "r"(pk[4 * c + 3]), "r"(which) : "memory");
      }
    }
    TS(13 + 5 * which);
  }

  {
    float oa[32], ob[32];
#pragma unroll
    for (int i = 0; i < 32; i++) { oa[i] = 0.f; ob[i] = 0.f; }
    uint32_t pk2[64];
#pragma unroll
    for (int i = 0; i < 64; i++) pk2[i] = 0;
    auto stage = [&](float (&o)[32], int ch) {
      reg_fence(o);
      uint32_t q[16];
#pragma unroll
      for (int i = 0; i < 16; i++) q[i] = pack_bf16(o[2 * i], o[2 * i + 1]);
      if (ch >= 4) mbar_wait(bar_addr(sb, B_S2_EMPTY + w * 4 + (ch & 3)), 0);
      store_block(qreg + (ch & 3) * 8192, lane_base16(), q);
    };
    auto hand_over = [&](int ch) {
      fence_async_smem();
      warp_arrive(bar_addr(sb, B_S2_FULL + w * 4 + (ch & 3)), lane);
    };
    uint32_t prev = 0;
    auto half = [&](int f, float (&o)[32], uint32_t (&a)[64], int accumulate) {
      const uint32_t sl = take(rdy0);
      const uint64_t d = desc_mn(sb + sl * SLOT);
      turn_begin();
      TS(40 + f);
      wg_fence();
#pragma unroll
      for (int kk = 0; kk < 16; kk++) {
        wgmma_rs_n64_tb(o, a[4 * kk], a[4 * kk + 1], a[4 * kk + 2], a[4 * kk + 3], desc_add(d, kk * 2048), accumulate | kk);
        if (kk == ARRIVE_KK && (f < 13 || w == 0)) turn_end();
      }
      wg_commit();
      if (f < 13) rdy0 = mbar_test(bar_addr(sb, B_FULL + r.slot), r.phase);
      wg_wait<1>();
      if (f >= 1 && f <= 9) give(prev);
      prev = sl;
    };
    auto load_ctx = [&](auto h0) {
      constexpr int I0 = decltype(h0)::value ? CTX_LD : 0, NL = decltype(h0)::value ? 16 - CTX_LD : CTX_LD;
      const uint4* src = at<const uint4>(g_qc, (uint32_t)(((h ^ 8) * 8 + j) * 2 + (w ^ 1)) * 32768 + (fresh_tid() & 127) * 16);
#pragma unroll
      for (int i = I0; i < I0 + NL; i++) { const uint4 v = __ldcg(src + i * 128); pk2[4 * i] = v.x; pk2[4 * i + 1] = v.y; pk2[4 * i + 2] = v.z; pk2[4 * i + 3] = v.w; }
    };
#pragma unroll 1
    for (int i = 0; i < 3; i++) {
      half(4 * i, oa, pk, 0);
      if (i == 0) { mbar_wait(bar_addr(sb, B_CTXOK + w), 0); load_ctx(Int<0>()); }
      else { hand_over(2 * i - 2); stage(ob, 2 * i - 1); }
      half(4 * i + 1, ob, pk, 0);
      if (i == 0) load_ctx(Int<1>()); else hand_over(2 * i - 1);
      half(4 * i + 2, oa, pk2, 1);
      half(4 * i + 3, ob, pk2, 1);
      stage(oa, 2 * i);
    }
    half(12, oa, pk, 0);
    hand_over(4);
    stage(ob, 5);
    half(13, oa, pk2, 1);
    hand_over(5);
    wg_wait<0>();
    reg_fence(pk);
    reg_fence(pk2);
    stage(oa, 6);
    hand_over(6);
  }
  TS(19);
  TDUMP();
}

namespace ssm {
constexpr int NCH = DA / NCONV;
constexpr int NS = 8, NP = 6;
constexpr uint32_t X0 = 384;
constexpr uint32_t HO = X0 + 4096;
constexpr uint32_t HE = HO + HO_STRIDE + 64;
constexpr uint32_t SSLOT = HE + 4096 + 64;
constexpr uint32_t PART = 264 * 16;
constexpr uint32_t OFF_P = NS * SSLOT, OFF_D = OFF_P + NP * 4 * PART, END = OFF_D + NCH * 4;
static_assert(SSLOT % 128 == 0 && HO % 128 == 0 && END <= BARS, "smem");
enum : uint32_t { B_FULL = 0, B_EMPTY = NS, B_PFULL = 2 * NS, B_PEMPTY = 2 * NS + NP };
__device__ __forceinline__ int channel(int cidx, int i) { return (i >> 4) * 64 + cidx * 16 + (i & 15); }

__device__ __forceinline__ void producer(const Params& p, uint32_t sb, int cidx, unsigned epoch) {
#pragma unroll 1
  for (int i = 0; i < NCH; i++) {
    const int s = i % NS, ch = channel(cidx, i);
    const uint32_t full = bar_addr(sb, B_FULL + s), dst = sb + s * SSLOT;
    mbar_wait(bar_addr(sb, B_EMPTY + s), ((i / NS) & 1) ^ 1);
    mbar_expect_tx(full, 4096 + 4128 + 4096);
    bulk_ld(dst + HE, at<uint8_t>(p.a_ssmk, ch * 4096), 4096, full);
    if ((i & 15) == 0) { flag_wait(flag_at(g_flags.x_ready, i >> 4), NMAIN, epoch); fence_async_all(); }
    bulk_ld(dst + HO, at<uint8_t>(g_ho, ch * HO_STRIDE), 4128, full);
    bulk_ld(dst + X0, at<uint8_t>(g_xs, ch * 4096), 4096, full);
  }
}

__device__ __forceinline__ void reducer(uint32_t sb, int cidx, int rw) {
  uint32_t n = 0;
#pragma unroll 1
  for (int i = rw; i < NCH; i += 3, n++) {
    const uint32_t b = rw + 3 * (n & 1), pb = sb + OFF_P + b * 4 * PART;
    uint8_t* dst = at<uint8_t>(g_xs, channel(cidx, i) * 4096);
    mbar_wait(bar_addr(sb, B_PFULL + b), (n >> 1) & 1);
    asm volatile("cp.async.bulk.global.shared::cta.bulk_group [%0], [%1], 4096;" :: "l"(dst), "r"(pb + 3 * PART) : "memory");
    bulk_commit();
    bulk_wait_all();
#pragma unroll
    for (int k = 2; k >= 0; k--)
      asm volatile("cp.reduce.async.bulk.global.shared::cta.bulk_group.add.noftz.bf16 [%0], [%1], 4096;" :: "l"(dst), "r"(pb + k * PART) : "memory");
    bulk_commit();
    bulk_wait_read();
    mbar_arrive(bar_addr(sb, B_PEMPTY + b));
    if (((i + 3) >> 4) != (i >> 4)) {
      bulk_wait_all();
      fence_async_all();
      flag_signal(flag_at(g_flags.z_ready, i >> 4));
    }
  }
}

__device__ __forceinline__ void mma_warpgroup(uint32_t sb, int w) {
  const int lane = threadIdx.x & 31, g = lane >> 2, c = lane & 3, wq = (threadIdx.x >> 5) & 3;
  const uint32_t aoff = ((g & 1) ? HO + 30 : HE) + (16 * wq - g + 2 * c) * 2;
  const uint32_t poff = OFF_P + wq * PART + (2 * wq + lane) * 16;
  const uint32_t dmask = (wq == 0 && c == (g >> 1)) ? ((g & 1) ? 0xffff0000u : 0xffffu) : 0u;
  float acc[8][16];
  uint32_t fa[16][4];
#pragma unroll
  for (int e = 0; e < 8; e++)
#pragma unroll
    for (int i = 0; i < 16; i++) acc[e][i] = 0.f;
  auto load_a = [&](int m, uint32_t ad) {
    fa[m][0] = lds4(ad + m * 256 + 16); fa[m][1] = lds4(ad + m * 256 + 144); fa[m][2] = lds4(ad + m * 256); fa[m][3] = lds4(ad + m * 256 + 128);
  };
  if (w == 1) named_arrive(PP_BAR, 256);
  mbar_wait(bar_addr(sb, B_FULL + w), 0);
#pragma unroll
  for (int m = 0; m < 16; m++) load_a(m, sb + w * SSLOT + aoff);
  uint32_t dd = lds4(sb + OFF_D + w * 4);
  if (threadIdx.x == 128) { GT(12); PT(10); }
  uint32_t pb = w, pphase = 1;
#pragma unroll 1
  for (int i = w; i < NCH; i += 2) {
    fa[0][2] = badd(fa[0][2], dd & dmask);
    const uint64_t db = (uint64_t)((((sb + (i % NS) * SSLOT + X0 - 16) & 0x3FFFF) >> 4) | (1u << 16)) | ((uint64_t)8 << 32);
    named_sync(PP_BAR + w, 256);
    wg_fence();
#pragma unroll
    for (int r = 0; r < 16; r++) {
      auto mm = [&](int e, int m) { wgmma_rs_n32(acc[e], fa[m][0], fa[m][1], fa[m][2], fa[m][3], db + (int64_t)(32 * e - 16 * m), m != 0); };
      mm(7, r);
      if (r < 14) mm(6, r); else mm(0, r - 14);
      if (r < 12) mm(5, r); else mm(1, r - 12);
      if (r < 10) mm(4, r); else mm(2, r - 10);
      if ((r & 1) == 0) mm(3, r >> 1);
      if (r == CONV_ARRIVE && (i + 1 < NCH)) named_arrive(PP_BAR + (w ^ 1), 256);
    }
    wg_commit();
    const int nx = i + 2 < NCH ? i + 2 : i;
    mbar_wait(bar_addr(sb, B_FULL + nx % NS), (nx / NS) & 1);
    mbar_wait(bar_addr(sb, B_PEMPTY + pb), pphase);
    const uint32_t ad = sb + (nx % NS) * SSLOT + aoff, pa = sb + pb * 4 * PART + poff;
    wg_wait<0>();
#pragma unroll
    for (int e = 0; e < 8; e++) reg_fence(acc[e]);
#pragma unroll
    for (int m = 0; m < 16; m++) reg_fence(fa[m]);
    if (lane == 0) mbar_arrive(bar_addr(sb, B_EMPTY + i % NS));
#pragma unroll
    for (int e = 0; e < 8; e++) {
      if (e < CONV_EARLY) load_a(e, ad);
      uint32_t u[4];
#pragma unroll
      for (int j = 0; j < 4; j++) {
        const int T = 4 * e + j, U = T - 1;
        float lo = acc[e][4 * j], hi = acc[e][4 * j + 1];
        if (T > 0) { lo += acc[U >> 2][4 * (U & 3) + 2]; hi += acc[U >> 2][4 * (U & 3) + 3]; }
        u[j] = pack_bf16(lo, hi);
      }
      asm volatile("stmatrix.sync.aligned.m8n8.x4.trans.shared.b16 [%0], {%1, %2, %3, %4};" :: "r"(pa + e * 512), "r"(u[0]), "r"(u[1]), "r"(u[2]), "r"(u[3]) : "memory");
    }
    dd = lds4(sb + OFF_D + nx * 4);
#pragma unroll
    for (int m = CONV_EARLY; m < CONV_FENCE; m++) load_a(m, ad);
    fence_async_smem();
    warp_arrive(bar_addr(sb, B_PFULL + pb), lane);
#pragma unroll
    for (int m = CONV_FENCE; m < 16; m++) load_a(m, ad);
    pb += 2;
    if (pb >= NP) { pb -= NP; pphase ^= 1; }
  }
  if (threadIdx.x == 128) { PT(9); GT(13); }
}

__device__ __forceinline__ void init(const Params& p, uint32_t sb, int cidx) {
  if (threadIdx.x < NS * 32) {
    const uint32_t s = threadIdx.x >> 5, r = threadIdx.x & 31;
    if (r < 28) sts16(sb + s * SSLOT + (r < 24 ? r * 16 : HE - 64 + (r - 24) * 16), 0, 0, 0, 0);
  } else {
    const uint32_t t = threadIdx.x - NS * 32;
    for (uint32_t u = t; u < NP * 32; u += 128) sts16(sb + OFF_P + (u >> 3) * PART + (u & 7) * 16, 0, 0, 0, 0);
    if (t < NCH) {
      const uint32_t d = (uint32_t)__ldg(reinterpret_cast<const unsigned short*>(p.a_D + channel(cidx, t))) * 0x10001u;
      asm volatile("st.shared.u32 [%0], %1;" :: "r"(sb + OFF_D + t * 4), "r"(d) : "memory");
    }
  }
  if (threadIdx.x == 0) {
    for (int i = 0; i < NS; i++) { mbar_init(bar_addr(sb, B_FULL + i), 1); mbar_init(bar_addr(sb, B_EMPTY + i), 4); }
    for (int i = 0; i < NP; i++) { mbar_init(bar_addr(sb, B_PFULL + i), 4); mbar_init(bar_addr(sb, B_PEMPTY + i), 1); }
  }
  fence_async_smem();
}

__device__ __forceinline__ void side_prepare(const Params& p, int cta, int rd) {
  const int lane = threadIdx.x & 31, t0 = 16 * cta + 8 * (lane & 1);
  if (EXP_SIDE & 16) { if (lane == 0) flag_signal_after_bulk(flag_at(g_flags.x_ready, rd)); return; }
#pragma unroll 1
  for (int ch = 64 * rd + (lane & ~1); ch < 64 * rd + 64; ch += 32) {
    const uint4 sv = __ldg(at<const uint4>(p.a_shift, ch * 8));
    const uint32_t* kp = at<const uint32_t>(p.a_k, (t0 * DA + ch) * 2);
    const uint32_t* vp = at<const uint32_t>(p.a_v, (t0 * DA + ch) * 2);
    uint32_t k0 = 0, k1 = 0, k2 = 0, kk[8], x[8];
    if (t0 > 0) { k0 = __ldg(kp - 3 * (DA / 2)); k1 = __ldg(kp - 2 * (DA / 2)); k2 = __ldg(kp - DA / 2); }
#pragma unroll
    for (int i = 0; i < 8; i++) { kk[i] = __ldg(kp + i * (DA / 2)); x[i] = __ldg(vp + i * (DA / 2)); }
    const uint32_t sh0 = __byte_perm(sv.x, sv.z, 0x5410), sh1 = __byte_perm(sv.x, sv.z, 0x7632);
    const uint32_t sh2 = __byte_perm(sv.y, sv.w, 0x5410), sh3 = __byte_perm(sv.y, sv.w, 0x7632);
#pragma unroll
    for (int i = 0; i < 8; i++) {
      uint32_t ks = bmul(k0, sh3);
      ks = badd(ks, bmul(k1, sh2)); ks = badd(ks, bmul(k2, sh1)); ks = badd(ks, bmul(kk[i], sh0));
      x[i] = bmul(ks, x[i]);
      k0 = k1; k1 = k2; k2 = kk[i];
    }
    uint4* dst = at<uint4>(g_xs, ch * 4096 + t0 * 2);
    if ((EXP_SIDE & 4) && (x[0] ^ x[1] ^ x[2] ^ x[3] ^ x[4] ^ x[5] ^ x[6] ^ x[7]) != 0x12345) continue;
    dst[0]   = make_uint4(__byte_perm(x[7], x[6], 0x5410), __byte_perm(x[5], x[4], 0x5410), __byte_perm(x[3], x[2], 0x5410), __byte_perm(x[1], x[0], 0x5410));
    dst[256] = make_uint4(__byte_perm(x[7], x[6], 0x7632), __byte_perm(x[5], x[4], 0x7632), __byte_perm(x[3], x[2], 0x7632), __byte_perm(x[1], x[0], 0x7632));
  }
  if (!(EXP_SIDE & 8)) {
    const int hc = 64 * rd + (cta >> 1), r0 = (cta & 1) * 128 + lane;
    const uint4* src = at<const uint4>(p.a_ssmk, hc * 4096 + r0 * 16);
    uint4* dst = at<uint4>(g_ho, hc * HO_STRIDE + r0 * 16);
    uint4 w[4];
    uint32_t nx[4];
#pragma unroll
    for (int i = 0; i < 4; i++) { w[i] = __ldg(src + 32 * i); nx[i] = r0 + 32 * i < 255 ? __ldg(reinterpret_cast<const uint32_t*>(src + 32 * i + 1)) : 0u; }
#pragma unroll
    for (int i = 0; i < 4; i++)
      dst[32 * i + 2] = make_uint4(__byte_perm(w[i].x, w[i].y, 0x5432), __byte_perm(w[i].y, w[i].z, 0x5432), __byte_perm(w[i].z, w[i].w, 0x5432), __byte_perm(w[i].w, nx[i], 0x5432));
    const uint32_t h0 = __shfl_sync(0xffffffffu, w[0].x, 0);
    if (r0 < 2) dst[0] = make_uint4(0, 0, 0, r0 ? h0 << 16 : 0u);
  }
  __syncwarp();
  if (lane == 0) { if (EXP_SIDE & 2) flag_signal_after_bulk(flag_at(g_flags.x_ready, rd)); else flag_signal(flag_at(g_flags.x_ready, rd)); }
}
__device__ __forceinline__ void side_finish(const Params& p, int cta, int rd) {
  const int lane = threadIdx.x & 31, t0 = 16 * cta + 8 * (lane & 1);
#pragma unroll 1
  for (int ch = 64 * rd + (lane & ~1); ch < 64 * rd + 64; ch += 32) {
    const uint4* src = at<const uint4>(g_xs, ch * 4096 + t0 * 2);
    const uint32_t* qp = at<const uint32_t>(p.a_q, (t0 * DA + ch) * 2);
    uint32_t* op = at<uint32_t>(p.out, (t0 * OUTW + ch) * 2);
    const uint4 z0 = __ldcg(src), z1 = __ldcg(src + 256);
    uint32_t q[8];
#pragma unroll
    for (int i = 0; i < 8; i++) q[i] = __ldg(qp + i * (DA / 2));
    const uint32_t a[4] = {z0.w, z0.z, z0.y, z0.x}, b[4] = {z1.w, z1.z, z1.y, z1.x};
#pragma unroll
    for (int i = 0; i < 4; i++) {
      op[(2 * i) * (OUTW / 2)]     = bmul(q[2 * i], __byte_perm(a[i], b[i], 0x7632));
      op[(2 * i + 1) * (OUTW / 2)] = bmul(q[2 * i + 1], __byte_perm(a[i], b[i], 0x5410));
    }
  }
}
__device__ __forceinline__ void clear_rows(const Params& p, int qt, int part) {
  const int lane = threadIdx.x & 31;
  if (lane < 28) {
    uint4* z = at<uint4>(p.out, ((qt * 128 + part * 16) * OUTW + DA) * 2 + lane * 16);
#pragma unroll
    for (int i = 0; i < 32; i++) z[(i >> 1) * (OUTW / 8) + (i & 1) * 28] = make_uint4(0, 0, 0, 0);
  }
  __syncwarp();
  if (lane == 0) flag_signal(flag_at(g_flags.zero_ready, qt));
}
__device__ __forceinline__ void side_work(const Params& p, int cta, int qt, unsigned epoch) {
#pragma unroll 1
  for (int rd = -SIDE_AHEAD; rd < 7; rd++) {
    if (rd >= 0) {
      if ((threadIdx.x & 31) == 0) flag_wait_slow(flag_at(g_flags.z_ready, rd), 3 * NCONV, epoch);
      __syncwarp();
    }
    if (rd + SIDE_AHEAD < 7) side_prepare(p, cta, rd + SIDE_AHEAD);
    if (rd >= 0 && !(EXP_SIDE & 1)) side_finish(p, cta, rd);
    if (rd == ZERO_RD) clear_rows(p, qt, (cta >> 3) & 7);
  }
}
}

__global__ void __cluster_dims__(2, 1, 1) __launch_bounds__(NTHREADS, 1)
concat_heads__ssm_conv_h3__compressed_kv_cla__prompt_kernel(const __grid_constant__ Params p) {
  extern __shared__ uint8_t smem_raw[];
  const uint32_t sb = (smem_u32(smem_raw) + 1023) & ~1023u;
  const int warp = __shfl_sync(0xffffffffu, threadIdx.x >> 5, 0);
  const int wg = warp >> 2;
  const int cta = blockIdx.x;
  const bool attn = cta < NMAIN;
  int h, u;
  {
    const int c = cta >> 1;
    if (c < 4) { h = 15; u = c; }
    else if (c < 36) { h = (c - 4) & 7; u = (c - 4) >> 3; }
    else { h = 8 + (c - 36) % 7; u = (c - 36) / 7; }
  }
  const int j = 2 * u + (cta & 1);
  if (!attn) ssm::init(p, sb, cta - NMAIN);
  if (attn && threadIdx.x == 0) {
    for (int i = 0; i < NSLOT; i++) { mbar_init(bar_addr(sb, B_FULL + i), 1); mbar_init(bar_addr(sb, B_EMPTY + i), 16); }
    for (int i = 0; i < 2; i++) {
      mbar_init(bar_addr(sb, B_XFREE + i), 8); mbar_init(bar_addr(sb, B_QFREE + i), 4); mbar_init(bar_addr(sb, B_QFULL + i), 1);
      mbar_init(bar_addr(sb, B_ST_KV + i), 4); mbar_init(bar_addr(sb, B_ST_Q + i), 4); mbar_init(bar_addr(sb, B_ST_CTX + i), 4);
      mbar_init(bar_addr(sb, B_CTXOK + i), 1);
    }
    mbar_init(bar_addr(sb, B_KVOK), 1);
    mbar_init(bar_addr(sb, B_DONE), 2);
    for (int i = 0; i < 8; i++) { mbar_init(bar_addr(sb, B_S2_FULL + i), 4); mbar_init(bar_addr(sb, B_S2_EMPTY + i), 1); }
    asm volatile("fence.mbarrier_init.release.cluster;" ::: "memory");
  }
  if (attn && threadIdx.x == 32) {
    prefetch_map(&p.ckv); prefetch_map(&p.wuk); prefetch_map(&p.wuv); prefetch_map(&p.x); prefetch_map(&p.wq);
    prefetch_map(&p.kv); prefetch_map(&p.o); prefetch_map(&p.wo); prefetch_map(&p.qc);
  }
  __syncwarp();
  asm volatile("barrier.cluster.arrive.release.aligned;" ::: "memory");
  if (attn && threadIdx.x == 0) {
    for (int k = 0; k < EARLY_LD; k++) {
      const uint32_t full = bar_addr(sb, B_FULL + k);
      mbar_expect_tx(full, 49152);
      tma_ld2(sb + QREG + k * 16384, &p.ckv, full, k * 64, p1_rows(h, j, 0) * 128);
      load_tile4(sb + k * SLOT, &p.wuk, full, k * 64, p1_head(h, 0) * 4, j & 1, false, pol(HINTS & 1));
    }
  }
  __syncwarp();
  asm volatile("barrier.cluster.wait.acquire.aligned;" ::: "memory");

  const int lane = threadIdx.x & 31;
  if (wg == 0) {
    if (!attn) {
      asm volatile("setmaxnreg.dec.sync.aligned.u32 40;");
      if (lane == 0) {
        if (warp == 0) { ssm::producer(p, sb, cta - NMAIN, load_epoch()); cta_done(32); }
        else ssm::reducer(sb, cta - NMAIN, warp - 1);
        if (warp == 1) GT(14);
      }
      return;
    }
    asm volatile("setmaxnreg.dec.sync.aligned.u32 40;");
    if (warp == 0) {
      if (lane == 0) producer_main(p, sb, h, j);
    } else if (warp < 3) {
      if (lane == 0) { helper_main(p, sb, h, j, warp - 1); mbar_arrive(bar_addr(sb, B_DONE)); }
    } else {
      ssm::side_work(p, h * 8 + j, q_tile(h, j, 1), load_epoch());
      if (lane == 0) { GT(57); mbar_wait(bar_addr(sb, B_DONE), 0); cta_done(1); }
    }
  } else {
    if (!attn) {
      asm volatile("setmaxnreg.inc.sync.aligned.u32 232;");
      if (p.out != nullptr) ssm::mma_warpgroup(sb, wg - 1);
      return;
    }
    asm volatile("setmaxnreg.inc.sync.aligned.u32 232;");
    if (p.out != nullptr) consumer_main(p, sb, h, j, wg - 1);
  }
}

typedef CUresult (*EncodeTiledFn)(CUtensorMap*, CUtensorMapDataType, cuuint32_t, void*, const cuuint64_t*, const cuuint64_t*,
                                  const cuuint32_t*, const cuuint32_t*, CUtensorMapInterleave, CUtensorMapSwizzle,
                                  CUtensorMapL2promotion, CUtensorMapFloatOOBfill);

void make_map(EncodeTiledFn enc, CUtensorMap* m, const void* ptr, int rank, const uint64_t* dims, const uint64_t* strides, const uint32_t* box) {
  cuuint64_t d[5], s[4]; cuuint32_t b[5], e[5] = {1, 1, 1, 1, 1};
  for (int i = 0; i < rank; i++) { d[i] = dims[i]; b[i] = box[i]; if (i) s[i - 1] = strides[i - 1]; }
  enc(m, CU_TENSOR_MAP_DATA_TYPE_BFLOAT16, rank, const_cast<void*>(ptr), d, s, b, e, CU_TENSOR_MAP_INTERLEAVE_NONE,
      CU_TENSOR_MAP_SWIZZLE_128B, CU_TENSOR_MAP_L2_PROMOTION_L2_256B, CU_TENSOR_MAP_FLOAT_OOB_FILL_NONE);
}
void map2(EncodeTiledFn enc, CUtensorMap* m, const void* ptr, uint64_t cols, uint64_t rows, uint32_t bc, uint32_t br) {
  const uint64_t dims[2] = {cols, rows}, st[1] = {cols * 2}; const uint32_t box[2] = {bc, br};
  make_map(enc, m, ptr, 2, dims, st, box);
}
void map3(EncodeTiledFn enc, CUtensorMap* m, const void* ptr, uint64_t rows, uint32_t nblk) {
  const uint64_t dims[3] = {64, rows, 64}, st[2] = {8192, 128}; const uint32_t box[3] = {64, 64, nblk};
  make_map(enc, m, ptr, 3, dims, st, box);
}

}

extern "C" void kernel_launch(void* const* d_in, const int* in_sizes, int n_in, void* d_out, int out_size) {
  (void)in_sizes; (void)n_in; (void)out_size;
  static EncodeTiledFn enc = nullptr;
  static void *kv_ptr = nullptr, *qc_ptr = nullptr;
  if (!enc) {
    void* fn = nullptr; cudaDriverEntryPointQueryResult qr;
    cudaGetDriverEntryPoint("cuTensorMapEncodeTiled", &fn, cudaEnableDefault, &qr);
    enc = (EncodeTiledFn)fn;
    cudaGetSymbolAddress(&kv_ptr, g_kv);
    cudaGetSymbolAddress(&qc_ptr, g_qc);
    cudaFuncSetAttribute(concat_heads__ssm_conv_h3__compressed_kv_cla__prompt_kernel, cudaFuncAttributeMaxDynamicSharedMemorySize, SMEM_BYTES);
  }
  Params p;
  p.a_q = (const bf16*)d_in[0]; p.a_k = (const bf16*)d_in[1]; p.a_v = (const bf16*)d_in[2];
  p.a_shift = (const bf16*)d_in[3]; p.a_ssmk = (const bf16*)d_in[4]; p.a_D = (const bf16*)d_in[5];
  p.out = (bf16*)d_out;
  map2(enc, &p.x, d_in[6], DM, SEQ, 64, 128);
  map2(enc, &p.ckv, d_in[7], DC, SEQ, 64, 128);
  map3(enc, &p.wq, d_in[8], DM, 2);
  map3(enc, &p.wuk, d_in[9], DC, 2);
  map3(enc, &p.wuv, d_in[10], DC, 2);
  {
    const uint64_t dims[5] = {DM, 2, 4, 4, NH * HD / 32}, st[4] = {DM * 2, 8 * DM * 2, 2 * DM * 2, 32 * DM * 2}; const uint32_t box[5] = {64, 2, 4, 4, 4};
    make_map(enc, &p.wo, d_in[11], 5, dims, st, box);
  }
  {
    const uint64_t dims[3] = {64, 2 * NH * SEQ, 4}, st[2] = {HD * 2, 128}; const uint32_t box[3] = {64, 64, 2};
    make_map(enc, &p.kv, kv_ptr, 3, dims, st, box);
  }
  map2(enc, &p.o, d_out, OUTW, SEQ, 64, 64);
  {
    const uint64_t dims[3] = {64, NMAIN * 128, 4}, st[2] = {HD * 2, 128}; const uint32_t box[3] = {64, 64, 4};
    make_map(enc, &p.qc, qc_ptr, 3, dims, st, box);
  }
  concat_heads__ssm_conv_h3__compressed_kv_cla__prompt_kernel<<<NCTA, NTHREADS, SMEM_BYTES>>>(p);
}
```

```cpp
#include <cuda_runtime.h>
#include <cuda_bf16.h>
#include <cuda.h>
#include <stdint.h>

namespace {

typedef __nv_bfloat16 bf16;

constexpr int SEQ  = 2048;
constexpr int DA   = 448;
constexpr int NH   = 16;
constexpr int HD   = 256;
constexpr int DM   = 448;
constexpr int DC   = 1024;
constexpr int OUTW = DA + DM;
constexpr int NMAIN = 128;
constexpr int NCONV = 4;
constexpr int NCTA  = NMAIN + NCONV;
constexpr int LOG_DONE = 8;
constexpr int NTHREADS = 384;

__device__ __align__(1024) bf16 g_kv[2ull * SEQ * NH * HD];
__device__ __align__(1024) bf16 g_qc[(size_t)NMAIN * 128 * HD];
__device__ __align__(128) uint8_t g_xs[DA * SEQ * 2];
constexpr uint32_t HO_STRIDE = 4224;
__device__ __align__(128) uint8_t g_ho[DA * HO_STRIDE];
struct alignas(128) Flag { unsigned v; unsigned pad[31]; };
struct Flags {
  Flag kv_ready[NH];
  Flag ctx_ready[NMAIN * 2];
  Flag x_ready[7];
  Flag z_ready[7];
  Flag zero_ready[16];
  alignas(128) unsigned long long done;
};
__device__ Flags g_flags;
#define TS(i)
#define TSC(i, cond)
#define TDUMP()
#define GT(i)
#define PT(i)
#define PCLK(var)
#define PACC(acc, t0)

struct alignas(64) Params {
  CUtensorMap ckv;
  CUtensorMap wuk;
  CUtensorMap wuv;
  CUtensorMap x;
  CUtensorMap wq;
  CUtensorMap o;
  CUtensorMap wo;
  const bf16 *a_q, *a_k, *a_v, *a_shift, *a_ssmk, *a_D, *b_x, *b_wq;
  bf16* out;
};

constexpr uint32_t SLOT     = 32768;
constexpr int      NSLOT    = 5;
constexpr uint32_t QREG     = 163840;
constexpr uint32_t BARS     = 229376;
constexpr uint32_t SMEM_BYTES = BARS + 1024 + 1024;
enum : uint32_t {
  B_FULL = 0, B_EMPTY = 5, B_XFREE = 10, B_ST_KV = 12, B_ST_Q = 14, B_ST_CTX = 16, B_KVOK = 18, B_DONE = 19, B_QFREE = 20, B_QFULL = 22,
  B_S2_FULL = 24, B_S2_EMPTY = 32, B_CTXOK = 40, B_PF = 42
};
constexpr int P1_STEPS = 4 * 16 + 2 * 7, P1_XS = P1_STEPS - 2;

template <typename T> __device__ __forceinline__ T* at(const void* base, uint32_t off) {
  asm volatile("" : "+r"(off));
  return reinterpret_cast<T*>(const_cast<char*>(static_cast<const char*>(base)) + off);
}
__device__ __forceinline__ unsigned* flag_at(Flag* f, uint32_t i) { return at<unsigned>(f, i * (uint32_t)sizeof(Flag)); }
__device__ __forceinline__ uint32_t smem_u32(const void* p) { return (uint32_t)__cvta_generic_to_shared(p); }
__device__ __forceinline__ void mbar_init(uint32_t bar, uint32_t cnt) {
  asm volatile("mbarrier.init.shared::cta.b64 [%0], %1;" :: "r"(bar), "r"(cnt) : "memory");
}
__device__ __forceinline__ void mbar_expect_tx(uint32_t bar, uint32_t bytes) {
  asm volatile("mbarrier.arrive.expect_tx.shared::cta.b64 _, [%0], %1;" :: "r"(bar), "r"(bytes) : "memory");
}
__device__ __forceinline__ void mbar_arrive(uint32_t bar) {
  asm volatile("mbarrier.arrive.shared::cta.b64 _, [%0];" :: "r"(bar) : "memory");
}
__device__ __forceinline__ void mbar_arrive_n(uint32_t bar, uint32_t n) {
  asm volatile("mbarrier.arrive.shared::cta.b64 _, [%0], %1;" :: "r"(bar), "r"(n) : "memory");
}
__device__ __forceinline__ void mbar_arrive_remote(uint32_t bar, uint32_t cta) {
  asm volatile("{\n.reg .b32 ra;\nmapa.shared::cluster.u32 ra, %0, %1;\n"
               "mbarrier.arrive.shared::cluster.b64 _, [ra];\n}" :: "r"(bar), "r"(cta) : "memory");
}
__device__ __forceinline__ bool mbar_try(uint32_t bar, uint32_t parity) {
  uint32_t ok;
  asm volatile("{\n.reg .pred p;\nmbarrier.try_wait.parity.shared::cta.b64 p, [%1], %2;\nselp.u32 %0, 1, 0, p;\n}"
               : "=r"(ok) : "r"(bar), "r"(parity) : "memory");
  return ok;
}
__device__ __forceinline__ uint32_t mbar_test(uint32_t bar, uint32_t parity) {
  uint32_t ok;
  asm volatile("{\n.reg .pred p;\nmbarrier.test_wait.parity.shared::cta.b64 p, [%1], %2;\nselp.u32 %0, 1, 0, p;\n}"
               : "=r"(ok) : "r"(bar), "r"(parity) : "memory");
  return ok;
}
constexpr uint32_t SPIN_LIMIT = 1u << 24;
__device__ __forceinline__ void mbar_wait(uint32_t bar, uint32_t parity) {
  if (mbar_try(bar, parity)) return;
  uint32_t n = 0;
  while (!mbar_try(bar, parity)) { if (++n > SPIN_LIMIT) __trap(); }
}
__device__ __forceinline__ void mbar_wait_unless(uint32_t ready, uint32_t bar, uint32_t parity) {
  asm volatile("{\n.reg .pred p;\n.reg .b32 n;\nsetp.ne.u32 p, %0, 0;\nvote.sync.all.pred p, p, 0xffffffff;\n@p bra.uni WDONE;\nmov.u32 n, 0;\n"
               "WLOOP:\nmbarrier.try_wait.parity.shared::cta.b64 p, [%1], %2;\n@p bra.uni WDONE;\nadd.u32 n, n, 1;\nsetp.lt.u32 p, n, %3;\n@p bra.uni WLOOP;\ntrap;\nWDONE:\n}"
               :: "r"(ready), "r"(bar), "r"(parity), "n"(SPIN_LIMIT) : "memory");
}
__device__ __forceinline__ unsigned load_epoch() {
  unsigned long long d; asm volatile("ld.relaxed.gpu.global.u64 %0, [%1];" : "=l"(d) : "l"(&g_flags.done) : "memory");
  return (unsigned)(d >> LOG_DONE);
}
__device__ __forceinline__ void flag_wait(const unsigned* f, unsigned count, unsigned epoch) {
  const unsigned target = (epoch + 1) * count;
  uint32_t n = 0;
  while (true) {
    unsigned v;
    asm volatile("ld.acquire.gpu.global.u32 %0, [%1];" : "=r"(v) : "l"(f) : "memory");
    if ((int)(v - target) >= 0) break;
    if (++n > SPIN_LIMIT) __trap();
    __nanosleep(20);
  }
}
__device__ __forceinline__ void flag_wait_slow(const unsigned* f, unsigned count, unsigned epoch) {
  const unsigned target = (epoch + 1) * count;
  uint32_t n = 0;
  while (true) {
    unsigned v;
    asm volatile("ld.acquire.gpu.global.u32 %0, [%1];" : "=r"(v) : "l"(f) : "memory");
    if ((int)(v - target) >= 0) break;
    if (++n > SPIN_LIMIT / 16) __trap();
    __nanosleep(1000);
  }
}
__device__ __forceinline__ void cta_done(unsigned long long n) { asm volatile("red.relaxed.gpu.global.add.u64 [%0], %1;" :: "l"(&g_flags.done), "l"(n) : "memory"); }
__device__ __forceinline__ void flag_wait_fast(const unsigned* f, unsigned count, unsigned epoch) {
  const unsigned target = (epoch + 1) * count;
  uint32_t n = 0;
  while (true) {
    unsigned v;
    asm volatile("ld.acquire.gpu.global.u32 %0, [%1];" : "=r"(v) : "l"(f) : "memory");
    if ((int)(v - target) >= 0) break;
    if (++n > SPIN_LIMIT) __trap();
  }
}
__device__ __forceinline__ void fence_async_all() { asm volatile("fence.proxy.async;" ::: "memory"); }
__device__ __forceinline__ void flag_signal(unsigned* f) {
  asm volatile("fence.acq_rel.gpu;" ::: "memory");
  asm volatile("red.relaxed.gpu.global.add.u32 [%0], 1;" :: "l"(f) : "memory");
}
__device__ __forceinline__ void flag_signal_after_bulk(unsigned* f) {
  asm volatile("red.relaxed.gpu.global.add.u32 [%0], 1;" :: "l"(f) : "memory");
}
__device__ __forceinline__ void fence_async_smem() { asm volatile("fence.proxy.async.shared::cta;" ::: "memory"); }
#define HINTS 0
constexpr uint64_t POL_NORMAL = 0x1000000000000000ull, POL_FIRST = 0x12F0000000000000ull;
__device__ __forceinline__ constexpr uint64_t pol(bool first) { return first ? POL_FIRST : POL_NORMAL; }
__device__ __forceinline__ void tma_ld2(uint32_t dst, const CUtensorMap* m, uint32_t bar, int c0, int c1, uint64_t pl = POL_NORMAL) {
  asm volatile("cp.async.bulk.tensor.2d.shared::cluster.global.mbarrier::complete_tx::bytes.L2::cache_hint [%0], [%1, {%3, %4}], [%2], %5;"
               :: "r"(dst), "l"(m), "r"(bar), "r"(c0), "r"(c1), "l"(pl) : "memory");
}
__device__ __forceinline__ void tma_ld3(uint32_t dst, const CUtensorMap* m, uint32_t bar, int c0, int c1, int c2, uint64_t pl = POL_NORMAL) {
  asm volatile("cp.async.bulk.tensor.3d.shared::cluster.global.mbarrier::complete_tx::bytes.L2::cache_hint [%0], [%1, {%3, %4, %5}], [%2], %6;"
               :: "r"(dst), "l"(m), "r"(bar), "r"(c0), "r"(c1), "r"(c2), "l"(pl) : "memory");
}
__device__ __forceinline__ void tma_ld3_mc(uint32_t dst, const CUtensorMap* m, uint32_t bar, int c0, int c1, int c2, uint64_t pl = POL_NORMAL) {
  asm volatile("cp.async.bulk.tensor.3d.shared::cluster.global.mbarrier::complete_tx::bytes.multicast::cluster.L2::cache_hint [%0], [%1, {%3, %4, %5}], [%2], %6, %7;"
               :: "r"(dst), "l"(m), "r"(bar), "r"(c0), "r"(c1), "r"(c2), "h"((uint16_t)3), "l"(pl) : "memory");
}
__device__ __forceinline__ void bulk_ld(uint32_t dst, const void* src, uint32_t bytes, uint32_t bar) {
  asm volatile("cp.async.bulk.shared::cluster.global.mbarrier::complete_tx::bytes [%0], [%1], %2, [%3];"
               :: "r"(dst), "l"(src), "r"(bytes), "r"(bar) : "memory");
}
__device__ __forceinline__ void bulk_ld_p(uint32_t dst, const void* src, uint32_t bytes, uint32_t bar, uint64_t pl) {
  asm volatile("cp.async.bulk.shared::cluster.global.mbarrier::complete_tx::bytes.L2::cache_hint [%0], [%1], %2, [%3], %4;"
               :: "r"(dst), "l"(src), "r"(bytes), "r"(bar), "l"(pl) : "memory");
}
__device__ __forceinline__ void bulk_ld_mc(uint32_t dst, const void* src, uint32_t bytes, uint32_t bar, uint64_t pl) {
  asm volatile("cp.async.bulk.shared::cluster.global.mbarrier::complete_tx::bytes.multicast::cluster.L2::cache_hint [%0], [%1], %2, [%3], %4, %5;"
               :: "r"(dst), "l"(src), "r"(bytes), "r"(bar), "h"((uint16_t)3), "l"(pl) : "memory");
}
__device__ __forceinline__ void tma_st3(const CUtensorMap* m, uint32_t src, int c0, int c1, int c2) {
  asm volatile("cp.async.bulk.tensor.3d.global.shared::cta.bulk_group.L2::cache_hint [%0, {%2, %3, %4}], [%1], %5;"
               :: "l"(m), "r"(src), "r"(c0), "r"(c1), "r"(c2), "l"(pol(HINTS & 1024)) : "memory");
}
__device__ __forceinline__ void tma_ld2_mc(uint32_t dst, const CUtensorMap* m, uint32_t bar, int c0, int c1, uint64_t pl = POL_NORMAL) {
  asm volatile("cp.async.bulk.tensor.2d.shared::cluster.global.mbarrier::complete_tx::bytes.multicast::cluster.L2::cache_hint [%0], [%1, {%3, %4}], [%2], %5, %6;"
               :: "r"(dst), "l"(m), "r"(bar), "r"(c0), "r"(c1), "h"((uint16_t)3), "l"(pl) : "memory");
}
__device__ __forceinline__ void tma_ld5_mc(uint32_t dst, const CUtensorMap* m, uint32_t bar, int c0, int c4, uint64_t pl = POL_NORMAL) {
  asm volatile("cp.async.bulk.tensor.5d.shared::cluster.global.mbarrier::complete_tx::bytes.multicast::cluster.L2::cache_hint [%0], [%1, {%3, %7, %7, %7, %4}], [%2], %5, %6;"
               :: "r"(dst), "l"(m), "r"(bar), "r"(c0), "r"(c4), "h"((uint16_t)3), "l"(pl), "r"(0) : "memory");
}
__device__ __forceinline__ void tma_st2(const CUtensorMap* m, uint32_t src, int c0, int c1) {
  asm volatile("cp.async.bulk.tensor.2d.global.shared::cta.bulk_group [%0, {%2, %3}], [%1];"
               :: "l"(m), "r"(src), "r"(c0), "r"(c1) : "memory");
}
__device__ __forceinline__ void tma_red2(const CUtensorMap* m, uint32_t src, int c0, int c1) {
  asm volatile("cp.reduce.async.bulk.tensor.2d.global.shared::cta.add.bulk_group [%0, {%2, %3}], [%1];"
               :: "l"(m), "r"(src), "r"(c0), "r"(c1) : "memory");
}
__device__ __forceinline__ void bulk_commit() { asm volatile("cp.async.bulk.commit_group;" ::: "memory"); }
__device__ __forceinline__ void bulk_wait_read() { asm volatile("cp.async.bulk.wait_group.read 0;" ::: "memory"); }
__device__ __forceinline__ void bulk_wait_all() { asm volatile("cp.async.bulk.wait_group 0;" ::: "memory"); }
__device__ __forceinline__ void prefetch_map(const CUtensorMap* m) { asm volatile("prefetch.tensormap [%0];" :: "l"(m) : "memory"); }
__device__ __forceinline__ void wg_fence() { asm volatile("wgmma.fence.sync.aligned;" ::: "memory"); }
__device__ __forceinline__ void wg_commit() { asm volatile("wgmma.commit_group.sync.aligned;" ::: "memory"); }
template <int N> __device__ __forceinline__ void wg_wait() { asm volatile("wgmma.wait_group.sync.aligned %0;" :: "n"(N) : "memory"); }
template <int N> __device__ __forceinline__ void reg_fence(float (&d)[N]) {
#pragma unroll
  for (int i = 0; i < N; i++) asm volatile("" : "+f"(d[i]) :: "memory");
}
template <int N> __device__ __forceinline__ void reg_fence(uint32_t (&d)[N]) {
#pragma unroll
  for (int i = 0; i < N; i++) asm volatile("" : "+r"(d[i]) :: "memory");
}
__device__ __forceinline__ uint32_t fresh_tid() { uint32_t t; asm volatile("mov.u32 %0, %%tid.x;" : "=r"(t)); return t; }
__device__ __forceinline__ uint32_t lane_base16() {
  const uint32_t t = fresh_tid(), lane = t & 31, wq = (t >> 5) & 3;
  return (16 * wq + (lane & 7) + 8 * ((lane >> 3) & 1)) * 128 + (((lane >> 4) ^ (lane & 7)) << 4);
}
__device__ __forceinline__ void named_sync(int id, int n) { asm volatile("bar.sync %0, %1;" :: "r"(id), "r"(n) : "memory"); }
__device__ __forceinline__ void named_arrive(int id, int n) { asm volatile("bar.arrive %0, %1;" :: "r"(id), "r"(n) : "memory"); }
__device__ __forceinline__ uint32_t pack_bf16(float lo, float hi) {
  uint32_t r; asm("cvt.rn.bf16x2.f32 %0, %1, %2;" : "=r"(r) : "f"(hi), "f"(lo)); return r;
}
__device__ __forceinline__ float ex2(float x) { float y; asm("ex2.approx.ftz.f32 %0, %1;" : "=f"(y) : "f"(x)); return y; }
__device__ __forceinline__ void stsm4(uint32_t addr, uint32_t a, uint32_t b, uint32_t c, uint32_t d) {
  asm volatile("stmatrix.sync.aligned.m8n8.x4.shared.b16 [%0], {%1, %2, %3, %4};" :: "r"(addr), "r"(a), "r"(b), "r"(c), "r"(d) : "memory");
}
__device__ __forceinline__ uint64_t mk_desc(uint32_t addr, uint32_t lbo, uint32_t sbo) {
  return (uint64_t)(((addr & 0x3FFFF) >> 4) | ((lbo >> 4) << 16)) | ((uint64_t)((sbo >> 4) | (1u << 30)) << 32);
}
__device__ __forceinline__ uint64_t desc_k(uint32_t addr)  { return mk_desc(addr, 16, 1024); }
__device__ __forceinline__ uint64_t desc_mn(uint32_t addr) { return mk_desc(addr, 8192, 1024); }
__device__ __forceinline__ uint64_t desc_64(uint32_t addr) { return (uint64_t)(((addr & 0x3FFFF) >> 4) | ((4096u >> 4) << 16)) | ((uint64_t)((512u >> 4) | (2u << 30)) << 32); }
__device__ __forceinline__ uint64_t desc_add(uint64_t d, uint32_t bytes) { return d + (bytes >> 4); }

__device__ __forceinline__ void wgmma_ss_n256_tb(float (&d)[128], uint64_t da, uint64_t db, int sd) {
  asm volatile("{\n.reg .pred p;\nsetp.ne.b32 p, %130, 0;\n"
    "wgmma.mma_async.sync.aligned.m64n256k16.f32.bf16.bf16 "
    "{%0, %1, %2, %3, %4, %5, %6, %7, %8, %9, %10, %11, %12, %13, %14, %15, "
    "%16, %17, %18, %19, %20, %21, %22, %23, %24, %25, %26, %27, %28, %29, %30, %31, "
    "%32, %33, %34, %35, %36, %37, %38, %39, %40, %41, %42, %43, %44, %45, %46, %47, "
    "%48, %49, %50, %51, %52, %53, %54, %55, %56, %57, %58, %59, %60, %61, %62, %63, "
    "%64, %65, %66, %67, %68, %69, %70, %71, %72, %73, %74, %75, %76, %77, %78, %79, "
    "%80, %81, %82, %83, %84, %85, %86, %87, %88, %89, %90, %91, %92, %93, %94, %95, "
    "%96, %97, %98, %99, %100, %101, %102, %103, %104, %105, %106, %107, %108, %109, %110, %111, "
    "%112, %113, %114, %115, %116, %117, %118, %119, %120, %121, %122, %123, %124, %125, %126, %127}, "
    "%128, %129, p, 1, 1, 0, 1;\n}"
    : "+f"(d[0]), "+f"(d[1]), "+f"(d[2]), "+f"(d[3]), "+f"(d[4]), "+f"(d[5]), "+f"(d[6]), "+f"(d[7]),
      "+f"(d[8]), "+f"(d[9]), "+f"(d[10]), "+f"(d[11]), "+f"(d[12]), "+f"(d[13]), "+f"(d[14]), "+f"(d[15]),
      "+f"(d[16]), "+f"(d[17]), "+f"(d[18]), "+f"(d[19]), "+f"(d[20]), "+f"(d[21]), "+f"(d[22]), "+f"(d[23]),
      "+f"(d[24]), "+f"(d[25]), "+f"(d[26]), "+f"(d[27]), "+f"(d[28]), "+f"(d[29]), "+f"(d[30]), "+f"(d[31]),
      "+f"(d[32]), "+f"(d[33]), "+f"(d[34]), "+f"(d[35]), "+f"(d[36]), "+f"(d[37]), "+f"(d[38]), "+f"(d[39]),
      "+f"(d[40]), "+f"(d[41]), "+f"(d[42]), "+f"(d[43]), "+f"(d[44]), "+f"(d[45]), "+f"(d[46]), "+f"(d[47]),
      "+f"(d[48]), "+f"(d[49]), "+f"(d[50]), "+f"(d[51]), "+f"(d[52]), "+f"(d[53]), "+f"(d[54]), "+f"(d[55]),
      "+f"(d[56]), "+f"(d[57]), "+f"(d[58]), "+f"(d[59]), "+f"(d[60]), "+f"(d[61]), "+f"(d[62]), "+f"(d[63]),
      "+f"(d[64]), "+f"(d[65]), "+f"(d[66]), "+f"(d[67]), "+f"(d[68]), "+f"(d[69]), "+f"(d[70]), "+f"(d[71]),
      "+f"(d[72]), "+f"(d[73]), "+f"(d[74]), "+f"(d[75]), "+f"(d[76]), "+f"(d[77]), "+f"(d[78]), "+f"(d[79]),
      "+f"(d[80]), "+f"(d[81]), "+f"(d[82]), "+f"(d[83]), "+f"(d[84]), "+f"(d[85]), "+f"(d[86]), "+f"(d[87]),
      "+f"(d[88]), "+f"(d[89]), "+f"(d[90]), "+f"(d[91]), "+f"(d[92]), "+f"(d[93]), "+f"(d[94]), "+f"(d[95]),
      "+f"(d[96]), "+f"(d[97]), "+f"(d[98]), "+f"(d[99]), "+f"(d[100]), "+f"(d[101]), "+f"(d[102]), "+f"(d[103]),
      "+f"(d[104]), "+f"(d[105]), "+f"(d[106]), "+f"(d[107]), "+f"(d[108]), "+f"(d[109]), "+f"(d[110]), "+f"(d[111]),
      "+f"(d[112]), "+f"(d[113]), "+f"(d[114]), "+f"(d[115]), "+f"(d[116]), "+f"(d[117]), "+f"(d[118]), "+f"(d[119]),
      "+f"(d[120]), "+f"(d[121]), "+f"(d[122]), "+f"(d[123]), "+f"(d[124]), "+f"(d[125]), "+f"(d[126]), "+f"(d[127])
    : "l"(da), "l"(db), "r"(sd));
}
__device__ __forceinline__ void wgmma_ss_n64(float (&d)[32], uint64_t da, uint64_t db, int sd) {
  asm volatile("{\n.reg .pred p;\nsetp.ne.b32 p, %34, 0;\n"
    "wgmma.mma_async.sync.aligned.m64n64k16.f32.bf16.bf16 "
    "{%0, %1, %2, %3, %4, %5, %6, %7, %8, %9, %10, %11, %12, %13, %14, %15, "
    "%16, %17, %18, %19, %20, %21, %22, %23, %24, %25, %26, %27, %28, %29, %30, %31}, "
    "%32, %33, p, 1, 1, 0, 0;\n}"
    : "+f"(d[0]), "+f"(d[1]), "+f"(d[2]), "+f"(d[3]), "+f"(d[4]), "+f"(d[5]), "+f"(d[6]), "+f"(d[7]),
      "+f"(d[8]), "+f"(d[9]), "+f"(d[10]), "+f"(d[11]), "+f"(d[12]), "+f"(d[13]), "+f"(d[14]), "+f"(d[15]),
      "+f"(d[16]), "+f"(d[17]), "+f"(d[18]), "+f"(d[19]), "+f"(d[20]), "+f"(d[21]), "+f"(d[22]), "+f"(d[23]),
      "+f"(d[24]), "+f"(d[25]), "+f"(d[26]), "+f"(d[27]), "+f"(d[28]), "+f"(d[29]), "+f"(d[30]), "+f"(d[31])
    : "l"(da), "l"(db), "r"(sd));
}
__device__ __forceinline__ void wgmma_rs_n256_tb(float (&d)[128], uint32_t a0, uint32_t a1, uint32_t a2, uint32_t a3, uint64_t db, int sd) {
  asm volatile("{\n.reg .pred p;\nsetp.ne.b32 p, %133, 0;\n"
    "wgmma.mma_async.sync.aligned.m64n256k16.f32.bf16.bf16 "
    "{%0, %1, %2, %3, %4, %5, %6, %7, %8, %9, %10, %11, %12, %13, %14, %15, "
    "%16, %17, %18, %19, %20, %21, %22, %23, %24, %25, %26, %27, %28, %29, %30, %31, "
    "%32, %33, %34, %35, %36, %37, %38, %39, %40, %41, %42, %43, %44, %45, %46, %47, "
    "%48, %49, %50, %51, %52, %53, %54, %55, %56, %57, %58, %59, %60, %61, %62, %63, "
    "%64, %65, %66, %67, %68, %69, %70, %71, %72, %73, %74, %75, %76, %77, %78, %79, "
    "%80, %81, %82, %83, %84, %85, %86, %87, %88, %89, %90, %91, %92, %93, %94, %95, "
    "%96, %97, %98, %99, %100, %101, %102, %103, %104, %105, %106, %107, %108, %109, %110, %111, "
    "%112, %113, %114, %115, %116, %117, %118, %119, %120, %121, %122, %123, %124, %125, %126, %127}, "
    "{%128, %129, %130, %131}, %132, p, 1, 1, 1;\n}"
    : "+f"(d[0]), "+f"(d[1]), "+f"(d[2]), "+f"(d[3]), "+f"(d[4]), "+f"(d[5]), "+f"(d[6]), "+f"(d[7]),
      "+f"(d[8]), "+f"(d[9]), "+f"(d[10]), "+f"(d[11]), "+f"(d[12]), "+f"(d[13]), "+f"(d[14]), "+f"(d[15]),
      "+f"(d[16]), "+f"(d[17]), "+f"(d[18]), "+f"(d[19]), "+f"(d[20]), "+f"(d[21]), "+f"(d[22]), "+f"(d[23]),
      "+f"(d[24]), "+f"(d[25]), "+f"(d[26]), "+f"(d[27]), "+f"(d[28]), "+f"(d[29]), "+f"(d[30]), "+f"(d[31]),
      "+f"(d[32]), "+f"(d[33]), "+f"(d[34]), "+f"(d[35]), "+f"(d[36]), "+f"(d[37]), "+f"(d[38]), "+f"(d[39]),
      "+f"(d[40]), "+f"(d[41]), "+f"(d[42]), "+f"(d[43]), "+f"(d[44]), "+f"(d[45]), "+f"(d[46]), "+f"(d[47]),
      "+f"(d[48]), "+f"(d[49]), "+f"(d[50]), "+f"(d[51]), "+f"(d[52]), "+f"(d[53]), "+f"(d[54]), "+f"(d[55]),
      "+f"(d[56]), "+f"(d[57]), "+f"(d[58]), "+f"(d[59]), "+f"(d[60]), "+f"(d[61]), "+f"(d[62]), "+f"(d[63]),
      "+f"(d[64]), "+f"(d[65]), "+f"(d[66]), "+f"(d[67]), "+f"(d[68]), "+f"(d[69]), "+f"(d[70]), "+f"(d[71]),
      "+f"(d[72]), "+f"(d[73]), "+f"(d[74]), "+f"(d[75]), "+f"(d[76]), "+f"(d[77]), "+f"(d[78]), "+f"(d[79]),
      "+f"(d[80]), "+f"(d[81]), "+f"(d[82]), "+f"(d[83]), "+f"(d[84]), "+f"(d[85]), "+f"(d[86]), "+f"(d[87]),
      "+f"(d[88]), "+f"(d[89]), "+f"(d[90]), "+f"(d[91]), "+f"(d[92]), "+f"(d[93]), "+f"(d[94]), "+f"(d[95]),
      "+f"(d[96]), "+f"(d[97]), "+f"(d[98]), "+f"(d[99]), "+f"(d[100]), "+f"(d[101]), "+f"(d[102]), "+f"(d[103]),
      "+f"(d[104]), "+f"(d[105]), "+f"(d[106]), "+f"(d[107]), "+f"(d[108]), "+f"(d[109]), "+f"(d[110]), "+f"(d[111]),
      "+f"(d[112]), "+f"(d[113]), "+f"(d[114]), "+f"(d[115]), "+f"(d[116]), "+f"(d[117]), "+f"(d[118]), "+f"(d[119]),
      "+f"(d[120]), "+f"(d[121]), "+f"(d[122]), "+f"(d[123]), "+f"(d[124]), "+f"(d[125]), "+f"(d[126]), "+f"(d[127])
    : "r"(a0), "r"(a1), "r"(a2), "r"(a3), "l"(db), "r"(sd));
}
__device__ __forceinline__ void wgmma_rs_n64_tb(float (&d)[32], uint32_t a0, uint32_t a1, uint32_t a2, uint32_t a3, uint64_t db, int sd) {
  asm volatile("{\n.reg .pred p;\nsetp.ne.b32 p, %37, 0;\n"
    "wgmma.mma_async.sync.aligned.m64n64k16.f32.bf16.bf16 "
    "{%0, %1, %2, %3, %4, %5, %6, %7, %8, %9, %10, %11, %12, %13, %14, %15, "
    "%16, %17, %18, %19, %20, %21, %22, %23, %24, %25, %26, %27, %28, %29, %30, %31}, "
    "{%32, %33, %34, %35}, %36, p, 1, 1, 1;\n}"
    : "+f"(d[0]), "+f"(d[1]), "+f"(d[2]), "+f"(d[3]), "+f"(d[4]), "+f"(d[5]), "+f"(d[6]), "+f"(d[7]),
      "+f"(d[8]), "+f"(d[9]), "+f"(d[10]), "+f"(d[11]), "+f"(d[12]), "+f"(d[13]), "+f"(d[14]), "+f"(d[15]),
      "+f"(d[16]), "+f"(d[17]), "+f"(d[18]), "+f"(d[19]), "+f"(d[20]), "+f"(d[21]), "+f"(d[22]), "+f"(d[23]),
      "+f"(d[24]), "+f"(d[25]), "+f"(d[26]), "+f"(d[27]), "+f"(d[28]), "+f"(d[29]), "+f"(d[30]), "+f"(d[31])
    : "r"(a0), "r"(a1), "r"(a2), "r"(a3), "l"(db), "r"(sd));
}
__device__ __forceinline__ void wgmma_rs_n32(float (&d)[16], uint32_t a0, uint32_t a1, uint32_t a2, uint32_t a3, uint64_t db, int sd) {
  asm volatile("{\n.reg .pred p;\nsetp.ne.b32 p, %21, 0;\n"
    "wgmma.mma_async.sync.aligned.m64n32k16.f32.bf16.bf16 "
    "{%0, %1, %2, %3, %4, %5, %6, %7, %8, %9, %10, %11, %12, %13, %14, %15}, "
    "{%16, %17, %18, %19}, %20, p, 1, 1, 0;\n}"
    : "+f"(d[0]), "+f"(d[1]), "+f"(d[2]), "+f"(d[3]), "+f"(d[4]), "+f"(d[5]), "+f"(d[6]), "+f"(d[7]),
      "+f"(d[8]), "+f"(d[9]), "+f"(d[10]), "+f"(d[11]), "+f"(d[12]), "+f"(d[13]), "+f"(d[14]), "+f"(d[15])
    : "r"(a0), "r"(a1), "r"(a2), "r"(a3), "l"(db), "r"(sd));
}
__device__ __forceinline__ void wgmma_rs_n64(float (&d)[32], uint32_t a0, uint32_t a1, uint32_t a2, uint32_t a3, uint64_t db, int sd) {
  asm volatile("{\n.reg .pred p;\nsetp.ne.b32 p, %37, 0;\n"
    "wgmma.mma_async.sync.aligned.m64n64k16.f32.bf16.bf16 "
    "{%0, %1, %2, %3, %4, %5, %6, %7, %8, %9, %10, %11, %12, %13, %14, %15, "
    "%16, %17, %18, %19, %20, %21, %22, %23, %24, %25, %26, %27, %28, %29, %30, %31}, "
    "{%32, %33, %34, %35}, %36, p, 1, 1, 0;\n}"
    : "+f"(d[0]), "+f"(d[1]), "+f"(d[2]), "+f"(d[3]), "+f"(d[4]), "+f"(d[5]), "+f"(d[6]), "+f"(d[7]),
      "+f"(d[8]), "+f"(d[9]), "+f"(d[10]), "+f"(d[11]), "+f"(d[12]), "+f"(d[13]), "+f"(d[14]), "+f"(d[15]),
      "+f"(d[16]), "+f"(d[17]), "+f"(d[18]), "+f"(d[19]), "+f"(d[20]), "+f"(d[21]), "+f"(d[22]), "+f"(d[23]),
      "+f"(d[24]), "+f"(d[25]), "+f"(d[26]), "+f"(d[27]), "+f"(d[28]), "+f"(d[29]), "+f"(d[30]), "+f"(d[31])
    : "r"(a0), "r"(a1), "r"(a2), "r"(a3), "l"(db), "r"(sd));
}

__device__ __forceinline__ uint4 lds16(uint32_t a) {
  uint4 v; asm volatile("ld.shared.v4.u32 {%0, %1, %2, %3}, [%4];" : "=r"(v.x), "=r"(v.y), "=r"(v.z), "=r"(v.w) : "r"(a) : "memory"); return v;
}
__device__ __forceinline__ void sts16(uint32_t a, uint32_t x, uint32_t y, uint32_t z, uint32_t w) {
  asm volatile("st.shared.v4.u32 [%0], {%1, %2, %3, %4};" :: "r"(a), "r"(x), "r"(y), "r"(z), "r"(w) : "memory");
}
__device__ __forceinline__ uint32_t lds4(uint32_t a) { uint32_t v; asm volatile("ld.shared.u32 %0, [%1];" : "=r"(v) : "r"(a) : "memory"); return v; }
__device__ __forceinline__ uint32_t lds4v(uint32_t a) { uint32_t v; asm volatile("ld.volatile.shared.u32 %0, [%1];" : "=r"(v) : "r"(a) : "memory"); return v; }
__device__ __forceinline__ uint32_t bmul(uint32_t a, uint32_t b) { uint32_t r; asm("mul.rn.bf16x2 %0, %1, %2;" : "=r"(r) : "r"(a), "r"(b)); return r; }
__device__ __forceinline__ uint32_t badd(uint32_t a, uint32_t b) { uint32_t r; asm("add.rn.bf16x2 %0, %1, %2;" : "=r"(r) : "r"(a), "r"(b)); return r; }

__device__ __forceinline__ void ldsm4(uint32_t (&r)[4], uint32_t a) {
  asm volatile("ldmatrix.sync.aligned.m8n8.x4.shared.b16 {%0, %1, %2, %3}, [%4];" : "=r"(r[0]), "=r"(r[1]), "=r"(r[2]), "=r"(r[3]) : "r"(a) : "memory");
}
__device__ __forceinline__ uint32_t transpose8(uint32_t a) { uint32_t d; asm volatile("movmatrix.sync.aligned.m8n8.trans.b16 %0, %1;" : "=r"(d) : "r"(a)); return d; }

__device__ __forceinline__ void mma16816(float (&d)[4], const uint32_t (&a)[4], uint32_t b0, uint32_t b1) {
  asm volatile("mma.sync.aligned.m16n8k16.row.col.f32.bf16.bf16.f32 {%0, %1, %2, %3}, {%4, %5, %6, %7}, {%8, %9}, {%0, %1, %2, %3};"
               : "+f"(d[0]), "+f"(d[1]), "+f"(d[2]), "+f"(d[3]) : "r"(a[0]), "r"(a[1]), "r"(a[2]), "r"(a[3]), "r"(b0), "r"(b1));
}

#define EXP_SIDE 0
#define SIDE_AHEAD 3
#define ZERO_RD 4
#define CTX_SPLIT 8
#define CONV_EARLY 8
#define CONV_FENCE 12
#define CTX_LD 16
#define PF_Q 0
#define HOOK_DEP s[4 * jj]
#define PEEK_JJ 7
#define PF_GAP 500
#define PF_CTX 2
#define STG_PAT 0
#define CONV_ARRIVE 13
#define ARRIVE_KK 12
#define SIDE_DELAY_NS 4000
#define KVH(h) (h)
#define HEAD_MAP 1
#define EARLY_LD 3
constexpr int RED_BAR = 6;
constexpr int CV_BAR = 5;
constexpr int PP_BAR = 3;
template <int V> struct Int { static constexpr int value = V; };
struct Ring {
  uint32_t slot, phase;
  __device__ __forceinline__ void next() { if (++slot == NSLOT) { slot = 0; phase ^= 1; } }
};
__device__ __forceinline__ uint32_t bar_addr(uint32_t sb, uint32_t i) { return sb + BARS + 8 * i; }

__device__ __forceinline__ int q_tile(int h, int j, int which) { return ((h < 8) == (which == 0)) ? 15 - j : j; }

__device__ __forceinline__ int att_head(int h, int which) { return h; }
__device__ __forceinline__ int p1_head(int h, int t) { return h; }
__device__ __forceinline__ int p1_isv(int t) { return t >> 1; }
__device__ __forceinline__ int p1_rows(int h, int j, int t) { return 2 * j + (t & 1); }
#define KV_FLAG(h) (h)
#define KV_COUNT 16

__device__ __forceinline__ void load_tile4(uint32_t dst, const CUtensorMap* m, uint32_t full, int row, int blk0, int rank, bool shared, uint64_t pl = POL_NORMAL) {
  if (shared) {
    tma_ld3_mc(dst + rank * 16384, m, full, 0, row, blk0 + 2 * rank, pl);
  } else {
    tma_ld3(dst, m, full, 0, row, blk0, pl);
    tma_ld3(dst + 16384, m, full, 0, row, blk0 + 2, pl);
  }
}
__device__ __forceinline__ void producer_main(const Params& p, uint32_t sb, int h, int j) {
  const int rank = j & 1;
  Ring r{EARLY_LD, 0};
  auto wait_slot = [&]() { mbar_wait(bar_addr(sb, B_EMPTY + r.slot), r.phase ^ 1); };
  auto load_a = [&](int it, uint32_t dst, uint32_t full) {
    if (it < 64) tma_ld2(dst, &p.ckv, full, (it & 15) * 64, p1_rows(h, j, it >> 4) * 128, pol((HINTS & 2) && it >= 48));
    else tma_ld2(dst, &p.x, full, (it < 71 ? it - 64 : it - 71) * 64, q_tile(h, j, it < 71) * 128, pol(HINTS & 64));
  };
  uint32_t prev = 0;
#pragma unroll 1
  for (int it = EARLY_LD; it < P1_STEPS; it++) {
    wait_slot();
    if (it > EARLY_LD && it <= P1_XS) load_a(it - 1, sb + QREG + ((it - 1) & 3) * 16384, prev);
    const uint32_t full = bar_addr(sb, B_FULL + r.slot), dst = sb + r.slot * SLOT;
    mbar_expect_tx(full, it < P1_XS ? 49152 : 32768);
    if (it < 64) load_tile4(dst, p1_isv(it >> 4) ? &p.wuv : &p.wuk, full, (it & 15) * 64, p1_head(h, it >> 4) * 4, rank, true, pol(HINTS & 1));
    else load_tile4(dst, &p.wq, full, (it < 71 ? it - 64 : it - 71) * 64, att_head(h, it < 71) * 4, rank, true, pol(HINTS & 4));
    prev = full;
    r.next();
    if (PF_Q && it == PF_Q) mbar_arrive(bar_addr(sb, B_PF));
    if (it == P1_XS) {
      wait_slot();
      const uint32_t f2 = bar_addr(sb, B_FULL + r.slot);
      mbar_expect_tx(f2, 32768);
      load_a(P1_XS, sb + r.slot * SLOT, f2);
      load_a(P1_XS + 1, sb + r.slot * SLOT + 16384, f2);
      r.next();
    }
  }
  mbar_wait(bar_addr(sb, B_KVOK), 0);
  const int qa = q_tile(h, j, 0), na = 2 * qa + 2, own = 2 * (qa & ~1) + 2;
#pragma unroll 1
  for (int f = 0; f < 68; f++) {
    const bool isK = (f == 0) || ((f & 1) && f < 67);
    const int i = isK ? (f + 1) >> 1 : (f - 1) >> 1, which = i >= na;
    wait_slot();
    const uint32_t full = bar_addr(sb, B_FULL + r.slot);
    mbar_expect_tx(full, 32768);
    const uint32_t src = (uint32_t)(((isK ? 0 : NH) + KVH(att_head(h, which))) * 32 + (which ? 33 - i : i)) * 32768;
    const uint64_t pl = pol(which ? (HINTS & 32) : (HINTS & 8));
    if ((i & ~1) != own) bulk_ld_mc(sb + r.slot * SLOT + rank * 16384, at<uint8_t>(g_kv, src + rank * 16384), 16384, full, pl);
    else bulk_ld_p(sb + r.slot * SLOT, at<uint8_t>(g_kv, src), 32768, full, pl);
    r.next();
  }
#pragma unroll 1
  for (int f = 0; f < 14; f++) {
    const int ch = f < 12 ? 2 * (f >> 2) + (f & 1) : 6, par = f < 12 ? (f >> 1) & 1 : f & 1;
    wait_slot();
    const uint32_t full = bar_addr(sb, B_FULL + r.slot);
    mbar_expect_tx(full, 32768);
    tma_ld5_mc(sb + r.slot * SLOT + rank * 16384, &p.wo, full, ch * 64, (par ? att_head(h ^ 8, 0) : att_head(h, 1)) * 8 + rank * 4, pol(HINTS & 16));
    r.next();
  }
}

__device__ __forceinline__ void helper_main(const Params& p, uint32_t sb, int h, int j, int w) {
  const unsigned epoch = load_epoch();
  const int cta = h * 8 + j, qb = q_tile(h, j, 1);
  const uint32_t qreg = sb + QREG + w * 32768, qfull = bar_addr(sb, B_QFULL + w);
  mbar_wait(bar_addr(sb, B_ST_KV + w), 0);
  flag_signal(flag_at(g_flags.kv_ready, KV_FLAG(h)));
  if (w == 0) {
    flag_wait(flag_at(g_flags.kv_ready, KV_FLAG(h)), KV_COUNT, epoch);
    fence_async_all();
    mbar_arrive(bar_addr(sb, B_KVOK));
  }
  mbar_wait(bar_addr(sb, B_ST_Q + w), 0);
  asm volatile("fence.acq_rel.gpu;" ::: "memory");
  fence_async_all();
  mbar_wait(bar_addr(sb, B_QFREE + w), 0);
  mbar_expect_tx(qfull, 32768);
  bulk_ld(qreg, at<uint8_t>(g_qc, (cta * 2 + w) * 32768), 32768, qfull);
  auto publish = [&]() { mbar_wait(bar_addr(sb, B_ST_CTX + w), 0); flag_signal(flag_at(g_flags.ctx_ready, cta * 2 + w)); };
  if (qb >= 8) publish();
  flag_wait(flag_at(g_flags.ctx_ready, (cta ^ 64) * 2 + (w ^ 1)), 1, epoch);
  mbar_arrive(bar_addr(sb, B_CTXOK + w));
  if (qb < 8) publish();
  flag_wait(flag_at(g_flags.zero_ready, qb), 8, epoch);
  fence_async_all();
#pragma unroll 1
  for (int ch = 0; ch < 7; ch++) {
    mbar_wait(bar_addr(sb, B_S2_FULL + w * 4 + (ch & 3)), ch >> 2);
    tma_red2(&p.o, qreg + (ch & 3) * 8192, DA + ch * 64, qb * 128 + (w ^ 1) * 64);
    bulk_commit();
    if (ch < 3) { bulk_wait_read(); mbar_arrive(bar_addr(sb, B_S2_EMPTY + w * 4 + ch)); }
  }
  bulk_wait_read();
  GT(48 + w);
}

__device__ __forceinline__ void store_block(uint32_t base, uint32_t lanebase, const uint32_t (&pk)[16]) {
#pragma unroll
  for (int J = 0; J < 8; J += 2) stsm4(base + (lanebase ^ (J << 4)), pk[2 * J], pk[2 * J + 1], pk[2 * J + 2], pk[2 * J + 3]);
}
__device__ __forceinline__ void pack_chunks(uint32_t (&pk)[64], const float (&acc)[128]) {
#pragma unroll
  for (int i = 0; i < 64; i++) { const int e = 16 * (i >> 3) + 4 * (i & 3) + 2 * ((i >> 2) & 1); pk[i] = pack_bf16(acc[e], acc[e + 1]); }
}
__device__ __forceinline__ uint32_t chunk_off() { const uint32_t t = fresh_tid(); return (t & 96) * 32 + (t & 28) * 16 + (((t ^ (t >> 3)) & 3) << 4); }
__device__ __forceinline__ void warp_arrive(uint32_t bar, int lane) { __syncwarp(); if (lane == 0) mbar_arrive(bar); }

__device__ __forceinline__ void consumer_main(const Params& p, uint32_t sb, int h, int j, int w, int wq) {
  const int lane = threadIdx.x & 31;
  const int rank = j & 1;

  auto turn_begin = [&]() { named_sync(PP_BAR + w, 256); };
  auto turn_end = [&]() { named_arrive(PP_BAR + (w ^ 1), 256); };
  if (w == 1) named_arrive(PP_BAR, 256);
  Ring r{0, 0};
  auto take = [&](uint32_t ready = 0) { const uint32_t sl = r.slot; mbar_wait_unless(ready, bar_addr(sb, B_FULL + sl), r.phase); r.next(); return sl; };
  uint32_t rdy0 = 0, rdy1 = 0;
  auto peek2 = [&]() { Ring q = r; rdy0 = mbar_test(bar_addr(sb, B_FULL + q.slot), q.phase); q.next(); rdy1 = mbar_test(bar_addr(sb, B_FULL + q.slot), q.phase); };
  auto give = [&](uint32_t sl) { if (lane < 2) mbar_arrive_remote(bar_addr(sb, B_EMPTY + sl), rank ^ lane); };
  float acc[128];
#pragma unroll
  for (int i = 0; i < 128; i++) acc[i] = 0.f;
  uint32_t pk[64];
#pragma unroll
  for (int i = 0; i < 64; i++) pk[i] = 0;
  TS(0);
  const uint32_t qreg = sb + QREG + w * 32768;
  {
    uint32_t xs = 0, prev = 0;
    uint4* row = nullptr;
    int it = 0;
#pragma unroll 1
    for (int t = 0; t < 6; t++) {
      const int nk = t < 4 ? 16 : 7;
#pragma unroll 1
      for (int k = 0; k < nk; k++, it++) {
        const uint32_t ws = take(rdy0);
        TSC(1, it == 0);
        if (it == P1_XS) xs = take();
        const uint32_t aa = (it < P1_XS ? QREG + (it & 3) * 16384 : xs * SLOT + (it - P1_XS) * 16384) + (w ^ (t == 4)) * 8192;
        const uint64_t da = desc_k(sb + aa), db = desc_mn(sb + ws * SLOT);
        turn_begin();
        wg_fence();
#pragma unroll
        for (int kk = 0; kk < 4; kk++) wgmma_ss_n256_tb(acc, desc_add(da, kk * 32), desc_add(db, kk * 2048), (k | kk) != 0);
        wg_commit();
        turn_end();
        rdy0 = mbar_test(bar_addr(sb, B_FULL + r.slot), r.phase);
        wg_wait<1>();
        if (k > 0) give(prev);
        prev = ws;
        if (it >= P1_XS - 2 && !(it & 1) && lane == 0) mbar_arrive(bar_addr(sb, B_XFREE + ((it - (P1_XS - 2)) >> 1)));
        if (t > 0) {
          const int c0 = t < 4 ? k : 3 * k, c1 = t < 4 ? k + 1 : 3 * k + 3;
#pragma unroll
          for (int i = 0; i < 16; i++)
            if (i >= c0 && i < c1) row[(i >> 1) * 256 + (i & 1) * 32] = make_uint4(pk[4 * i], pk[4 * i + 1], pk[4 * i + 2], pk[4 * i + 3]);
          if (t >= 4 && k == (STG_PAT == 1 ? 6 : 5)) warp_arrive(bar_addr(sb, (t == 4 ? B_ST_KV : B_ST_Q) + w), lane);
        }
      }
      if (t == 5) mbar_wait(bar_addr(sb, B_XFREE + w), 0);
      wg_wait<0>();
      reg_fence(acc);
      give(prev);
      pack_chunks(pk, acc);
      row = at<uint4>(t < 4 ? (const void*)g_kv : (const void*)g_qc, chunk_off() +
                      (t < 4 ? (uint32_t)((p1_isv(t) * NH + KVH(p1_head(h, t))) * SEQ + p1_rows(h, j, t) * 128 + w * 64) * 512 : (uint32_t)((h * 8 + j) * 2 + w) * 32768));
      TS(2 + t);
    }
    give(xs);
    const uint32_t qa = qreg + chunk_off();
#pragma unroll
    for (int i = 0; i < 16; i++) sts16(qa + (i >> 1) * 4096 + (i & 1) * 512, pk[4 * i], pk[4 * i + 1], pk[4 * i + 2], pk[4 * i + 3]);
    fence_async_smem();
  }
  TS(8);

  constexpr float SC = 0.0625f * 1.4426950408889634f;
#pragma unroll 1
  for (int which = 0; which < 2; which++) {
    float s[32];
#pragma unroll
    for (int i = 0; i < 32; i++) s[i] = 0.f;
    uint32_t pa[16], pb[16];
    float m0 = -INFINITY, m1 = -INFINITY, l0 = 0.f, l1 = 0.f;
    const uint64_t dq = desc_64(qreg);
    uint64_t dk = 0, dqq = 0, dv = 0;
    auto prep_qk = [&](uint32_t kaddr) { dk = desc_64(kaddr); dqq = dq + (kaddr >> 31); asm volatile("" : "+l"(dk), "+l"(dqq)); };
    auto prep_pv = [&](uint32_t vaddr) { dv = desc_64(vaddr); asm volatile("" : "+l"(dv)); };
    auto issue_qk = [&]() {
#pragma unroll
      for (int kk = 0; kk < 16; kk++)
        wgmma_ss_n64(s, desc_add(dqq, (kk >> 1) * 4096 + (kk & 1) * 32), desc_add(dk, (kk >> 1) * 4096 + (kk & 1) * 32), kk != 0);
    };
    auto issue_pv = [&](int accumulate) {
#pragma unroll
      for (int kk = 0; kk < 4; kk++)
        wgmma_rs_n256_tb(acc, pa[4 * kk], pa[4 * kk + 1], pa[4 * kk + 2], pa[4 * kk + 3], desc_add(dv, kk * 1024), accumulate | kk);
    };
    auto mask_diag = [&]() {
      const int d = 16 * wq + (lane >> 2) - 2 * (lane & 3);
#pragma unroll
      for (int jj = 0; jj < 8; jj++) {
        if (8 * jj > d)     { s[4 * jj] = -INFINITY;     if (jj < 7) s[4 * jj + 6] = -INFINITY; }
        if (8 * jj + 1 > d) { s[4 * jj + 1] = -INFINITY; if (jj < 7) s[4 * jj + 7] = -INFINITY; }
      }
    };
    float a0, a1;
    auto softmax = [&](auto hook) -> bool {
      float x0 = fmaxf(s[0], s[1]), x1 = fmaxf(s[2], s[3]);
#pragma unroll
      for (int jj = 1; jj < 8; jj++) {
        x0 = fmaxf(x0, fmaxf(s[4 * jj], s[4 * jj + 1]));
        x1 = fmaxf(x1, fmaxf(s[4 * jj + 2], s[4 * jj + 3]));
      }
      x0 = fmaxf(x0, __shfl_xor_sync(0xffffffffu, x0, 1));
      x1 = fmaxf(x1, __shfl_xor_sync(0xffffffffu, x1, 1));
      x0 = fmaxf(x0, __shfl_xor_sync(0xffffffffu, x0, 2));
      x1 = fmaxf(x1, __shfl_xor_sync(0xffffffffu, x1, 2));
      const bool grow = __any_sync(0xffffffffu, fmaxf(x0 - m0, x1 - m1) * SC > 8.f);
      if (grow) {
        x0 = fmaxf(x0, m0); x1 = fmaxf(x1, m1);
        a0 = ex2((m0 - x0) * SC); a1 = ex2((m1 - x1) * SC);
        m0 = x0; m1 = x1;
        l0 *= a0; l1 *= a1;
      }
      const float b0 = -m0 * SC, b1 = -m1 * SC;
      float t0 = 0.f, t1 = 0.f, t2 = 0.f, t3 = 0.f;
#pragma unroll
      for (int jj = 0; jj < 8; jj++) {
        s[4 * jj]     = ex2(fmaf(s[4 * jj], SC, b0));
        s[4 * jj + 1] = ex2(fmaf(s[4 * jj + 1], SC, b0));
        s[4 * jj + 2] = ex2(fmaf(s[4 * jj + 2], SC, b1));
        s[4 * jj + 3] = ex2(fmaf(s[4 * jj + 3], SC, b1));
        t0 += s[4 * jj]; t1 += s[4 * jj + 1]; t2 += s[4 * jj + 2]; t3 += s[4 * jj + 3];
        hook(jj, HOOK_DEP);
      }
      l0 += t0 + t1; l1 += t2 + t3;
      return grow;
    };
    auto softmax_fast = [&]() -> bool {
      const float b0 = -m0 * SC, b1 = -m1 * SC;
      float t0 = 0.f, t1 = 0.f, t2 = 0.f, t3 = 0.f;
#pragma unroll
      for (int jj = 0; jj < 8; jj++) {
        const float e0 = ex2(fmaf(s[4 * jj], SC, b0)), e1 = ex2(fmaf(s[4 * jj + 1], SC, b0));
        const float e2 = ex2(fmaf(s[4 * jj + 2], SC, b1)), e3 = ex2(fmaf(s[4 * jj + 3], SC, b1));
        pb[2 * jj] = pack_bf16(e0, e1); pb[2 * jj + 1] = pack_bf16(e2, e3);
        if (jj == 0) { t0 = e0; t1 = e1; t2 = e2; t3 = e3; } else { t0 += e0; t1 += e1; t2 += e2; t3 += e3; }
      }
      t0 += t1; t2 += t3;
      const bool redo = __any_sync(0xffffffffu, !(t0 + t2 <= 16777216.f));
      if (!redo) { l0 += t0; l1 += t2; }
      return redo;
    };
    auto rescale = [&]() {
#pragma unroll
      for (int i = 0; i < 32; i++) { acc[4 * i] *= a0; acc[4 * i + 1] *= a0; acc[4 * i + 2] *= a1; acc[4 * i + 3] *= a1; }
    };
    auto to_p = [&](uint32_t (&pp)[16]) {
#pragma unroll
      for (int i = 0; i < 16; i++) pp[i] = pack_bf16(s[2 * i], s[2 * i + 1]);
    };
    auto q_free = [&]() { if (lane == 0) mbar_arrive(bar_addr(sb, B_QFREE + w)); };

    const int n = 2 * q_tile(h, j, which) + 1 + (w ^ which);
    uint32_t ks = take(rdy0);
    TS(9 + 5 * which);
    prep_qk(sb + ks * SLOT);
    turn_begin();
    TS(20 + 10 * which);
    wg_fence();
    issue_qk();
    wg_commit();
    turn_end();
    if (which == 1) give(take(rdy1));
    TS(22 + 10 * which);
    wg_wait<0>();
    TS(21 + 10 * which);
    reg_fence(s);
    give(ks);
    if (which == 0 && n == 1) q_free();
    if (which == 1 || n == 1) mask_diag();
    {
      const uint4* dst = at<uint4>(g_qc, (uint32_t)((h * 8 + j) * 2 + w) * 32768 + (fresh_tid() & 127) * 16);
      softmax([&](int jj, float e) {
        if (jj == PEEK_JJ) peek2();
        const int i = CTX_SPLIT + jj;
        if (i < 16)
          asm volatile("{\n.reg .pred p, q;\nsetp.ne.b32 q, %6, 0;\nsetp.geu.and.f32 p, %5, 0fBF800000, q;\n@p st.global.v4.u32 [%0], {%1, %2, %3, %4};\n}"
                       :: "l"(dst + i * 128), "r"(pk[4 * (i & 15)]), "r"(pk[4 * (i & 15) + 1]), "r"(pk[4 * (i & 15) + 2]), "r"(pk[4 * (i & 15) + 3]), "f"(e), "r"(which) : "memory");
      });
    }
    to_p(pa);
    if (which == 1) warp_arrive(bar_addr(sb, B_ST_CTX + w), lane);
    TS(10 + 5 * which);
#pragma unroll 1
    for (int jj = 1; jj < n; jj++) {
      ks = take(rdy0);
      const uint32_t vs = take(rdy1);
      prep_qk(sb + ks * SLOT);
      prep_pv(sb + vs * SLOT);
      TSC(23 + 10 * which, jj == 1);
      turn_begin();
      TSC(24 + 10 * which, jj == 1);
      TSC(26 + 10 * which, jj == n - 1);
      wg_fence();
      issue_qk();
      wg_commit();
      issue_pv(jj > 1);
      wg_commit();
      turn_end();
      wg_wait<1>();
      TSC(25 + 10 * which, jj == 1);
      reg_fence(s);
      give(ks);
      if (jj == n - 1 && which == 0) { q_free(); mask_diag(); }
      if (PF_CTX && which == 1 && jj == max(n - PF_CTX, 1)) {
        const uint8_t* src = at<const uint8_t>(g_qc, (uint32_t)(((h ^ 8) * 8 + j) * 2 + (w ^ 1)) * 32768 + (fresh_tid() & 127) * 128);
        asm volatile("prefetch.global.L2 [%0];" :: "l"(src));
        asm volatile("prefetch.global.L2 [%0];" :: "l"(src + 16384));
      }
      if (softmax_fast()) {
        wg_wait<0>();
        reg_fence(acc);
        if (softmax([](int, float) {})) rescale();
        to_p(pb);
      }
      peek2();
      wg_wait<0>();
      reg_fence(acc);
      reg_fence(pa);
      give(vs);
#pragma unroll
      for (int i = 0; i < 16; i++) pa[i] = pb[i] | (vs >> 8);
    }
    TS(11 + 5 * which);
    if (which == 0) { give(take(rdy0)); rdy0 = rdy1; }
    {
      const uint32_t vs = take(rdy0);
      prep_pv(sb + vs * SLOT);
      TS(27 + 10 * which);
      turn_begin();
      TS(28 + 10 * which);
      wg_fence();
      issue_pv(n > 1);
      wg_commit();
      turn_end();
      l0 += __shfl_xor_sync(0xffffffffu, l0, 1); l1 += __shfl_xor_sync(0xffffffffu, l1, 1);
      l0 += __shfl_xor_sync(0xffffffffu, l0, 2); l1 += __shfl_xor_sync(0xffffffffu, l1, 2);
      asm("rcp.approx.ftz.f32 %0, %0;" : "+f"(l0));
      asm("rcp.approx.ftz.f32 %0, %0;" : "+f"(l1));
      peek2();
      if (which == 0) mbar_wait(bar_addr(sb, B_QFULL + w), 0);
      wg_wait<0>();
      reg_fence(acc);
      reg_fence(pa);
      give(vs);
    }
    TS(12 + 5 * which);
    {
      const uint4* dst = at<uint4>(g_qc, (uint32_t)((h * 8 + j) * 2 + w) * 32768 + (fresh_tid() & 127) * 16);
#pragma unroll
      for (int i = 0; i < 16; i++) {
        const int c = (i & 1) ? (i >> 1) + 8 : i >> 1;
        pk[4 * c]     = pack_bf16(acc[8 * c] * l0, acc[8 * c + 1] * l0);
        pk[4 * c + 1] = pack_bf16(acc[8 * c + 2] * l1, acc[8 * c + 3] * l1);
        pk[4 * c + 2] = pack_bf16(acc[8 * c + 4] * l0, acc[8 * c + 5] * l0);
        pk[4 * c + 3] = pack_bf16(acc[8 * c + 6] * l1, acc[8 * c + 7] * l1);
        if (c < CTX_SPLIT)
          asm volatile("{\n.reg .pred p;\nsetp.eq.b32 p, %5, 0;\n@p st.global.v4.u32 [%0], {%1, %2, %3, %4};\n}"
                       :: "l"(dst + c * 128), "r"(pk[4 * c]), "r"(pk[4 * c + 1]), "r"(pk[4 * c + 2]), "r"(pk[4 * c + 3]), "r"(which) : "memory");
      }
    }
    TS(13 + 5 * which);
  }

  {
    float oa[32], ob[32];
#pragma unroll
    for (int i = 0; i < 32; i++) { oa[i] = 0.f; ob[i] = 0.f; }
    uint32_t pk2[64];
#pragma unroll
    for (int i = 0; i < 64; i++) pk2[i] = 0;
    auto stage = [&](float (&o)[32], int ch) {
      reg_fence(o);
      uint32_t q[16];
#pragma unroll
      for (int i = 0; i < 16; i++) q[i] = pack_bf16(o[2 * i], o[2 * i + 1]);
      if (ch >= 4) mbar_wait(bar_addr(sb, B_S2_EMPTY + w * 4 + (ch & 3)), 0);
      store_block(qreg + (ch & 3) * 8192, lane_base16(), q);
    };
    auto hand_over = [&](int ch) {
      fence_async_smem();
      warp_arrive(bar_addr(sb, B_S2_FULL + w * 4 + (ch & 3)), lane);
    };
    uint32_t prev = 0;
    auto half = [&](int f, float (&o)[32], uint32_t (&a)[64], int accumulate) {
      const uint32_t sl = take(rdy0);
      const uint64_t d = desc_mn(sb + sl * SLOT);
      turn_begin();
      TS(40 + f);
      wg_fence();
#pragma unroll
      for (int kk = 0; kk < 16; kk++) {
        wgmma_rs_n64_tb(o, a[4 * kk], a[4 * kk + 1], a[4 * kk + 2], a[4 * kk + 3], desc_add(d, kk * 2048), accumulate | kk);
        if (kk == ARRIVE_KK && (f < 13 || w == 0)) turn_end();
      }
      wg_commit();
      if (f < 13) rdy0 = mbar_test(bar_addr(sb, B_FULL + r.slot), r.phase);
      wg_wait<1>();
      if (f >= 1 && f <= 9) give(prev);
      prev = sl;
    };
    auto load_ctx = [&](auto h0) {
      constexpr int I0 = decltype(h0)::value ? CTX_LD : 0, NL = decltype(h0)::value ? 16 - CTX_LD : CTX_LD;
      const uint4* src = at<const uint4>(g_qc, (uint32_t)(((h ^ 8) * 8 + j) * 2 + (w ^ 1)) * 32768 + (fresh_tid() & 127) * 16);
#pragma unroll
      for (int i = I0; i < I0 + NL; i++) { const uint4 v = __ldcg(src + i * 128); pk2[4 * i] = v.x; pk2[4 * i + 1] = v.y; pk2[4 * i + 2] = v.z; pk2[4 * i + 3] = v.w; }
    };
#pragma unroll 1
    for (int i = 0; i < 3; i++) {
      half(4 * i, oa, pk, 0);
      if (i == 0) { mbar_wait(bar_addr(sb, B_CTXOK + w), 0); load_ctx(Int<0>()); }
      else { hand_over(2 * i - 2); stage(ob, 2 * i - 1); }
      half(4 * i + 1, ob, pk, 0);
      if (i == 0) load_ctx(Int<1>()); else hand_over(2 * i - 1);
      half(4 * i + 2, oa, pk2, 1);
      half(4 * i + 3, ob, pk2, 1);
      stage(oa, 2 * i);
    }
    half(12, oa, pk, 0);
    hand_over(4);
    stage(ob, 5);
    half(13, oa, pk2, 1);
    hand_over(5);
    wg_wait<0>();
    reg_fence(pk);
    reg_fence(pk2);
    stage(oa, 6);
    hand_over(6);
  }
  TS(19);
  TDUMP();
}

namespace ssm {
constexpr int NCH = DA / NCONV;
constexpr int NS = 8, NP = 6;
constexpr uint32_t X0 = 384;
constexpr uint32_t HO = X0 + 4096;
constexpr uint32_t HE = HO + HO_STRIDE + 64;
constexpr uint32_t SSLOT = HE + 4096 + 64;
constexpr uint32_t PART = 264 * 16;
constexpr uint32_t OFF_P = NS * SSLOT, OFF_D = OFF_P + NP * 4 * PART, END = OFF_D + NCH * 4;
static_assert(SSLOT % 128 == 0 && HO % 128 == 0 && END <= BARS, "smem");
enum : uint32_t { B_FULL = 0, B_EMPTY = NS, B_PFULL = 2 * NS, B_PEMPTY = 2 * NS + NP };
__device__ __forceinline__ int channel(int cidx, int i) { return (i >> 4) * 64 + cidx * 16 + (i & 15); }

__device__ __forceinline__ void producer(const Params& p, uint32_t sb, int cidx, unsigned epoch) {
#pragma unroll 1
  for (int i = 0; i < NCH; i++) {
    const int s = i % NS, ch = channel(cidx, i);
    const uint32_t full = bar_addr(sb, B_FULL + s), dst = sb + s * SSLOT;
    mbar_wait(bar_addr(sb, B_EMPTY + s), ((i / NS) & 1) ^ 1);
    mbar_expect_tx(full, 4096 + 4128 + 4096);
    bulk_ld(dst + HE, at<uint8_t>(p.a_ssmk, ch * 4096), 4096, full);
    if ((i & 15) == 0) { flag_wait(flag_at(g_flags.x_ready, i >> 4), NMAIN, epoch); fence_async_all(); }
    bulk_ld(dst + HO, at<uint8_t>(g_ho, ch * HO_STRIDE), 4128, full);
    bulk_ld(dst + X0, at<uint8_t>(g_xs, ch * 4096), 4096, full);
  }
}

__device__ __forceinline__ void reducer(uint32_t sb, int cidx, int rw) {
  uint32_t n = 0;
#pragma unroll 1
  for (int i = rw; i < NCH; i += 3, n++) {
    const uint32_t b = rw + 3 * (n & 1), pb = sb + OFF_P + b * 4 * PART;
    uint8_t* dst = at<uint8_t>(g_xs, channel(cidx, i) * 4096);
    mbar_wait(bar_addr(sb, B_PFULL + b), (n >> 1) & 1);
    asm volatile("cp.async.bulk.global.shared::cta.bulk_group [%0], [%1], 4096;" :: "l"(dst), "r"(pb + 3 * PART) : "memory");
    bulk_commit();
    bulk_wait_all();
#pragma unroll
    for (int k = 2; k >= 0; k--)
      asm volatile("cp.reduce.async.bulk.global.shared::cta.bulk_group.add.noftz.bf16 [%0], [%1], 4096;" :: "l"(dst), "r"(pb + k * PART) : "memory");
    bulk_commit();
    bulk_wait_read();
    mbar_arrive(bar_addr(sb, B_PEMPTY + b));
    if (((i + 3) >> 4) != (i >> 4)) {
      bulk_wait_all();
      fence_async_all();
      flag_signal(flag_at(g_flags.z_ready, i >> 4));
    }
  }
}

__device__ __forceinline__ void mma_warpgroup(uint32_t sb, int w) {
  const int lane = threadIdx.x & 31, g = lane >> 2, c = lane & 3, wq = (threadIdx.x >> 5) & 3;
  const uint32_t aoff = ((g & 1) ? HO + 30 : HE) + (16 * wq - g + 2 * c) * 2;
  const uint32_t poff = OFF_P + wq * PART + (2 * wq + lane) * 16;
  const uint32_t dmask = (wq == 0 && c == (g >> 1)) ? ((g & 1) ? 0xffff0000u : 0xffffu) : 0u;
  float acc[8][16];
  uint32_t fa[16][4];
#pragma unroll
  for (int e = 0; e < 8; e++)
#pragma unroll
    for (int i = 0; i < 16; i++) acc[e][i] = 0.f;
  auto load_a = [&](int m, uint32_t ad) {
    fa[m][0] = lds4(ad + m * 256 + 16); fa[m][1] = lds4(ad + m * 256 + 144); fa[m][2] = lds4(ad + m * 256); fa[m][3] = lds4(ad + m * 256 + 128);
  };
  if (w == 1) named_arrive(PP_BAR, 256);
  mbar_wait(bar_addr(sb, B_FULL + w), 0);
#pragma unroll
  for (int m = 0; m < 16; m++) load_a(m, sb + w * SSLOT + aoff);
  uint32_t dd = lds4(sb + OFF_D + w * 4);
  if (threadIdx.x == 128) { GT(12); PT(10); }
  uint32_t pb = w, pphase = 1;
#pragma unroll 1
  for (int i = w; i < NCH; i += 2) {
    fa[0][2] = badd(fa[0][2], dd & dmask);
    const uint64_t db = (uint64_t)((((sb + (i % NS) * SSLOT + X0 - 16) & 0x3FFFF) >> 4) | (1u << 16)) | ((uint64_t)8 << 32);
    named_sync(PP_BAR + w, 256);
    wg_fence();
#pragma unroll
    for (int r = 0; r < 16; r++) {
      auto mm = [&](int e, int m) { wgmma_rs_n32(acc[e], fa[m][0], fa[m][1], fa[m][2], fa[m][3], db + (int64_t)(32 * e - 16 * m), m != 0); };
      mm(7, r);
      if (r < 14) mm(6, r); else mm(0, r - 14);
      if (r < 12) mm(5, r); else mm(1, r - 12);
      if (r < 10) mm(4, r); else mm(2, r - 10);
      if ((r & 1) == 0) mm(3, r >> 1);
      if (r == CONV_ARRIVE && (i + 1 < NCH)) named_arrive(PP_BAR + (w ^ 1), 256);
    }
    wg_commit();
    const int nx = i + 2 < NCH ? i + 2 : i;
    mbar_wait(bar_addr(sb, B_FULL + nx % NS), (nx / NS) & 1);
    mbar_wait(bar_addr(sb, B_PEMPTY + pb), pphase);
    const uint32_t ad = sb + (nx % NS) * SSLOT + aoff, pa = sb + pb * 4 * PART + poff;
    wg_wait<0>();
#pragma unroll
    for (int e = 0; e < 8; e++) reg_fence(acc[e]);
#pragma unroll
    for (int m = 0; m < 16; m++) reg_fence(fa[m]);
    if (lane == 0) mbar_arrive(bar_addr(sb, B_EMPTY + i % NS));
#pragma unroll
    for (int e = 0; e < 8; e++) {
      if (e < CONV_EARLY) load_a(e, ad);
      uint32_t u[4];
#pragma unroll
      for (int j = 0; j < 4; j++) {
        const int T = 4 * e + j, U = T - 1;
        float lo = acc[e][4 * j], hi = acc[e][4 * j + 1];
        if (T > 0) { lo += acc[U >> 2][4 * (U & 3) + 2]; hi += acc[U >> 2][4 * (U & 3) + 3]; }
        u[j] = pack_bf16(lo, hi);
      }
      asm volatile("stmatrix.sync.aligned.m8n8.x4.trans.shared.b16 [%0], {%1, %2, %3, %4};" :: "r"(pa + e * 512), "r"(u[0]), "r"(u[1]), "r"(u[2]), "r"(u[3]) : "memory");
    }
    dd = lds4(sb + OFF_D + nx * 4);
#pragma unroll
    for (int m = CONV_EARLY; m < CONV_FENCE; m++) load_a(m, ad);
    fence_async_smem();
    warp_arrive(bar_addr(sb, B_PFULL + pb), lane);
#pragma unroll
    for (int m = CONV_FENCE; m < 16; m++) load_a(m, ad);
    pb += 2;
    if (pb >= NP) { pb -= NP; pphase ^= 1; }
  }
  if (threadIdx.x == 128) { PT(9); GT(13); }
}

__device__ __forceinline__ void init(const Params& p, uint32_t sb, int cidx) {
  if (threadIdx.x < NS * 32) {
    const uint32_t s = threadIdx.x >> 5, r = threadIdx.x & 31;
    if (r < 28) sts16(sb + s * SSLOT + (r < 24 ? r * 16 : HE - 64 + (r - 24) * 16), 0, 0, 0, 0);
  } else {
    const uint32_t t = threadIdx.x - NS * 32;
    for (uint32_t u = t; u < NP * 32; u += 128) sts16(sb + OFF_P + (u >> 3) * PART + (u & 7) * 16, 0, 0, 0, 0);
    if (t < NCH) {
      const uint32_t d = (uint32_t)__ldg(reinterpret_cast<const unsigned short*>(p.a_D + channel(cidx, t))) * 0x10001u;
      asm volatile("st.shared.u32 [%0], %1;" :: "r"(sb + OFF_D + t * 4), "r"(d) : "memory");
    }
  }
  if (threadIdx.x == 0) {
    for (int i = 0; i < NS; i++) { mbar_init(bar_addr(sb, B_FULL + i), 1); mbar_init(bar_addr(sb, B_EMPTY + i), 4); }
    for (int i = 0; i < NP; i++) { mbar_init(bar_addr(sb, B_PFULL + i), 4); mbar_init(bar_addr(sb, B_PEMPTY + i), 1); }
  }
  fence_async_smem();
}

__device__ __forceinline__ void side_prepare(const Params& p, int cta, int rd) {
  const int lane = threadIdx.x & 31, t0 = 16 * cta + 8 * (lane & 1);
  if (EXP_SIDE & 16) { if (lane == 0) flag_signal_after_bulk(flag_at(g_flags.x_ready, rd)); return; }
#pragma unroll 1
  for (int ch = 64 * rd + (lane & ~1); ch < 64 * rd + 64; ch += 32) {
    const uint4 sv = __ldg(at<const uint4>(p.a_shift, ch * 8));
    const uint32_t* kp = at<const uint32_t>(p.a_k, (t0 * DA + ch) * 2);
    const uint32_t* vp = at<const uint32_t>(p.a_v, (t0 * DA + ch) * 2);
    uint32_t k0 = 0, k1 = 0, k2 = 0, kk[8], x[8];
    if (t0 > 0) { k0 = __ldg(kp - 3 * (DA / 2)); k1 = __ldg(kp - 2 * (DA / 2)); k2 = __ldg(kp - DA / 2); }
#pragma unroll
    for (int i = 0; i < 8; i++) { kk[i] = __ldg(kp + i * (DA / 2)); x[i] = __ldg(vp + i * (DA / 2)); }
    const uint32_t sh0 = __byte_perm(sv.x, sv.z, 0x5410), sh1 = __byte_perm(sv.x, sv.z, 0x7632);
    const uint32_t sh2 = __byte_perm(sv.y, sv.w, 0x5410), sh3 = __byte_perm(sv.y, sv.w, 0x7632);
#pragma unroll
    for (int i = 0; i < 8; i++) {
      uint32_t ks = bmul(k0, sh3);
      ks = badd(ks, bmul(k1, sh2)); ks = badd(ks, bmul(k2, sh1)); ks = badd(ks, bmul(kk[i], sh0));
      x[i] = bmul(ks, x[i]);
      k0 = k1; k1 = k2; k2 = kk[i];
    }
    uint4* dst = at<uint4>(g_xs, ch * 4096 + t0 * 2);
    if ((EXP_SIDE & 4) && (x[0] ^ x[1] ^ x[2] ^ x[3] ^ x[4] ^ x[5] ^ x[6] ^ x[7]) != 0x12345) continue;
    dst[0]   = make_uint4(__byte_perm(x[7], x[6], 0x5410), __byte_perm(x[5], x[4], 0x5410), __byte_perm(x[3], x[2], 0x5410), __byte_perm(x[1], x[0], 0x5410));
    dst[256] = make_uint4(__byte_perm(x[7], x[6], 0x7632), __byte_perm(x[5], x[4], 0x7632), __byte_perm(x[3], x[2], 0x7632), __byte_perm(x[1], x[0], 0x7632));
  }
  if (!(EXP_SIDE & 8)) {
    const int hc = 64 * rd + (cta >> 1), r0 = (cta & 1) * 128 + lane;
    const uint4* src = at<const uint4>(p.a_ssmk, hc * 4096 + r0 * 16);
    uint4* dst = at<uint4>(g_ho, hc * HO_STRIDE + r0 * 16);
    uint4 w[4];
    uint32_t nx[4];
#pragma unroll
    for (int i = 0; i < 4; i++) { w[i] = __ldg(src + 32 * i); nx[i] = r0 + 32 * i < 255 ? __ldg(reinterpret_cast<const uint32_t*>(src + 32 * i + 1)) : 0u; }
#pragma unroll
    for (int i = 0; i < 4; i++)
      dst[32 * i + 2] = make_uint4(__byte_perm(w[i].x, w[i].y, 0x5432), __byte_perm(w[i].y, w[i].z, 0x5432), __byte_perm(w[i].z, w[i].w, 0x5432), __byte_perm(w[i].w, nx[i], 0x5432));
    const uint32_t h0 = __shfl_sync(0xffffffffu, w[0].x, 0);
    if (r0 < 2) dst[0] = make_uint4(0, 0, 0, r0 ? h0 << 16 : 0u);
  }
  __syncwarp();
  if (lane == 0) { if (EXP_SIDE & 2) flag_signal_after_bulk(flag_at(g_flags.x_ready, rd)); else flag_signal(flag_at(g_flags.x_ready, rd)); }
}
__device__ __forceinline__ void side_finish(const Params& p, int cta, int rd) {
  const int lane = threadIdx.x & 31, t0 = 16 * cta + 8 * (lane & 1);
#pragma unroll 1
  for (int ch = 64 * rd + (lane & ~1); ch < 64 * rd + 64; ch += 32) {
    const uint4* src = at<const uint4>(g_xs, ch * 4096 + t0 * 2);
    const uint32_t* qp = at<const uint32_t>(p.a_q, (t0 * DA + ch) * 2);
    uint32_t* op = at<uint32_t>(p.out, (t0 * OUTW + ch) * 2);
    const uint4 z0 = __ldcg(src), z1 = __ldcg(src + 256);
    uint32_t q[8];
#pragma unroll
    for (int i = 0; i < 8; i++) q[i] = __ldg(qp + i * (DA / 2));
    const uint32_t a[4] = {z0.w, z0.z, z0.y, z0.x}, b[4] = {z1.w, z1.z, z1.y, z1.x};
#pragma unroll
    for (int i = 0; i < 4; i++) {
      op[(2 * i) * (OUTW / 2)]     = bmul(q[2 * i], __byte_perm(a[i], b[i], 0x7632));
      op[(2 * i + 1) * (OUTW / 2)] = bmul(q[2 * i + 1], __byte_perm(a[i], b[i], 0x5410));
    }
  }
}
__device__ __forceinline__ void clear_rows(const Params& p, int qt, int part) {
  const int lane = threadIdx.x & 31;
  if (lane < 28) {
    uint4* z = at<uint4>(p.out, ((qt * 128 + part * 16) * OUTW + DA) * 2 + lane * 16);
#pragma unroll
    for (int i = 0; i < 32; i++) z[(i >> 1) * (OUTW / 8) + (i & 1) * 28] = make_uint4(0, 0, 0, 0);
  }
  __syncwarp();
  if (lane == 0) flag_signal(flag_at(g_flags.zero_ready, qt));
}
__device__ __forceinline__ void side_work(const Params& p, int cta, int qt, unsigned epoch) {
#pragma unroll 1
  for (int rd = -SIDE_AHEAD; rd < 7; rd++) {
    if (rd >= 0) {
      if ((threadIdx.x & 31) == 0) flag_wait_slow(flag_at(g_flags.z_ready, rd), 3 * NCONV, epoch);
      __syncwarp();
    }
    if (rd + SIDE_AHEAD < 7) side_prepare(p, cta, rd + SIDE_AHEAD);
    if (rd >= 0 && !(EXP_SIDE & 1)) side_finish(p, cta, rd);
    if (rd == ZERO_RD) clear_rows(p, qt, (cta >> 3) & 7);
  }
}
}

__global__ void __cluster_dims__(2, 1, 1) __launch_bounds__(NTHREADS, 1)
concat_heads__ssm_conv_h3__compressed_kv_cla__prompt_kernel(const __grid_constant__ Params p) {
  extern __shared__ uint8_t smem_raw[];
  const uint32_t sb = (smem_u32(smem_raw) + 1023) & ~1023u;
  const int warp = __shfl_sync(0xffffffffu, threadIdx.x >> 5, 0);
  const int wg = warp >> 2;
  const int cta = blockIdx.x;
  const bool attn = cta < NMAIN;
  int h, u;
  {
    const int c = cta >> 1;
    if (c < 4) { h = 15; u = c; }
    else if (c < 36) { h = (c - 4) & 7; u = (c - 4) >> 3; }
    else { h = 8 + (c - 36) % 7; u = (c - 36) / 7; }
  }
  const int j = 2 * u + (cta & 1);
  if (!attn) ssm::init(p, sb, cta - NMAIN);
  if (attn && threadIdx.x == 0) {
    for (int i = 0; i < NSLOT; i++) { mbar_init(bar_addr(sb, B_FULL + i), 1); mbar_init(bar_addr(sb, B_EMPTY + i), 16); }
    for (int i = 0; i < 2; i++) {
      mbar_init(bar_addr(sb, B_XFREE + i), 8); mbar_init(bar_addr(sb, B_QFREE + i), 4); mbar_init(bar_addr(sb, B_QFULL + i), 1);
      mbar_init(bar_addr(sb, B_ST_KV + i), 4); mbar_init(bar_addr(sb, B_ST_Q + i), 4); mbar_init(bar_addr(sb, B_ST_CTX + i), 4);
      mbar_init(bar_addr(sb, B_CTXOK + i), 1);
    }
    mbar_init(bar_addr(sb, B_KVOK), 1); mbar_init(bar_addr(sb, B_PF), 1);
    mbar_init(bar_addr(sb, B_DONE), 2);
    for (int i = 0; i < 8; i++) { mbar_init(bar_addr(sb, B_S2_FULL + i), 4); mbar_init(bar_addr(sb, B_S2_EMPTY + i), 1); }
    asm volatile("fence.mbarrier_init.release.cluster;" ::: "memory");
  }
  if (attn && threadIdx.x == 32) {
    prefetch_map(&p.ckv); prefetch_map(&p.wuk); prefetch_map(&p.wuv); prefetch_map(&p.x); prefetch_map(&p.wq);
    prefetch_map(&p.o); prefetch_map(&p.wo);
  }
  __syncwarp();
  asm volatile("barrier.cluster.arrive.release.aligned;" ::: "memory");
  if (attn && threadIdx.x == 0) {
    for (int k = 0; k < EARLY_LD; k++) {
      const uint32_t full = bar_addr(sb, B_FULL + k);
      mbar_expect_tx(full, 49152);
      tma_ld2(sb + QREG + k * 16384, &p.ckv, full, k * 64, p1_rows(h, j, 0) * 128);
      load_tile4(sb + k * SLOT, &p.wuk, full, k * 64, p1_head(h, 0) * 4, j & 1, false, pol(HINTS & 1));
    }
  }
  __syncwarp();
  asm volatile("barrier.cluster.wait.acquire.aligned;" ::: "memory");

  const int lane = threadIdx.x & 31;
  if (wg == 0) {
    if (!attn) {
      asm volatile("setmaxnreg.dec.sync.aligned.u32 40;");
      if (lane == 0) {
        if (warp == 0) { ssm::producer(p, sb, cta - NMAIN, load_epoch()); cta_done(32); }
        else ssm::reducer(sb, cta - NMAIN, warp - 1);
        if (warp == 1) GT(14);
      }
      return;
    }
    asm volatile("setmaxnreg.dec.sync.aligned.u32 40;");
    if (warp == 0) {
      if (lane == 0) producer_main(p, sb, h, j);
    } else if (warp < 3) {
      if (PF_Q && warp == 2) {
        mbar_wait(bar_addr(sb, B_PF), 0);
        const uint8_t* xp = at<const uint8_t>(p.b_x, (h * 8 + j) * 16 * DM * 2 + lane * 128);
        const uint8_t* wp = at<const uint8_t>(p.b_wq, ((j * 56 + (lane >> 2)) * NH + h) * HD * 2 + (lane & 3) * 128);
#pragma unroll
        for (int i = 0; i < 7; i++) {
          if (i < 3 || (i == 3 && lane < 16)) asm volatile("prefetch.global.L2 [%0];" :: "l"(xp + i * 4096));
          asm volatile("prefetch.global.L2 [%0];" :: "l"(wp + i * 8 * NH * HD * 2));
          __nanosleep(PF_GAP);
        }
      }
      if (lane == 0) { helper_main(p, sb, h, j, warp - 1); mbar_arrive(bar_addr(sb, B_DONE)); }
    } else {
      ssm::side_work(p, h * 8 + j, q_tile(h, j, 1), load_epoch());
      if (lane == 0) { GT(57); mbar_wait(bar_addr(sb, B_DONE), 0); cta_done(1); }
    }
  } else {
    if (!attn) {
      asm volatile("setmaxnreg.inc.sync.aligned.u32 232;");
      if (p.out != nullptr) ssm::mma_warpgroup(sb, wg - 1);
      return;
    }
    asm volatile("setmaxnreg.inc.sync.aligned.u32 232;");
    if (p.out != nullptr) consumer_main(p, sb, h, j, wg - 1, warp & 3);
  }
}

typedef CUresult (*EncodeTiledFn)(CUtensorMap*, CUtensorMapDataType, cuuint32_t, void*, const cuuint64_t*, const cuuint64_t*,
                                  const cuuint32_t*, const cuuint32_t*, CUtensorMapInterleave, CUtensorMapSwizzle,
                                  CUtensorMapL2promotion, CUtensorMapFloatOOBfill);

void make_map(EncodeTiledFn enc, CUtensorMap* m, const void* ptr, int rank, const uint64_t* dims, const uint64_t* strides, const uint32_t* box) {
  cuuint64_t d[5], s[4]; cuuint32_t b[5], e[5] = {1, 1, 1, 1, 1};
  for (int i = 0; i < rank; i++) { d[i] = dims[i]; b[i] = box[i]; if (i) s[i - 1] = strides[i - 1]; }
  enc(m, CU_TENSOR_MAP_DATA_TYPE_BFLOAT16, rank, const_cast<void*>(ptr), d, s, b, e, CU_TENSOR_MAP_INTERLEAVE_NONE,
      CU_TENSOR_MAP_SWIZZLE_128B, CU_TENSOR_MAP_L2_PROMOTION_L2_256B, CU_TENSOR_MAP_FLOAT_OOB_FILL_NONE);
}
void map2(EncodeTiledFn enc, CUtensorMap* m, const void* ptr, uint64_t cols, uint64_t rows, uint32_t bc, uint32_t br) {
  const uint64_t dims[2] = {cols, rows}, st[1] = {cols * 2}; const uint32_t box[2] = {bc, br};
  make_map(enc, m, ptr, 2, dims, st, box);
}
void map3(EncodeTiledFn enc, CUtensorMap* m, const void* ptr, uint64_t rows, uint32_t nblk) {
  const uint64_t dims[3] = {64, rows, 64}, st[2] = {8192, 128}; const uint32_t box[3] = {64, 64, nblk};
  make_map(enc, m, ptr, 3, dims, st, box);
}

}

extern "C" void kernel_launch(void* const* d_in, const int* in_sizes, int n_in, void* d_out, int out_size) {
  (void)in_sizes; (void)n_in; (void)out_size;
  static EncodeTiledFn enc = nullptr;
  if (!enc) {
    void* fn = nullptr; cudaDriverEntryPointQueryResult qr;
    cudaGetDriverEntryPoint("cuTensorMapEncodeTiled", &fn, cudaEnableDefault, &qr);
    enc = (EncodeTiledFn)fn;
    cudaFuncSetAttribute(concat_heads__ssm_conv_h3__compressed_kv_cla__prompt_kernel, cudaFuncAttributeMaxDynamicSharedMemorySize, SMEM_BYTES);
  }
  Params p;
  p.a_q = (const bf16*)d_in[0]; p.a_k = (const bf16*)d_in[1]; p.a_v = (const bf16*)d_in[2];
  p.a_shift = (const bf16*)d_in[3]; p.a_ssmk = (const bf16*)d_in[4]; p.a_D = (const bf16*)d_in[5];
  p.out = (bf16*)d_out;
  p.b_x = (const bf16*)d_in[6]; p.b_wq = (const bf16*)d_in[8];
  map2(enc, &p.x, d_in[6], DM, SEQ, 64, 128);
  map2(enc, &p.ckv, d_in[7], DC, SEQ, 64, 128);
  map3(enc, &p.wq, d_in[8], DM, 2);
  map3(enc, &p.wuk, d_in[9], DC, 2);
  map3(enc, &p.wuv, d_in[10], DC, 2);
  {
    const uint64_t dims[5] = {DM, 2, 4, 4, NH * HD / 32}, st[4] = {DM * 2, 8 * DM * 2, 2 * DM * 2, 32 * DM * 2}; const uint32_t box[5] = {64, 2, 4, 4, 4};
    make_map(enc, &p.wo, d_in[11], 5, dims, st, box);
  }
  map2(enc, &p.o, d_out, OUTW, SEQ, 64, 64);
  concat_heads__ssm_conv_h3__compressed_kv_cla__prompt_kernel<<<NCTA, NTHREADS, SMEM_BYTES>>>(p);
}
```

```cpp
#include <cuda_runtime.h>
#include <cuda_bf16.h>
#include <cuda.h>
#include <stdint.h>

namespace {

typedef __nv_bfloat16 bf16;

constexpr int SEQ  = 2048;
constexpr int DA   = 448;
constexpr int NH   = 16;
constexpr int HD   = 256;
constexpr int DM   = 448;
constexpr int DC   = 1024;
constexpr int OUTW = DA + DM;
constexpr int NMAIN = 128;
constexpr int NCONV = 4;
constexpr int NCTA  = NMAIN + NCONV;
constexpr int LOG_DONE = 8;
constexpr int NTHREADS = 384;

__device__ __align__(1024) bf16 g_kv[2ull * SEQ * NH * HD];
__device__ __align__(1024) bf16 g_qc[(size_t)NMAIN * 128 * HD];
__device__ __align__(128) uint8_t g_xs[DA * SEQ * 2];
constexpr uint32_t HO_STRIDE = 4224;
__device__ __align__(128) uint8_t g_ho[DA * HO_STRIDE];
struct alignas(128) Flag { unsigned v; unsigned pad[31]; };
struct Flags {
  Flag kv_ready[NH * 2];
  Flag ctx_ready[NMAIN * 2];
  Flag x_ready[7];
  Flag z_ready[7];
  Flag zero_ready[16];
  alignas(128) unsigned long long done;
};
__device__ Flags g_flags;
#define TS(i)
#define TSC(i, cond)
#define TDUMP()
#define GT(i)
#define PT(i)
#define PCLK(var)
#define PACC(acc, t0)

struct alignas(64) Params {
  CUtensorMap ckv;
  CUtensorMap wuk;
  CUtensorMap wuv;
  CUtensorMap x;
  CUtensorMap wq;
  CUtensorMap o;
  CUtensorMap wo;
  const bf16 *a_q, *a_k, *a_v, *a_shift, *a_ssmk, *a_D, *b_x, *b_wq;
  bf16* out;
};

constexpr uint32_t SLOT     = 32768;
constexpr int      NSLOT    = 5;
constexpr uint32_t QREG     = 163840;
constexpr uint32_t BARS     = 229376;
constexpr uint32_t SMEM_BYTES = BARS + 1024 + 1024;
enum : uint32_t {
  B_FULL = 0, B_EMPTY = 5, B_XFREE = 10, B_KVOK = 12, B_ST_Q = 14, B_ST_CTX = 16, B_DONE = 19, B_QFREE = 20, B_QFULL = 22,
  B_S2_FULL = 24, B_S2_EMPTY = 32, B_CTXOK = 40, B_PF = 42, B_ST_KV = 44
};
constexpr int P1_STEPS = 4 * 16 + 2 * 7, P1_XS = P1_STEPS - 2;

template <typename T> __device__ __forceinline__ T* at(const void* base, uint32_t off) {
  asm volatile("" : "+r"(off));
  return reinterpret_cast<T*>(const_cast<char*>(static_cast<const char*>(base)) + off);
}
__device__ __forceinline__ unsigned* flag_at(Flag* f, uint32_t i) { return at<unsigned>(f, i * (uint32_t)sizeof(Flag)); }
__device__ __forceinline__ uint32_t smem_u32(const void* p) { return (uint32_t)__cvta_generic_to_shared(p); }
__device__ __forceinline__ void mbar_init(uint32_t bar, uint32_t cnt) {
  asm volatile("mbarrier.init.shared::cta.b64 [%0], %1;" :: "r"(bar), "r"(cnt) : "memory");
}
__device__ __forceinline__ void mbar_expect_tx(uint32_t bar, uint32_t bytes) {
  asm volatile("mbarrier.arrive.expect_tx.shared::cta.b64 _, [%0], %1;" :: "r"(bar), "r"(bytes) : "memory");
}
__device__ __forceinline__ void mbar_arrive(uint32_t bar) {
  asm volatile("mbarrier.arrive.shared::cta.b64 _, [%0];" :: "r"(bar) : "memory");
}
__device__ __forceinline__ void mbar_arrive_n(uint32_t bar, uint32_t n) {
  asm volatile("mbarrier.arrive.shared::cta.b64 _, [%0], %1;" :: "r"(bar), "r"(n) : "memory");
}
__device__ __forceinline__ void mbar_arrive_remote(uint32_t bar, uint32_t cta) {
  asm volatile("{\n.reg .b32 ra;\nmapa.shared::cluster.u32 ra, %0, %1;\n"
               "mbarrier.arrive.shared::cluster.b64 _, [ra];\n}" :: "r"(bar), "r"(cta) : "memory");
}
__device__ __forceinline__ bool mbar_try(uint32_t bar, uint32_t parity) {
  uint32_t ok;
  asm volatile("{\n.reg .pred p;\nmbarrier.try_wait.parity.shared::cta.b64 p, [%1], %2;\nselp.u32 %0, 1, 0, p;\n}"
               : "=r"(ok) : "r"(bar), "r"(parity) : "memory");
  return ok;
}
__device__ __forceinline__ uint32_t mbar_test(uint32_t bar, uint32_t parity) {
  uint32_t ok;
  asm volatile("{\n.reg .pred p;\nmbarrier.test_wait.parity.shared::cta.b64 p, [%1], %2;\nselp.u32 %0, 1, 0, p;\n}"
               : "=r"(ok) : "r"(bar), "r"(parity) : "memory");
  return ok;
}
constexpr uint32_t SPIN_LIMIT = 1u << 24;
__device__ __forceinline__ void mbar_wait(uint32_t bar, uint32_t parity) {
  if (mbar_try(bar, parity)) return;
  uint32_t n = 0;
  while (!mbar_try(bar, parity)) { if (++n > SPIN_LIMIT) __trap(); }
}
__device__ __forceinline__ void mbar_wait_unless(uint32_t ready, uint32_t bar, uint32_t parity) {
  asm volatile("{\n.reg .pred p;\n.reg .b32 n;\nsetp.ne.u32 p, %0, 0;\nvote.sync.all.pred p, p, 0xffffffff;\n@p bra.uni WDONE;\nmov.u32 n, 0;\n"
               "WLOOP:\nmbarrier.try_wait.parity.shared::cta.b64 p, [%1], %2;\n@p bra.uni WDONE;\nadd.u32 n, n, 1;\nsetp.lt.u32 p, n, %3;\n@p bra.uni WLOOP;\ntrap;\nWDONE:\n}"
               :: "r"(ready), "r"(bar), "r"(parity), "n"(SPIN_LIMIT) : "memory");
}
__device__ __forceinline__ unsigned load_epoch() {
  unsigned long long d; asm volatile("ld.relaxed.gpu.global.u64 %0, [%1];" : "=l"(d) : "l"(&g_flags.done) : "memory");
  return (unsigned)(d >> LOG_DONE);
}
__device__ __forceinline__ void flag_wait(const unsigned* f, unsigned count, unsigned epoch) {
  const unsigned target = (epoch + 1) * count;
  uint32_t n = 0;
  while (true) {
    unsigned v;
    asm volatile("ld.acquire.gpu.global.u32 %0, [%1];" : "=r"(v) : "l"(f) : "memory");
    if ((int)(v - target) >= 0) break;
    if (++n > SPIN_LIMIT) __trap();
    __nanosleep(20);
  }
}
__device__ __forceinline__ void flag_wait_slow(const unsigned* f, unsigned count, unsigned epoch) {
  const unsigned target = (epoch + 1) * count;
  uint32_t n = 0;
  while (true) {
    unsigned v;
    asm volatile("ld.acquire.gpu.global.u32 %0, [%1];" : "=r"(v) : "l"(f) : "memory");
    if ((int)(v - target) >= 0) break;
    if (++n > SPIN_LIMIT / 16) __trap();
    __nanosleep(1000);
  }
}
__device__ __forceinline__ void cta_done(unsigned long long n) { asm volatile("red.relaxed.gpu.global.add.u64 [%0], %1;" :: "l"(&g_flags.done), "l"(n) : "memory"); }
__device__ __forceinline__ void flag_wait_fast(const unsigned* f, unsigned count, unsigned epoch) {
  const unsigned target = (epoch + 1) * count;
  uint32_t n = 0;
  while (true) {
    unsigned v;
    asm volatile("ld.acquire.gpu.global.u32 %0, [%1];" : "=r"(v) : "l"(f) : "memory");
    if ((int)(v - target) >= 0) break;
    if (++n > SPIN_LIMIT) __trap();
  }
}
__device__ __forceinline__ void fence_async_all() { asm volatile("fence.proxy.async.global;" ::: "memory"); }
__device__ __forceinline__ void flag_signal(unsigned* f) { asm volatile("red.release.gpu.global.add.u32 [%0], 1;" :: "l"(f) : "memory"); }
__device__ __forceinline__ void flag_signal_after_bulk(unsigned* f) {
  asm volatile("red.relaxed.gpu.global.add.u32 [%0], 1;" :: "l"(f) : "memory");
}
__device__ __forceinline__ void fence_async_smem() { asm volatile("fence.proxy.async.shared::cta;" ::: "memory"); }
#define HINTS 40
constexpr uint64_t POL_NORMAL = 0x1000000000000000ull, POL_FIRST = 0x12F0000000000000ull;
__device__ __forceinline__ constexpr uint64_t pol(bool first) { return first ? POL_FIRST : POL_NORMAL; }
__device__ __forceinline__ void tma_ld2(uint32_t dst, const CUtensorMap* m, uint32_t bar, int c0, int c1, uint64_t pl = POL_NORMAL) {
  asm volatile("cp.async.bulk.tensor.2d.shared::cluster.global.mbarrier::complete_tx::bytes.L2::cache_hint [%0], [%1, {%3, %4}], [%2], %5;"
               :: "r"(dst), "l"(m), "r"(bar), "r"(c0), "r"(c1), "l"(pl) : "memory");
}
__device__ __forceinline__ void tma_ld3(uint32_t dst, const CUtensorMap* m, uint32_t bar, int c0, int c1, int c2, uint64_t pl = POL_NORMAL) {
  asm volatile("cp.async.bulk.tensor.3d.shared::cluster.global.mbarrier::complete_tx::bytes.L2::cache_hint [%0], [%1, {%3, %4, %5}], [%2], %6;"
               :: "r"(dst), "l"(m), "r"(bar), "r"(c0), "r"(c1), "r"(c2), "l"(pl) : "memory");
}
__device__ __forceinline__ void tma_ld3_mc(uint32_t dst, const CUtensorMap* m, uint32_t bar, int c0, int c1, int c2, uint64_t pl = POL_NORMAL) {
  asm volatile("cp.async.bulk.tensor.3d.shared::cluster.global.mbarrier::complete_tx::bytes.multicast::cluster.L2::cache_hint [%0], [%1, {%3, %4, %5}], [%2], %6, %7;"
               :: "r"(dst), "l"(m), "r"(bar), "r"(c0), "r"(c1), "r"(c2), "h"((uint16_t)3), "l"(pl) : "memory");
}
__device__ __forceinline__ void bulk_ld(uint32_t dst, const void* src, uint32_t bytes, uint32_t bar) {
  asm volatile("cp.async.bulk.shared::cluster.global.mbarrier::complete_tx::bytes [%0], [%1], %2, [%3];"
               :: "r"(dst), "l"(src), "r"(bytes), "r"(bar) : "memory");
}
__device__ __forceinline__ void bulk_ld_p(uint32_t dst, const void* src, uint32_t bytes, uint32_t bar, uint64_t pl) {
  asm volatile("cp.async.bulk.shared::cluster.global.mbarrier::complete_tx::bytes.L2::cache_hint [%0], [%1], %2, [%3], %4;"
               :: "r"(dst), "l"(src), "r"(bytes), "r"(bar), "l"(pl) : "memory");
}
__device__ __forceinline__ void bulk_ld_mc(uint32_t dst, const void* src, uint32_t bytes, uint32_t bar, uint64_t pl) {
  asm volatile("cp.async.bulk.shared::cluster.global.mbarrier::complete_tx::bytes.multicast::cluster.L2::cache_hint [%0], [%1], %2, [%3], %4, %5;"
               :: "r"(dst), "l"(src), "r"(bytes), "r"(bar), "h"((uint16_t)3), "l"(pl) : "memory");
}
__device__ __forceinline__ void tma_st3(const CUtensorMap* m, uint32_t src, int c0, int c1, int c2) {
  asm volatile("cp.async.bulk.tensor.3d.global.shared::cta.bulk_group.L2::cache_hint [%0, {%2, %3, %4}], [%1], %5;"
               :: "l"(m), "r"(src), "r"(c0), "r"(c1), "r"(c2), "l"(pol(HINTS & 1024)) : "memory");
}
__device__ __forceinline__ void tma_ld2_mc(uint32_t dst, const CUtensorMap* m, uint32_t bar, int c0, int c1, uint64_t pl = POL_NORMAL) {
  asm volatile("cp.async.bulk.tensor.2d.shared::cluster.global.mbarrier::complete_tx::bytes.multicast::cluster.L2::cache_hint [%0], [%1, {%3, %4}], [%2], %5, %6;"
               :: "r"(dst), "l"(m), "r"(bar), "r"(c0), "r"(c1), "h"((uint16_t)3), "l"(pl) : "memory");
}
__device__ __forceinline__ void tma_ld5_mc(uint32_t dst, const CUtensorMap* m, uint32_t bar, int c0, int c4, uint64_t pl = POL_NORMAL) {
  asm volatile("cp.async.bulk.tensor.5d.shared::cluster.global.mbarrier::complete_tx::bytes.multicast::cluster.L2::cache_hint [%0], [%1, {%3, %7, %7, %7, %4}], [%2], %5, %6;"
               :: "r"(dst), "l"(m), "r"(bar), "r"(c0), "r"(c4), "h"((uint16_t)3), "l"(pl), "r"(0) : "memory");
}
__device__ __forceinline__ void tma_st2(const CUtensorMap* m, uint32_t src, int c0, int c1) {
  asm volatile("cp.async.bulk.tensor.2d.global.shared::cta.bulk_group [%0, {%2, %3}], [%1];"
               :: "l"(m), "r"(src), "r"(c0), "r"(c1) : "memory");
}
__device__ __forceinline__ void tma_red2(const CUtensorMap* m, uint32_t src, int c0, int c1) {
  asm volatile("cp.reduce.async.bulk.tensor.2d.global.shared::cta.add.bulk_group [%0, {%2, %3}], [%1];"
               :: "l"(m), "r"(src), "r"(c0), "r"(c1) : "memory");
}
__device__ __forceinline__ void bulk_commit() { asm volatile("cp.async.bulk.commit_group;" ::: "memory"); }
__device__ __forceinline__ void bulk_wait_read() { asm volatile("cp.async.bulk.wait_group.read 0;" ::: "memory"); }
__device__ __forceinline__ void bulk_wait_all() { asm volatile("cp.async.bulk.wait_group 0;" ::: "memory"); }
__device__ __forceinline__ void prefetch_map(const CUtensorMap* m) { asm volatile("prefetch.tensormap [%0];" :: "l"(m) : "memory"); }
__device__ __forceinline__ void wg_fence() { asm volatile("wgmma.fence.sync.aligned;" ::: "memory"); }
__device__ __forceinline__ void wg_commit() { asm volatile("wgmma.commit_group.sync.aligned;" ::: "memory"); }
template <int N> __device__ __forceinline__ void wg_wait() { asm volatile("wgmma.wait_group.sync.aligned %0;" :: "n"(N) : "memory"); }
template <int N> __device__ __forceinline__ void reg_fence(float (&d)[N]) {
#pragma unroll
  for (int i = 0; i < N; i++) asm volatile("" : "+f"(d[i]) :: "memory");
}
template <int N> __device__ __forceinline__ void reg_fence(uint32_t (&d)[N]) {
#pragma unroll
  for (int i = 0; i < N; i++) asm volatile("" : "+r"(d[i]) :: "memory");
}
__device__ __forceinline__ uint32_t fresh_tid() { uint32_t t; asm volatile("mov.u32 %0, %%tid.x;" : "=r"(t)); return t; }
__device__ __forceinline__ uint32_t lane_base16() {
  const uint32_t t = fresh_tid(), lane = t & 31, wq = (t >> 5) & 3;
  return (16 * wq + (lane & 7) + 8 * ((lane >> 3) & 1)) * 128 + (((lane >> 4) ^ (lane & 7)) << 4);
}
__device__ __forceinline__ void named_sync(int id, int n) { asm volatile("bar.sync %0, %1;" :: "r"(id), "r"(n) : "memory"); }
__device__ __forceinline__ void named_arrive(int id, int n) { asm volatile("bar.arrive %0, %1;" :: "r"(id), "r"(n) : "memory"); }
__device__ __forceinline__ uint32_t pack_bf16(float lo, float hi) {
  uint32_t r; asm("cvt.rn.bf16x2.f32 %0, %1, %2;" : "=r"(r) : "f"(hi), "f"(lo)); return r;
}
__device__ __forceinline__ float ex2(float x) { float y; asm("ex2.approx.ftz.f32 %0, %1;" : "=f"(y) : "f"(x)); return y; }
__device__ __forceinline__ void stsm4(uint32_t addr, uint32_t a, uint32_t b, uint32_t c, uint32_t d) {
  asm volatile("stmatrix.sync.aligned.m8n8.x4.shared.b16 [%0], {%1, %2, %3, %4};" :: "r"(addr), "r"(a), "r"(b), "r"(c), "r"(d) : "memory");
}
__device__ __forceinline__ uint64_t mk_desc(uint32_t addr, uint32_t lbo, uint32_t sbo) {
  return (uint64_t)(((addr & 0x3FFFF) >> 4) | ((lbo >> 4) << 16)) | ((uint64_t)((sbo >> 4) | (1u << 30)) << 32);
}
__device__ __forceinline__ uint64_t desc_k(uint32_t addr)  { return mk_desc(addr, 16, 1024); }
__device__ __forceinline__ uint64_t desc_mn(uint32_t addr) { return mk_desc(addr, 8192, 1024); }
__device__ __forceinline__ uint64_t desc_64(uint32_t addr) { return (uint64_t)(((addr & 0x3FFFF) >> 4) | ((4096u >> 4) << 16)) | ((uint64_t)((512u >> 4) | (2u << 30)) << 32); }
__device__ __forceinline__ uint64_t desc_add(uint64_t d, uint32_t bytes) { return d + (bytes >> 4); }

__device__ __forceinline__ void wgmma_ss_n256_tb(float (&d)[128], uint64_t da, uint64_t db, int sd) {
  asm volatile("{\n.reg .pred p;\nsetp.ne.b32 p, %130, 0;\n"
    "wgmma.mma_async.sync.aligned.m64n256k16.f32.bf16.bf16 "
    "{%0, %1, %2, %3, %4, %5, %6, %7, %8, %9, %10, %11, %12, %13, %14, %15, "
    "%16, %17, %18, %19, %20, %21, %22, %23, %24, %25, %26, %27, %28, %29, %30, %31, "
    "%32, %33, %34, %35, %36, %37, %38, %39, %40, %41, %42, %43, %44, %45, %46, %47, "
    "%48, %49, %50, %51, %52, %53, %54, %55, %56, %57, %58, %59, %60, %61, %62, %63, "
    "%64, %65, %66, %67, %68, %69, %70, %71, %72, %73, %74, %75, %76, %77, %78, %79, "
    "%80, %81, %82, %83, %84, %85, %86, %87, %88, %89, %90, %91, %92, %93, %94, %95, "
    "%96, %97, %98, %99, %100, %101, %102, %103, %104, %105, %106, %107, %108, %109, %110, %111, "
    "%112, %113, %114, %115, %116, %117, %118, %119, %120, %121, %122, %123, %124, %125, %126, %127}, "
    "%128, %129, p, 1, 1, 0, 1;\n}"
    : "+f"(d[0]), "+f"(d[1]), "+f"(d[2]), "+f"(d[3]), "+f"(d[4]), "+f"(d[5]), "+f"(d[6]), "+f"(d[7]),
      "+f"(d[8]), "+f"(d[9]), "+f"(d[10]), "+f"(d[11]), "+f"(d[12]), "+f"(d[13]), "+f"(d[14]), "+f"(d[15]),
      "+f"(d[16]), "+f"(d[17]), "+f"(d[18]), "+f"(d[19]), "+f"(d[20]), "+f"(d[21]), "+f"(d[22]), "+f"(d[23]),
      "+f"(d[24]), "+f"(d[25]), "+f"(d[26]), "+f"(d[27]), "+f"(d[28]), "+f"(d[29]), "+f"(d[30]), "+f"(d[31]),
      "+f"(d[32]), "+f"(d[33]), "+f"(d[34]), "+f"(d[35]), "+f"(d[36]), "+f"(d[37]), "+f"(d[38]), "+f"(d[39]),
      "+f"(d[40]), "+f"(d[41]), "+f"(d[42]), "+f"(d[43]), "+f"(d[44]), "+f"(d[45]), "+f"(d[46]), "+f"(d[47]),
      "+f"(d[48]), "+f"(d[49]), "+f"(d[50]), "+f"(d[51]), "+f"(d[52]), "+f"(d[53]), "+f"(d[54]), "+f"(d[55]),
      "+f"(d[56]), "+f"(d[57]), "+f"(d[58]), "+f"(d[59]), "+f"(d[60]), "+f"(d[61]), "+f"(d[62]), "+f"(d[63]),
      "+f"(d[64]), "+f"(d[65]), "+f"(d[66]), "+f"(d[67]), "+f"(d[68]), "+f"(d[69]), "+f"(d[70]), "+f"(d[71]),
      "+f"(d[72]), "+f"(d[73]), "+f"(d[74]), "+f"(d[75]), "+f"(d[76]), "+f"(d[77]), "+f"(d[78]), "+f"(d[79]),
      "+f"(d[80]), "+f"(d[81]), "+f"(d[82]), "+f"(d[83]), "+f"(d[84]), "+f"(d[85]), "+f"(d[86]), "+f"(d[87]),
      "+f"(d[88]), "+f"(d[89]), "+f"(d[90]), "+f"(d[91]), "+f"(d[92]), "+f"(d[93]), "+f"(d[94]), "+f"(d[95]),
      "+f"(d[96]), "+f"(d[97]), "+f"(d[98]), "+f"(d[99]), "+f"(d[100]), "+f"(d[101]), "+f"(d[102]), "+f"(d[103]),
      "+f"(d[104]), "+f"(d[105]), "+f"(d[106]), "+f"(d[107]), "+f"(d[108]), "+f"(d[109]), "+f"(d[110]), "+f"(d[111]),
      "+f"(d[112]), "+f"(d[113]), "+f"(d[114]), "+f"(d[115]), "+f"(d[116]), "+f"(d[117]), "+f"(d[118]), "+f"(d[119]),
      "+f"(d[120]), "+f"(d[121]), "+f"(d[122]), "+f"(d[123]), "+f"(d[124]), "+f"(d[125]), "+f"(d[126]), "+f"(d[127])
    : "l"(da), "l"(db), "r"(sd));
}
__device__ __forceinline__ void wgmma_ss_n64(float (&d)[32], uint64_t da, uint64_t db, int sd) {
  asm volatile("{\n.reg .pred p;\nsetp.ne.b32 p, %34, 0;\n"
    "wgmma.mma_async.sync.aligned.m64n64k16.f32.bf16.bf16 "
    "{%0, %1, %2, %3, %4, %5, %6, %7, %8, %9, %10, %11, %12, %13, %14, %15, "
    "%16, %17, %18, %19, %20, %21, %22, %23, %24, %25, %26, %27, %28, %29, %30, %31}, "
    "%32, %33, p, 1, 1, 0, 0;\n}"
    : "+f"(d[0]), "+f"(d[1]), "+f"(d[2]), "+f"(d[3]), "+f"(d[4]), "+f"(d[5]), "+f"(d[6]), "+f"(d[7]),
      "+f"(d[8]), "+f"(d[9]), "+f"(d[10]), "+f"(d[11]), "+f"(d[12]), "+f"(d[13]), "+f"(d[14]), "+f"(d[15]),
      "+f"(d[16]), "+f"(d[17]), "+f"(d[18]), "+f"(d[19]), "+f"(d[20]), "+f"(d[21]), "+f"(d[22]), "+f"(d[23]),
      "+f"(d[24]), "+f"(d[25]), "+f"(d[26]), "+f"(d[27]), "+f"(d[28]), "+f"(d[29]), "+f"(d[30]), "+f"(d[31])
    : "l"(da), "l"(db), "r"(sd));
}
__device__ __forceinline__ void wgmma_rs_n256_tb(float (&d)[128], uint32_t a0, uint32_t a1, uint32_t a2, uint32_t a3, uint64_t db, int sd) {
  asm volatile("{\n.reg .pred p;\nsetp.ne.b32 p, %133, 0;\n"
    "wgmma.mma_async.sync.aligned.m64n256k16.f32.bf16.bf16 "
    "{%0, %1, %2, %3, %4, %5, %6, %7, %8, %9, %10, %11, %12, %13, %14, %15, "
    "%16, %17, %18, %19, %20, %21, %22, %23, %24, %25, %26, %27, %28, %29, %30, %31, "
    "%32, %33, %34, %35, %36, %37, %38, %39, %40, %41, %42, %43, %44, %45, %46, %47, "
    "%48, %49, %50, %51, %52, %53, %54, %55, %56, %57, %58, %59, %60, %61, %62, %63, "
    "%64, %65, %66, %67, %68, %69, %70, %71, %72, %73, %74, %75, %76, %77, %78, %79, "
    "%80, %81, %82, %83, %84, %85, %86, %87, %88, %89, %90, %91, %92, %93, %94, %95, "
    "%96, %97, %98, %99, %100, %101, %102, %103, %104, %105, %106, %107, %108, %109, %110, %111, "
    "%112, %113, %114, %115, %116, %117, %118, %119, %120, %121, %122, %123, %124, %125, %126, %127}, "
    "{%128, %129, %130, %131}, %132, p, 1, 1, 1;\n}"
    : "+f"(d[0]), "+f"(d[1]), "+f"(d[2]), "+f"(d[3]), "+f"(d[4]), "+f"(d[5]), "+f"(d[6]), "+f"(d[7]),
      "+f"(d[8]), "+f"(d[9]), "+f"(d[10]), "+f"(d[11]), "+f"(d[12]), "+f"(d[13]), "+f"(d[14]), "+f"(d[15]),
      "+f"(d[16]), "+f"(d[17]), "+f"(d[18]), "+f"(d[19]), "+f"(d[20]), "+f"(d[21]), "+f"(d[22]), "+f"(d[23]),
      "+f"(d[24]), "+f"(d[25]), "+f"(d[26]), "+f"(d[27]), "+f"(d[28]), "+f"(d[29]), "+f"(d[30]), "+f"(d[31]),
      "+f"(d[32]), "+f"(d[33]), "+f"(d[34]), "+f"(d[35]), "+f"(d[36]), "+f"(d[37]), "+f"(d[38]), "+f"(d[39]),
      "+f"(d[40]), "+f"(d[41]), "+f"(d[42]), "+f"(d[43]), "+f"(d[44]), "+f"(d[45]), "+f"(d[46]), "+f"(d[47]),
      "+f"(d[48]), "+f"(d[49]), "+f"(d[50]), "+f"(d[51]), "+f"(d[52]), "+f"(d[53]), "+f"(d[54]), "+f"(d[55]),
      "+f"(d[56]), "+f"(d[57]), "+f"(d[58]), "+f"(d[59]), "+f"(d[60]), "+f"(d[61]), "+f"(d[62]), "+f"(d[63]),
      "+f"(d[64]), "+f"(d[65]), "+f"(d[66]), "+f"(d[67]), "+f"(d[68]), "+f"(d[69]), "+f"(d[70]), "+f"(d[71]),
      "+f"(d[72]), "+f"(d[73]), "+f"(d[74]), "+f"(d[75]), "+f"(d[76]), "+f"(d[77]), "+f"(d[78]), "+f"(d[79]),
      "+f"(d[80]), "+f"(d[81]), "+f"(d[82]), "+f"(d[83]), "+f"(d[84]), "+f"(d[85]), "+f"(d[86]), "+f"(d[87]),
      "+f"(d[88]), "+f"(d[89]), "+f"(d[90]), "+f"(d[91]), "+f"(d[92]), "+f"(d[93]), "+f"(d[94]), "+f"(d[95]),
      "+f"(d[96]), "+f"(d[97]), "+f"(d[98]), "+f"(d[99]), "+f"(d[100]), "+f"(d[101]), "+f"(d[102]), "+f"(d[103]),
      "+f"(d[104]), "+f"(d[105]), "+f"(d[106]), "+f"(d[107]), "+f"(d[108]), "+f"(d[109]), "+f"(d[110]), "+f"(d[111]),
      "+f"(d[112]), "+f"(d[113]), "+f"(d[114]), "+f"(d[115]), "+f"(d[116]), "+f"(d[117]), "+f"(d[118]), "+f"(d[119]),
      "+f"(d[120]), "+f"(d[121]), "+f"(d[122]), "+f"(d[123]), "+f"(d[124]), "+f"(d[125]), "+f"(d[126]), "+f"(d[127])
    : "r"(a0), "r"(a1), "r"(a2), "r"(a3), "l"(db), "r"(sd));
}
__device__ __forceinline__ void wgmma_rs_n64_tb(float (&d)[32], uint32_t a0, uint32_t a1, uint32_t a2, uint32_t a3, uint64_t db, int sd) {
  asm volatile("{\n.reg .pred p;\nsetp.ne.b32 p, %37, 0;\n"
    "wgmma.mma_async.sync.aligned.m64n64k16.f32.bf16.bf16 "
    "{%0, %1, %2, %3, %4, %5, %6, %7, %8, %9, %10, %11, %12, %13, %14, %15, "
    "%16, %17, %18, %19, %20, %21, %22, %23, %24, %25, %26, %27, %28, %29, %30, %31}, "
    "{%32, %33, %34, %35}, %36, p, 1, 1, 1;\n}"
    : "+f"(d[0]), "+f"(d[1]), "+f"(d[2]), "+f"(d[3]), "+f"(d[4]), "+f"(d[5]), "+f"(d[6]), "+f"(d[7]),
      "+f"(d[8]), "+f"(d[9]), "+f"(d[10]), "+f"(d[11]), "+f"(d[12]), "+f"(d[13]), "+f"(d[14]), "+f"(d[15]),
      "+f"(d[16]), "+f"(d[17]), "+f"(d[18]), "+f"(d[19]), "+f"(d[20]), "+f"(d[21]), "+f"(d[22]), "+f"(d[23]),
      "+f"(d[24]), "+f"(d[25]), "+f"(d[26]), "+f"(d[27]), "+f"(d[28]), "+f"(d[29]), "+f"(d[30]), "+f"(d[31])
    : "r"(a0), "r"(a1), "r"(a2), "r"(a3), "l"(db), "r"(sd));
}
__device__ __forceinline__ void wgmma_rs_n32(float (&d)[16], uint32_t a0, uint32_t a1, uint32_t a2, uint32_t a3, uint64_t db, int sd) {
  asm volatile("{\n.reg .pred p;\nsetp.ne.b32 p, %21, 0;\n"
    "wgmma.mma_async.sync.aligned.m64n32k16.f32.bf16.bf16 "
    "{%0, %1, %2, %3, %4, %5, %6, %7, %8, %9, %10, %11, %12, %13, %14, %15}, "
    "{%16, %17, %18, %19}, %20, p, 1, 1, 0;\n}"
    : "+f"(d[0]), "+f"(d[1]), "+f"(d[2]), "+f"(d[3]), "+f"(d[4]), "+f"(d[5]), "+f"(d[6]), "+f"(d[7]),
      "+f"(d[8]), "+f"(d[9]), "+f"(d[10]), "+f"(d[11]), "+f"(d[12]), "+f"(d[13]), "+f"(d[14]), "+f"(d[15])
    : "r"(a0), "r"(a1), "r"(a2), "r"(a3), "l"(db), "r"(sd));
}
__device__ __forceinline__ void wgmma_rs_n64(float (&d)[32], uint32_t a0, uint32_t a1, uint32_t a2, uint32_t a3, uint64_t db, int sd) {
  asm volatile("{\n.reg .pred p;\nsetp.ne.b32 p, %37, 0;\n"
    "wgmma.mma_async.sync.aligned.m64n64k16.f32.bf16.bf16 "
    "{%0, %1, %2, %3, %4, %5, %6, %7, %8, %9, %10, %11, %12, %13, %14, %15, "
    "%16, %17, %18, %19, %20, %21, %22, %23, %24, %25, %26, %27, %28, %29, %30, %31}, "
    "{%32, %33, %34, %35}, %36, p, 1, 1, 0;\n}"
    : "+f"(d[0]), "+f"(d[1]), "+f"(d[2]), "+f"(d[3]), "+f"(d[4]), "+f"(d[5]), "+f"(d[6]), "+f"(d[7]),
      "+f"(d[8]), "+f"(d[9]), "+f"(d[10]), "+f"(d[11]), "+f"(d[12]), "+f"(d[13]), "+f"(d[14]), "+f"(d[15]),
      "+f"(d[16]), "+f"(d[17]), "+f"(d[18]), "+f"(d[19]), "+f"(d[20]), "+f"(d[21]), "+f"(d[22]), "+f"(d[23]),
      "+f"(d[24]), "+f"(d[25]), "+f"(d[26]), "+f"(d[27]), "+f"(d[28]), "+f"(d[29]), "+f"(d[30]), "+f"(d[31])
    : "r"(a0), "r"(a1), "r"(a2), "r"(a3), "l"(db), "r"(sd));
}

__device__ __forceinline__ uint4 lds16(uint32_t a) {
  uint4 v; asm volatile("ld.shared.v4.u32 {%0, %1, %2, %3}, [%4];" : "=r"(v.x), "=r"(v.y), "=r"(v.z), "=r"(v.w) : "r"(a) : "memory"); return v;
}
__device__ __forceinline__ void sts16(uint32_t a, uint32_t x, uint32_t y, uint32_t z, uint32_t w) {
  asm volatile("st.shared.v4.u32 [%0], {%1, %2, %3, %4};" :: "r"(a), "r"(x), "r"(y), "r"(z), "r"(w) : "memory");
}
__device__ __forceinline__ uint32_t lds4(uint32_t a) { uint32_t v; asm volatile("ld.shared.u32 %0, [%1];" : "=r"(v) : "r"(a) : "memory"); return v; }
__device__ __forceinline__ uint32_t lds4v(uint32_t a) { uint32_t v; asm volatile("ld.volatile.shared.u32 %0, [%1];" : "=r"(v) : "r"(a) : "memory"); return v; }
__device__ __forceinline__ uint32_t bmul(uint32_t a, uint32_t b) { uint32_t r; asm("mul.rn.bf16x2 %0, %1, %2;" : "=r"(r) : "r"(a), "r"(b)); return r; }
__device__ __forceinline__ uint32_t badd(uint32_t a, uint32_t b) { uint32_t r; asm("add.rn.bf16x2 %0, %1, %2;" : "=r"(r) : "r"(a), "r"(b)); return r; }

__device__ __forceinline__ void ldsm4(uint32_t (&r)[4], uint32_t a) {
  asm volatile("ldmatrix.sync.aligned.m8n8.x4.shared.b16 {%0, %1, %2, %3}, [%4];" : "=r"(r[0]), "=r"(r[1]), "=r"(r[2]), "=r"(r[3]) : "r"(a) : "memory");
}
__device__ __forceinline__ uint32_t transpose8(uint32_t a) { uint32_t d; asm volatile("movmatrix.sync.aligned.m8n8.trans.b16 %0, %1;" : "=r"(d) : "r"(a)); return d; }

__device__ __forceinline__ void mma16816(float (&d)[4], const uint32_t (&a)[4], uint32_t b0, uint32_t b1) {
  asm volatile("mma.sync.aligned.m16n8k16.row.col.f32.bf16.bf16.f32 {%0, %1, %2, %3}, {%4, %5, %6, %7}, {%8, %9}, {%0, %1, %2, %3};"
               : "+f"(d[0]), "+f"(d[1]), "+f"(d[2]), "+f"(d[3]) : "r"(a[0]), "r"(a[1]), "r"(a[2]), "r"(a[3]), "r"(b0), "r"(b1));
}

#define EXP_SIDE 0
#define SIDE_AHEAD 3
#define ZERO_RD 4
#define CTX_SPLIT 8
#define CONV_EARLY 8
#define CONV_FENCE 12
#define CTX_LD 16
#define PF_Q 0
#define HOOK_DEP s[4 * jj]
#define PEEK_JJ 7
#define PF_GAP 500
#define PF_CTX 2
#define STG_PAT 1
#define KV_ORDER 3
#define QFIRST 0
#define UNICAST 2
#define CONV_ARRIVE 13
#define ARRIVE_KK 12
#define SIDE_DELAY_NS 4000
#define KVH(h) (h)
#define HEAD_MAP 2
#define EARLY_LD 3
constexpr int RED_BAR = 6;
constexpr int CV_BAR = 5;
constexpr int PP_BAR = 3;
template <int V> struct Int { static constexpr int value = V; };
struct Ring {
  uint32_t slot, phase;
  __device__ __forceinline__ void next() { if (++slot == NSLOT) { slot = 0; phase ^= 1; } }
};
__device__ __forceinline__ uint32_t bar_addr(uint32_t sb, uint32_t i) { return sb + BARS + 8 * i; }

__device__ __forceinline__ int q_tile(int h, int j, int which) { return ((h < 8) == (which == 0)) ? 15 - j : j; }

constexpr int T_QB = QFIRST ? 0 : 4, IT_KV = QFIRST ? 7 : 0, IT_QB = QFIRST ? 0 : 64;
constexpr int KV_ISV  = KV_ORDER == 0 ? 0xC : KV_ORDER == 1 ? 0xA : KV_ORDER == 2 ? 0x6 : KV_ORDER == 3 ? 0xA : 0xC;
constexpr int KV_PART = KV_ORDER == 0 ? 0xA : KV_ORDER == 1 ? 0xC : KV_ORDER == 2 ? 0xC : KV_ORDER == 3 ? 0x3 : KV_ORDER == 4 ? 0x5 : 0x9;
constexpr int LAST_PART = KV_PART >> 3;
constexpr int T_FIRST = (((KV_PART >> 2) & 1) != LAST_PART ? 3 : 2) + QFIRST;
constexpr int T_LAST = 4 + QFIRST;
__device__ __forceinline__ int p1_isv(int n) { return (KV_ISV >> n) & 1; }
__device__ __forceinline__ int att_head(int h, int which) { return (h & 7) + 8 * which; }
__device__ __forceinline__ int p1_head(int h, int n) { return (h & 7) + 8 * ((KV_PART >> n) & 1); }
__device__ __forceinline__ int p1_rows(int h, int j, int n) { return q_tile(h, j, 0); }
#define KV_FLAG(h) ((h) & 7)
#define KV_COUNT 32
#define F_PART1 (2 * own - 1)

__device__ __forceinline__ void load_tile4(uint32_t dst, const CUtensorMap* m, uint32_t full, int row, int blk0, int rank, bool shared, uint64_t pl = POL_NORMAL) {
  if (shared) {
    tma_ld3_mc(dst + rank * 16384, m, full, 0, row, blk0 + 2 * rank, pl);
  } else {
    tma_ld3(dst, m, full, 0, row, blk0, pl);
    tma_ld3(dst + 16384, m, full, 0, row, blk0 + 2, pl);
  }
}
__device__ __forceinline__ void producer_main(const Params& p, uint32_t sb, int h, int j) {
  const int rank = j & 1;
  Ring r{EARLY_LD, 0};
  auto wait_slot = [&]() { mbar_wait(bar_addr(sb, B_EMPTY + r.slot), r.phase ^ 1); };
  auto load_a = [&](int it, uint32_t dst, uint32_t full) {
    const unsigned u = it - IT_KV;
    if (u < 64) tma_ld2(dst, &p.ckv, full, (u & 15) * 64, p1_rows(h, j, u >> 4) * 128, pol((HINTS & 2) && u >= 48));
    else tma_ld2(dst, &p.x, full, (it < 71 ? it - IT_QB : it - 71) * 64, q_tile(h, j, it < 71) * 128, pol((HINTS & 64) && it >= 71));
  };
  uint32_t prev = 0;
#pragma unroll 1
  for (int it = EARLY_LD; it < P1_STEPS; it++) {
    wait_slot();
    if (it > EARLY_LD && it <= P1_XS) load_a(it - 1, sb + QREG + ((it - 1) & 3) * 16384, prev);
    const uint32_t full = bar_addr(sb, B_FULL + r.slot), dst = sb + r.slot * SLOT;
    mbar_expect_tx(full, it < P1_XS ? 49152 : 32768);
    const unsigned u = it - IT_KV;
    if (u < 64) load_tile4(dst, p1_isv(u >> 4) ? &p.wuv : &p.wuk, full, (u & 15) * 64, p1_head(h, u >> 4) * 4, rank, !(UNICAST & 2), pol(HINTS & 1));
    else load_tile4(dst, &p.wq, full, (it < 71 ? it - IT_QB : it - 71) * 64, att_head(h, it < 71) * 4, rank, !(UNICAST & 2), pol((HINTS & 4) && it >= 71));
    prev = full;
    r.next();
    if (PF_Q && it == PF_Q) mbar_arrive(bar_addr(sb, B_PF));
    if (it == P1_XS) {
      wait_slot();
      const uint32_t f2 = bar_addr(sb, B_FULL + r.slot);
      mbar_expect_tx(f2, 32768);
      load_a(P1_XS, sb + r.slot * SLOT, f2);
      load_a(P1_XS + 1, sb + r.slot * SLOT + 16384, f2);
      r.next();
    }
  }
  const int qa = q_tile(h, j, 0), na = 2 * qa + 2, own = 2 * (qa & ~1) + 2;
#pragma unroll 1
  for (int f = 0; f < 68; f++) {
    const bool isK = (f == 0) || ((f & 1) && f < 67);
    const int i = isK ? (f + 1) >> 1 : (f - 1) >> 1, which = i >= na;
    if (f == 0 || f == F_PART1) mbar_wait(bar_addr(sb, B_KVOK + (f & 1)), 0);
    wait_slot();
    const uint32_t full = bar_addr(sb, B_FULL + r.slot);
    mbar_expect_tx(full, 32768);
    const uint32_t src = (uint32_t)(((isK ? 0 : NH) + KVH(att_head(h, which))) * 32 + (which ? 33 - i : i)) * 32768;
    const uint64_t pl = pol(which ? (HINTS & 32) : (HINTS & 8));
    if (!(UNICAST & 1) && (i & ~1) != own) bulk_ld_mc(sb + r.slot * SLOT + rank * 16384, at<uint8_t>(g_kv, src + rank * 16384), 16384, full, pl);
    else bulk_ld_p(sb + r.slot * SLOT, at<uint8_t>(g_kv, src), 32768, full, pl);
    r.next();
  }
#pragma unroll 1
  for (int f = 0; f < 14; f++) {
    const int ch = f < 12 ? 2 * (f >> 2) + (f & 1) : 6, par = f < 12 ? (f >> 1) & 1 : f & 1;
    wait_slot();
    const uint32_t full = bar_addr(sb, B_FULL + r.slot);
    mbar_expect_tx(full, 32768);
    tma_ld5_mc(sb + r.slot * SLOT + rank * 16384, &p.wo, full, ch * 64, (par ? att_head(h ^ 8, 0) : att_head(h, 1)) * 8 + rank * 4, pol(HINTS & 16));
    r.next();
  }
}

__device__ __forceinline__ void helper_main(const Params& p, uint32_t sb, int h, int j, int w) {
  const unsigned epoch = load_epoch();
  const int cta = h * 8 + j, qb = q_tile(h, j, 1);
  const uint32_t qreg = sb + QREG + w * 32768, qfull = bar_addr(sb, B_QFULL + w);
  auto acquire = [&]() {
    flag_wait(flag_at(g_flags.kv_ready, KV_FLAG(h) * 2 + w), KV_COUNT, epoch);
    fence_async_all();
    mbar_arrive(bar_addr(sb, B_KVOK + w));
  };
  if (QFIRST) mbar_wait(bar_addr(sb, B_ST_Q + w), 0);
  mbar_wait(bar_addr(sb, B_ST_KV + w), 0);
  flag_signal(flag_at(g_flags.kv_ready, KV_FLAG(h) * 2 + (LAST_PART ^ 1)));
  if (w != LAST_PART) acquire();
  mbar_wait(bar_addr(sb, B_ST_KV + 2 + w), 0);
  flag_signal(flag_at(g_flags.kv_ready, KV_FLAG(h) * 2 + LAST_PART));
  const bool late = false;
  if (w == LAST_PART && !late) acquire();
  if (!QFIRST) { mbar_wait(bar_addr(sb, B_ST_Q + w), 0); asm volatile("fence.release.gpu;" ::: "memory"); }
  fence_async_all();
  mbar_wait(bar_addr(sb, B_QFREE + w), 0);
  mbar_expect_tx(qfull, 32768);
  bulk_ld(qreg, at<uint8_t>(g_qc, (cta * 2 + w) * 32768), 32768, qfull);
  if (w == LAST_PART && late) acquire();
  auto publish = [&]() { mbar_wait(bar_addr(sb, B_ST_CTX + w), 0); flag_signal(flag_at(g_flags.ctx_ready, cta * 2 + w)); };
  if (qb >= 8) publish();
  flag_wait(flag_at(g_flags.ctx_ready, (cta ^ 64) * 2 + (w ^ 1)), 1, epoch);
  mbar_arrive(bar_addr(sb, B_CTXOK + w));
  if (qb < 8) publish();
  flag_wait(flag_at(g_flags.zero_ready, qb), 8, epoch);
  fence_async_all();
#pragma unroll 1
  for (int ch = 0; ch < 7; ch++) {
    mbar_wait(bar_addr(sb, B_S2_FULL + w * 4 + (ch & 3)), ch >> 2);
    tma_red2(&p.o, qreg + (ch & 3) * 8192, DA + ch * 64, qb * 128 + (w ^ 1) * 64);
    bulk_commit();
    if (ch < 3) { bulk_wait_read(); mbar_arrive(bar_addr(sb, B_S2_EMPTY + w * 4 + ch)); }
  }
  bulk_wait_read();
  GT(48 + w);
}

__device__ __forceinline__ void store_block(uint32_t base, uint32_t lanebase, const uint32_t (&pk)[16]) {
#pragma unroll
  for (int J = 0; J < 8; J += 2) stsm4(base + (lanebase ^ (J << 4)), pk[2 * J], pk[2 * J + 1], pk[2 * J + 2], pk[2 * J + 3]);
}
__device__ __forceinline__ void pack_chunks(uint32_t (&pk)[64], const float (&acc)[128]) {
#pragma unroll
  for (int i = 0; i < 64; i++) { const int e = 16 * (i >> 3) + 4 * (i & 3) + 2 * ((i >> 2) & 1); pk[i] = pack_bf16(acc[e], acc[e + 1]); }
}
__device__ __forceinline__ uint32_t chunk_off() { const uint32_t t = fresh_tid(); return (t & 96) * 32 + (t & 28) * 16 + (((t ^ (t >> 3)) & 3) << 4); }
__device__ __forceinline__ void warp_arrive(uint32_t bar, int lane) { __syncwarp(); if (lane == 0) mbar_arrive(bar); }

__device__ __forceinline__ void consumer_main(const Params& p, uint32_t sb, int h, int j, int w, int wq) {
  const int lane = threadIdx.x & 31;
  const int rank = j & 1;

  auto turn_begin = [&]() { named_sync(PP_BAR + w, 256); };
  auto turn_end = [&]() { named_arrive(PP_BAR + (w ^ 1), 256); };
  if (w == 1) named_arrive(PP_BAR, 256);
  Ring r{0, 0};
  auto take = [&](uint32_t ready = 0) { const uint32_t sl = r.slot; mbar_wait_unless(ready, bar_addr(sb, B_FULL + sl), r.phase); r.next(); return sl; };
  uint32_t rdy0 = 0, rdy1 = 0;
  auto peek2 = [&]() { Ring q = r; rdy0 = mbar_test(bar_addr(sb, B_FULL + q.slot), q.phase); q.next(); rdy1 = mbar_test(bar_addr(sb, B_FULL + q.slot), q.phase); };
  auto give = [&](uint32_t sl) { if (lane < 2) mbar_arrive_remote(bar_addr(sb, B_EMPTY + sl), rank ^ lane); };
  float acc[128];
#pragma unroll
  for (int i = 0; i < 128; i++) acc[i] = 0.f;
  uint32_t pk[64];
#pragma unroll
  for (int i = 0; i < 64; i++) pk[i] = 0;
  TS(0);
  const uint32_t qreg = sb + QREG + w * 32768;
  {
    uint32_t xs = 0, prev = 0;
    uint4* row = nullptr;
    int it = 0;
#pragma unroll 1
    for (int t = 0; t < 6; t++) {
      const int nk = (t == T_QB || t == 5) ? 7 : 16;
#pragma unroll 1
      for (int k = 0; k < nk; k++, it++) {
        const uint32_t ws = take(rdy0);
        TSC(1, it == 0);
        if (it == P1_XS) xs = take();
        const uint32_t aa = (it < P1_XS ? QREG + (it & 3) * 16384 : xs * SLOT + (it - P1_XS) * 16384) + (w ^ (t == T_QB)) * 8192;
        const uint64_t da = desc_k(sb + aa), db = desc_mn(sb + ws * SLOT);
        turn_begin();
        wg_fence();
#pragma unroll
        for (int kk = 0; kk < 4; kk++) wgmma_ss_n256_tb(acc, desc_add(da, kk * 32), desc_add(db, kk * 2048), (k | kk) != 0);
        wg_commit();
        turn_end();
        rdy0 = mbar_test(bar_addr(sb, B_FULL + r.slot), r.phase);
        wg_wait<1>();
        if (k > 0) give(prev);
        prev = ws;
        if (it >= P1_XS - 2 && !(it & 1) && lane == 0) mbar_arrive(bar_addr(sb, B_XFREE + ((it - (P1_XS - 2)) >> 1)));
        if (t > 0) {
          const int c0 = nk == 16 ? k : (16 * k + 3) * 37 >> 8, c1 = nk == 16 ? k + 1 : (16 * k + 19) * 37 >> 8;
#pragma unroll
          for (int i = 0; i < 16; i++)
            if (i >= c0 && i < c1) row[(i >> 1) * 256 + (i & 1) * 32] = make_uint4(pk[4 * i], pk[4 * i + 1], pk[4 * i + 2], pk[4 * i + 3]);
          if (c0 < 16 && c1 >= 16 && (t == T_QB + 1 || t == T_FIRST || t == T_LAST))
            warp_arrive(bar_addr(sb, (t == T_QB + 1 ? B_ST_Q : t == T_LAST ? B_ST_KV + 2 : B_ST_KV) + w), lane);
        }
      }
      if (t == 5) mbar_wait(bar_addr(sb, B_XFREE + w), 0);
      wg_wait<0>();
      reg_fence(acc);
      give(prev);
      pack_chunks(pk, acc);
      const int n = t - QFIRST;
      row = at<uint4>(t != T_QB ? (const void*)g_kv : (const void*)g_qc, chunk_off() +
                      (t != T_QB ? (uint32_t)((p1_isv(n) * NH + KVH(p1_head(h, n))) * 32 + p1_rows(h, j, n) * 2 + w) : (uint32_t)((h * 8 + j) * 2 + w)) * 32768);
      TS(2 + t);
    }
    give(xs);
    const uint32_t qa = qreg + chunk_off();
#pragma unroll
    for (int i = 0; i < 16; i++) sts16(qa + (i >> 1) * 4096 + (i & 1) * 512, pk[4 * i], pk[4 * i + 1], pk[4 * i + 2], pk[4 * i + 3]);
    fence_async_smem();
  }
  TS(8);

  constexpr float SC = 0.0625f * 1.4426950408889634f;
#pragma unroll 1
  for (int which = 0; which < 2; which++) {
    float s[32];
#pragma unroll
    for (int i = 0; i < 32; i++) s[i] = 0.f;
    uint32_t pa[16], pb[16];
    float m0 = -INFINITY, m1 = -INFINITY, l0 = 0.f, l1 = 0.f;
    const uint64_t dq = desc_64(qreg);
    uint64_t dk = 0, dqq = 0, dv = 0;
    auto prep_qk = [&](uint32_t kaddr) { dk = desc_64(kaddr); dqq = dq + (kaddr >> 31); asm volatile("" : "+l"(dk), "+l"(dqq)); };
    auto prep_pv = [&](uint32_t vaddr) { dv = desc_64(vaddr); asm volatile("" : "+l"(dv)); };
    auto issue_qk = [&]() {
#pragma unroll
      for (int kk = 0; kk < 16; kk++)
        wgmma_ss_n64(s, desc_add(dqq, (kk >> 1) * 4096 + (kk & 1) * 32), desc_add(dk, (kk >> 1) * 4096 + (kk & 1) * 32), kk != 0);
    };
    auto issue_pv = [&](int accumulate) {
#pragma unroll
      for (int kk = 0; kk < 4; kk++)
        wgmma_rs_n256_tb(acc, pa[4 * kk], pa[4 * kk + 1], pa[4 * kk + 2], pa[4 * kk + 3], desc_add(dv, kk * 1024), accumulate | kk);
    };
    auto mask_diag = [&]() {
      const int d = 16 * wq + (lane >> 2) - 2 * (lane & 3);
#pragma unroll
      for (int jj = 0; jj < 8; jj++) {
        if (8 * jj > d)     { s[4 * jj] = -INFINITY;     if (jj < 7) s[4 * jj + 6] = -INFINITY; }
        if (8 * jj + 1 > d) { s[4 * jj + 1] = -INFINITY; if (jj < 7) s[4 * jj + 7] = -INFINITY; }
      }
    };
    float a0, a1;
    auto softmax = [&](auto hook) -> bool {
      float x0 = fmaxf(s[0], s[1]), x1 = fmaxf(s[2], s[3]);
#pragma unroll
      for (int jj = 1; jj < 8; jj++) {
        x0 = fmaxf(x0, fmaxf(s[4 * jj], s[4 * jj + 1]));
        x1 = fmaxf(x1, fmaxf(s[4 * jj + 2], s[4 * jj + 3]));
      }
      x0 = fmaxf(x0, __shfl_xor_sync(0xffffffffu, x0, 1));
      x1 = fmaxf(x1, __shfl_xor_sync(0xffffffffu, x1, 1));
      x0 = fmaxf(x0, __shfl_xor_sync(0xffffffffu, x0, 2));
      x1 = fmaxf(x1, __shfl_xor_sync(0xffffffffu, x1, 2));
      const bool grow = __any_sync(0xffffffffu, fmaxf(x0 - m0, x1 - m1) * SC > 8.f);
      if (grow) {
        x0 = fmaxf(x0, m0); x1 = fmaxf(x1, m1);
        a0 = ex2((m0 - x0) * SC); a1 = ex2((m1 - x1) * SC);
        m0 = x0; m1 = x1;
        l0 *= a0; l1 *= a1;
      }
      const float b0 = -m0 * SC, b1 = -m1 * SC;
      float t0 = 0.f, t1 = 0.f, t2 = 0.f, t3 = 0.f;
#pragma unroll
      for (int jj = 0; jj < 8; jj++) {
        s[4 * jj]     = ex2(fmaf(s[4 * jj], SC, b0));
        s[4 * jj + 1] = ex2(fmaf(s[4 * jj + 1], SC, b0));
        s[4 * jj + 2] = ex2(fmaf(s[4 * jj + 2], SC, b1));
        s[4 * jj + 3] = ex2(fmaf(s[4 * jj + 3], SC, b1));
        t0 += s[4 * jj]; t1 += s[4 * jj + 1]; t2 += s[4 * jj + 2]; t3 += s[4 * jj + 3];
        hook(jj, HOOK_DEP);
      }
      l0 += t0 + t1; l1 += t2 + t3;
      return grow;
    };
    auto softmax_fast = [&]() -> bool {
      const float b0 = -m0 * SC, b1 = -m1 * SC;
      float t0 = 0.f, t1 = 0.f, t2 = 0.f, t3 = 0.f;
#pragma unroll
      for (int jj = 0; jj < 8; jj++) {
        const float e0 = ex2(fmaf(s[4 * jj], SC, b0)), e1 = ex2(fmaf(s[4 * jj + 1], SC, b0));
        const float e2 = ex2(fmaf(s[4 * jj + 2], SC, b1)), e3 = ex2(fmaf(s[4 * jj + 3], SC, b1));
        pb[2 * jj] = pack_bf16(e0, e1); pb[2 * jj + 1] = pack_bf16(e2, e3);
        if (jj == 0) { t0 = e0; t1 = e1; t2 = e2; t3 = e3; } else { t0 += e0; t1 += e1; t2 += e2; t3 += e3; }
      }
      t0 += t1; t2 += t3;
      const bool redo = __any_sync(0xffffffffu, !(t0 + t2 <= 16777216.f));
      if (!redo) { l0 += t0; l1 += t2; }
      return redo;
    };
    auto rescale = [&]() {
#pragma unroll
      for (int i = 0; i < 32; i++) { acc[4 * i] *= a0; acc[4 * i + 1] *= a0; acc[4 * i + 2] *= a1; acc[4 * i + 3] *= a1; }
    };
    auto to_p = [&](uint32_t (&pp)[16]) {
#pragma unroll
      for (int i = 0; i < 16; i++) pp[i] = pack_bf16(s[2 * i], s[2 * i + 1]);
    };
    auto q_free = [&]() { if (lane == 0) mbar_arrive(bar_addr(sb, B_QFREE + w)); };

    const int n = 2 * q_tile(h, j, which) + 1 + (w ^ which);
    uint32_t ks = take(rdy0);
    TS(9 + 5 * which);
    prep_qk(sb + ks * SLOT);
    turn_begin();
    TS(20 + 10 * which);
    wg_fence();
    issue_qk();
    wg_commit();
    turn_end();
    if (which == 1) give(take(rdy1));
    TS(22 + 10 * which);
    wg_wait<0>();
    TS(21 + 10 * which);
    reg_fence(s);
    give(ks);
    if (which == 0 && n == 1) q_free();
    if (which == 1 || n == 1) mask_diag();
    {
      const uint4* dst = at<uint4>(g_qc, (uint32_t)((h * 8 + j) * 2 + w) * 32768 + (fresh_tid() & 127) * 16);
      softmax([&](int jj, float e) {
        if (jj == PEEK_JJ) peek2();
        const int i = CTX_SPLIT + jj;
        if (i < 16)
          asm volatile("{\n.reg .pred p, q;\nsetp.ne.b32 q, %6, 0;\nsetp.geu.and.f32 p, %5, 0fBF800000, q;\n@p st.global.v4.u32 [%0], {%1, %2, %3, %4};\n}"
                       :: "l"(dst + i * 128), "r"(pk[4 * (i & 15)]), "r"(pk[4 * (i & 15) + 1]), "r"(pk[4 * (i & 15) + 2]), "r"(pk[4 * (i & 15) + 3]), "f"(e), "r"(which) : "memory");
      });
    }
    to_p(pa);
    if (which == 1) warp_arrive(bar_addr(sb, B_ST_CTX + w), lane);
    TS(10 + 5 * which);
#pragma unroll 1
    for (int jj = 1; jj < n; jj++) {
      ks = take(rdy0);
      const uint32_t vs = take(rdy1);
      prep_qk(sb + ks * SLOT);
      prep_pv(sb + vs * SLOT);
      TSC(23 + 10 * which, jj == 1);
      turn_begin();
      TSC(24 + 10 * which, jj == 1);
      TSC(26 + 10 * which, jj == n - 1);
      wg_fence();
      issue_qk();
      wg_commit();
      issue_pv(jj > 1);
      wg_commit();
      turn_end();
      wg_wait<1>();
      TSC(25 + 10 * which, jj == 1);
      reg_fence(s);
      give(ks);
      if (jj == n - 1 && which == 0) { q_free(); mask_diag(); }
      if (PF_CTX && which == 1 && jj == max(n - PF_CTX, 1)) {
        const uint8_t* src = at<const uint8_t>(g_qc, (uint32_t)(((h ^ 8) * 8 + j) * 2 + (w ^ 1)) * 32768 + (fresh_tid() & 127) * 128);
        asm volatile("prefetch.global.L2 [%0];" :: "l"(src));
        asm volatile("prefetch.global.L2 [%0];" :: "l"(src + 16384));
      }
      if (softmax_fast()) {
        wg_wait<0>();
        reg_fence(acc);
        if (softmax([](int, float) {})) rescale();
        to_p(pb);
      }
      peek2();
      wg_wait<0>();
      reg_fence(acc);
      reg_fence(pa);
      give(vs);
#pragma unroll
      for (int i = 0; i < 16; i++) pa[i] = pb[i] | (vs >> 8);
    }
    TS(11 + 5 * which);
    if (which == 0) { give(take(rdy0)); rdy0 = rdy1; }
    {
      const uint32_t vs = take(rdy0);
      prep_pv(sb + vs * SLOT);
      TS(27 + 10 * which);
      turn_begin();
      TS(28 + 10 * which);
      wg_fence();
      issue_pv(n > 1);
      wg_commit();
      turn_end();
      l0 += __shfl_xor_sync(0xffffffffu, l0, 1); l1 += __shfl_xor_sync(0xffffffffu, l1, 1);
      l0 += __shfl_xor_sync(0xffffffffu, l0, 2); l1 += __shfl_xor_sync(0xffffffffu, l1, 2);
      asm("rcp.approx.ftz.f32 %0, %0;" : "+f"(l0));
      asm("rcp.approx.ftz.f32 %0, %0;" : "+f"(l1));
      peek2();
      if (which == 0) mbar_wait(bar_addr(sb, B_QFULL + w), 0);
      wg_wait<0>();
      reg_fence(acc);
      reg_fence(pa);
      give(vs);
    }
    TS(12 + 5 * which);
    {
      const uint4* dst = at<uint4>(g_qc, (uint32_t)((h * 8 + j) * 2 + w) * 32768 + (fresh_tid() & 127) * 16);
#pragma unroll
      for (int i = 0; i < 16; i++) {
        const int c = (i & 1) ? (i >> 1) + 8 : i >> 1;
        pk[4 * c]     = pack_bf16(acc[8 * c] * l0, acc[8 * c + 1] * l0);
        pk[4 * c + 1] = pack_bf16(acc[8 * c + 2] * l1, acc[8 * c + 3] * l1);
        pk[4 * c + 2] = pack_bf16(acc[8 * c + 4] * l0, acc[8 * c + 5] * l0);
        pk[4 * c + 3] = pack_bf16(acc[8 * c + 6] * l1, acc[8 * c + 7] * l1);
        if (c < CTX_SPLIT)
          asm volatile("{\n.reg .pred p;\nsetp.eq.b32 p, %5, 0;\n@p st.global.v4.u32 [%0], {%1, %2, %3, %4};\n}"
                       :: "l"(dst + c * 128), "r"(pk[4 * c]), "r"(pk[4 * c + 1]), "r"(pk[4 * c + 2]), "r"(pk[4 * c + 3]), "r"(which) : "memory");
      }
    }
    TS(13 + 5 * which);
  }

  {
    float oa[32], ob[32];
#pragma unroll
    for (int i = 0; i < 32; i++) { oa[i] = 0.f; ob[i] = 0.f; }
    uint32_t pk2[64];
#pragma unroll
    for (int i = 0; i < 64; i++) pk2[i] = 0;
    auto stage = [&](float (&o)[32], int ch) {
      reg_fence(o);
      uint32_t q[16];
#pragma unroll
      for (int i = 0; i < 16; i++) q[i] = pack_bf16(o[2 * i], o[2 * i + 1]);
      if (ch >= 4) mbar_wait(bar_addr(sb, B_S2_EMPTY + w * 4 + (ch & 3)), 0);
      store_block(qreg + (ch & 3) * 8192, lane_base16(), q);
    };
    auto hand_over = [&](int ch) {
      fence_async_smem();
      warp_arrive(bar_addr(sb, B_S2_FULL + w * 4 + (ch & 3)), lane);
    };
    uint32_t prev = 0;
    auto half = [&](int f, float (&o)[32], uint32_t (&a)[64], int accumulate) {
      const uint32_t sl = take(rdy0);
      const uint64_t d = desc_mn(sb + sl * SLOT);
      turn_begin();
      TS(40 + f);
      wg_fence();
#pragma unroll
      for (int kk = 0; kk < 16; kk++) {
        wgmma_rs_n64_tb(o, a[4 * kk], a[4 * kk + 1], a[4 * kk + 2], a[4 * kk + 3], desc_add(d, kk * 2048), accumulate | kk);
        if (kk == ARRIVE_KK && (f < 13 || w == 0)) turn_end();
      }
      wg_commit();
      if (f < 13) rdy0 = mbar_test(bar_addr(sb, B_FULL + r.slot), r.phase);
      wg_wait<1>();
      if (f >= 1 && f <= 9) give(prev);
      prev = sl;
    };
    auto load_ctx = [&](auto h0) {
      constexpr int I0 = decltype(h0)::value ? CTX_LD : 0, NL = decltype(h0)::value ? 16 - CTX_LD : CTX_LD;
      const uint4* src = at<const uint4>(g_qc, (uint32_t)(((h ^ 8) * 8 + j) * 2 + (w ^ 1)) * 32768 + (fresh_tid() & 127) * 16);
#pragma unroll
      for (int i = I0; i < I0 + NL; i++) { const uint4 v = __ldcg(src + i * 128); pk2[4 * i] = v.x; pk2[4 * i + 1] = v.y; pk2[4 * i + 2] = v.z; pk2[4 * i + 3] = v.w; }
    };
#pragma unroll 1
    for (int i = 0; i < 3; i++) {
      half(4 * i, oa, pk, 0);
      if (i == 0) { mbar_wait(bar_addr(sb, B_CTXOK + w), 0); load_ctx(Int<0>()); }
      else { hand_over(2 * i - 2); stage(ob, 2 * i - 1); }
      half(4 * i + 1, ob, pk, 0);
      if (i == 0) load_ctx(Int<1>()); else hand_over(2 * i - 1);
      half(4 * i + 2, oa, pk2, 1);
      half(4 * i + 3, ob, pk2, 1);
      stage(oa, 2 * i);
    }
    half(12, oa, pk, 0);
    hand_over(4);
    stage(ob, 5);
    half(13, oa, pk2, 1);
    hand_over(5);
    wg_wait<0>();
    reg_fence(pk);
    reg_fence(pk2);
    stage(oa, 6);
    hand_over(6);
  }
  TS(19);
  TDUMP();
}

namespace ssm {
constexpr int NCH = DA / NCONV;
constexpr int NS = 8, NP = 6;
constexpr uint32_t X0 = 384;
constexpr uint32_t HO = X0 + 4096;
constexpr uint32_t HE = HO + HO_STRIDE + 64;
constexpr uint32_t SSLOT = HE + 4096 + 64;
constexpr uint32_t PART = 264 * 16;
constexpr uint32_t OFF_P = NS * SSLOT, OFF_D = OFF_P + NP * 4 * PART, END = OFF_D + NCH * 4;
static_assert(SSLOT % 128 == 0 && HO % 128 == 0 && END <= BARS, "smem");
enum : uint32_t { B_FULL = 0, B_EMPTY = NS, B_PFULL = 2 * NS, B_PEMPTY = 2 * NS + NP };
__device__ __forceinline__ int channel(int cidx, int i) { return (i >> 4) * 64 + cidx * 16 + (i & 15); }

__device__ __forceinline__ void producer(const Params& p, uint32_t sb, int cidx, unsigned epoch) {
#pragma unroll 1
  for (int i = 0; i < NCH; i++) {
    const int s = i % NS, ch = channel(cidx, i);
    const uint32_t full = bar_addr(sb, B_FULL + s), dst = sb + s * SSLOT;
    mbar_wait(bar_addr(sb, B_EMPTY + s), ((i / NS) & 1) ^ 1);
    mbar_expect_tx(full, 4096 + 4128 + 4096);
    bulk_ld(dst + HE, at<uint8_t>(p.a_ssmk, ch * 4096), 4096, full);
    if ((i & 15) == 0) { flag_wait(flag_at(g_flags.x_ready, i >> 4), NMAIN, epoch); fence_async_all(); }
    bulk_ld(dst + HO, at<uint8_t>(g_ho, ch * HO_STRIDE), 4128, full);
    bulk_ld(dst + X0, at<uint8_t>(g_xs, ch * 4096), 4096, full);
  }
}

__device__ __forceinline__ void reducer(uint32_t sb, int cidx, int rw) {
  uint32_t n = 0;
#pragma unroll 1
  for (int i = rw; i < NCH; i += 3, n++) {
    const uint32_t b = rw + 3 * (n & 1), pb = sb + OFF_P + b * 4 * PART;
    uint8_t* dst = at<uint8_t>(g_xs, channel(cidx, i) * 4096);
    mbar_wait(bar_addr(sb, B_PFULL + b), (n >> 1) & 1);
    asm volatile("cp.async.bulk.global.shared::cta.bulk_group [%0], [%1], 4096;" :: "l"(dst), "r"(pb + 3 * PART) : "memory");
    bulk_commit();
    bulk_wait_all();
#pragma unroll
    for (int k = 2; k >= 0; k--)
      asm volatile("cp.reduce.async.bulk.global.shared::cta.bulk_group.add.noftz.bf16 [%0], [%1], 4096;" :: "l"(dst), "r"(pb + k * PART) : "memory");
    bulk_commit();
    bulk_wait_read();
    mbar_arrive(bar_addr(sb, B_PEMPTY + b));
    if (((i + 3) >> 4) != (i >> 4)) {
      bulk_wait_all();
      fence_async_all();
      flag_signal(flag_at(g_flags.z_ready, i >> 4));
    }
  }
}

__device__ __forceinline__ void mma_warpgroup(uint32_t sb, int w) {
  const int lane = threadIdx.x & 31, g = lane >> 2, c = lane & 3, wq = (threadIdx.x >> 5) & 3;
  const uint32_t aoff = ((g & 1) ? HO + 30 : HE) + (16 * wq - g + 2 * c) * 2;
  const uint32_t poff = OFF_P + wq * PART + (2 * wq + lane) * 16;
  const uint32_t dmask = (wq == 0 && c == (g >> 1)) ? ((g & 1) ? 0xffff0000u : 0xffffu) : 0u;
  float acc[8][16];
  uint32_t fa[16][4];
#pragma unroll
  for (int e = 0; e < 8; e++)
#pragma unroll
    for (int i = 0; i < 16; i++) acc[e][i] = 0.f;
  auto load_a = [&](int m, uint32_t ad) {
    fa[m][0] = lds4(ad + m * 256 + 16); fa[m][1] = lds4(ad + m * 256 + 144); fa[m][2] = lds4(ad + m * 256); fa[m][3] = lds4(ad + m * 256 + 128);
  };
  if (w == 1) named_arrive(PP_BAR, 256);
  mbar_wait(bar_addr(sb, B_FULL + w), 0);
#pragma unroll
  for (int m = 0; m < 16; m++) load_a(m, sb + w * SSLOT + aoff);
  uint32_t dd = lds4(sb + OFF_D + w * 4);
  if (threadIdx.x == 128) { GT(12); PT(10); }
  uint32_t pb = w, pphase = 1;
#pragma unroll 1
  for (int i = w; i < NCH; i += 2) {
    fa[0][2] = badd(fa[0][2], dd & dmask);
    const uint64_t db = (uint64_t)((((sb + (i % NS) * SSLOT + X0 - 16) & 0x3FFFF) >> 4) | (1u << 16)) | ((uint64_t)8 << 32);
    named_sync(PP_BAR + w, 256);
    wg_fence();
#pragma unroll
    for (int r = 0; r < 16; r++) {
      auto mm = [&](int e, int m) { wgmma_rs_n32(acc[e], fa[m][0], fa[m][1], fa[m][2], fa[m][3], db + (int64_t)(32 * e - 16 * m), m != 0); };
      mm(7, r);
      if (r < 14) mm(6, r); else mm(0, r - 14);
      if (r < 12) mm(5, r); else mm(1, r - 12);
      if (r < 10) mm(4, r); else mm(2, r - 10);
      if ((r & 1) == 0) mm(3, r >> 1);
      if (r == CONV_ARRIVE && (i + 1 < NCH)) named_arrive(PP_BAR + (w ^ 1), 256);
    }
    wg_commit();
    const int nx = i + 2 < NCH ? i + 2 : i;
    mbar_wait(bar_addr(sb, B_FULL + nx % NS), (nx / NS) & 1);
    mbar_wait(bar_addr(sb, B_PEMPTY + pb), pphase);
    const uint32_t ad = sb + (nx % NS) * SSLOT + aoff, pa = sb + pb * 4 * PART + poff;
    wg_wait<0>();
#pragma unroll
    for (int e = 0; e < 8; e++) reg_fence(acc[e]);
#pragma unroll
    for (int m = 0; m < 16; m++) reg_fence(fa[m]);
    if (lane == 0) mbar_arrive(bar_addr(sb, B_EMPTY + i % NS));
#pragma unroll
    for (int e = 0; e < 8; e++) {
      if (e < CONV_EARLY) load_a(e, ad);
      uint32_t u[4];
#pragma unroll
      for (int j = 0; j < 4; j++) {
        const int T = 4 * e + j, U = T - 1;
        float lo = acc[e][4 * j], hi = acc[e][4 * j + 1];
        if (T > 0) { lo += acc[U >> 2][4 * (U & 3) + 2]; hi += acc[U >> 2][4 * (U & 3) + 3]; }
        u[j] = pack_bf16(lo, hi);
      }
      asm volatile("stmatrix.sync.aligned.m8n8.x4.trans.shared.b16 [%0], {%1, %2, %3, %4};" :: "r"(pa + e * 512), "r"(u[0]), "r"(u[1]), "r"(u[2]), "r"(u[3]) : "memory");
    }
    dd = lds4(sb + OFF_D + nx * 4);
#pragma unroll
    for (int m = CONV_EARLY; m < CONV_FENCE; m++) load_a(m, ad);
    fence_async_smem();
    warp_arrive(bar_addr(sb, B_PFULL + pb), lane);
#pragma unroll
    for (int m = CONV_FENCE; m < 16; m++) load_a(m, ad);
    pb += 2;
    if (pb >= NP) { pb -= NP; pphase ^= 1; }
  }
  if (threadIdx.x == 128) { PT(9); GT(13); }
}

__device__ __forceinline__ void init(const Params& p, uint32_t sb, int cidx) {
  if (threadIdx.x < NS * 32) {
    const uint32_t s = threadIdx.x >> 5, r = threadIdx.x & 31;
    if (r < 28) sts16(sb + s * SSLOT + (r < 24 ? r * 16 : HE - 64 + (r - 24) * 16), 0, 0, 0, 0);
  } else {
    const uint32_t t = threadIdx.x - NS * 32;
    for (uint32_t u = t; u < NP * 32; u += 128) sts16(sb + OFF_P + (u >> 3) * PART + (u & 7) * 16, 0, 0, 0, 0);
    if (t < NCH) {
      const uint32_t d = (uint32_t)__ldg(reinterpret_cast<const unsigned short*>(p.a_D + channel(cidx, t))) * 0x10001u;
      asm volatile("st.shared.u32 [%0], %1;" :: "r"(sb + OFF_D + t * 4), "r"(d) : "memory");
    }
  }
  if (threadIdx.x == 0) {
    for (int i = 0; i < NS; i++) { mbar_init(bar_addr(sb, B_FULL + i), 1); mbar_init(bar_addr(sb, B_EMPTY + i), 4); }
    for (int i = 0; i < NP; i++) { mbar_init(bar_addr(sb, B_PFULL + i), 4); mbar_init(bar_addr(sb, B_PEMPTY + i), 1); }
  }
  fence_async_smem();
}

__device__ __forceinline__ void side_prepare(const Params& p, int cta, int rd) {
  const int lane = threadIdx.x & 31, t0 = 16 * cta + 8 * (lane & 1);
  if (EXP_SIDE & 16) { if (lane == 0) flag_signal_after_bulk(flag_at(g_flags.x_ready, rd)); return; }
#pragma unroll 1
  for (int ch = 64 * rd + (lane & ~1); ch < 64 * rd + 64; ch += 32) {
    const uint4 sv = __ldg(at<const uint4>(p.a_shift, ch * 8));
    const uint32_t* kp = at<const uint32_t>(p.a_k, (t0 * DA + ch) * 2);
    const uint32_t* vp = at<const uint32_t>(p.a_v, (t0 * DA + ch) * 2);
    uint32_t k0 = 0, k1 = 0, k2 = 0, kk[8], x[8];
    if (t0 > 0) { k0 = __ldg(kp - 3 * (DA / 2)); k1 = __ldg(kp - 2 * (DA / 2)); k2 = __ldg(kp - DA / 2); }
#pragma unroll
    for (int i = 0; i < 8; i++) { kk[i] = __ldg(kp + i * (DA / 2)); x[i] = __ldg(vp + i * (DA / 2)); }
    const uint32_t sh0 = __byte_perm(sv.x, sv.z, 0x5410), sh1 = __byte_perm(sv.x, sv.z, 0x7632);
    const uint32_t sh2 = __byte_perm(sv.y, sv.w, 0x5410), sh3 = __byte_perm(sv.y, sv.w, 0x7632);
#pragma unroll
    for (int i = 0; i < 8; i++) {
      uint32_t ks = bmul(k0, sh3);
      ks = badd(ks, bmul(k1, sh2)); ks = badd(ks, bmul(k2, sh1)); ks = badd(ks, bmul(kk[i], sh0));
      x[i] = bmul(ks, x[i]);
      k0 = k1; k1 = k2; k2 = kk[i];
    }
    uint4* dst = at<uint4>(g_xs, ch * 4096 + t0 * 2);
    if ((EXP_SIDE & 4) && (x[0] ^ x[1] ^ x[2] ^ x[3] ^ x[4] ^ x[5] ^ x[6] ^ x[7]) != 0x12345) continue;
    dst[0]   = make_uint4(__byte_perm(x[7], x[6], 0x5410), __byte_perm(x[5], x[4], 0x5410), __byte_perm(x[3], x[2], 0x5410), __byte_perm(x[1], x[0], 0x5410));
    dst[256] = make_uint4(__byte_perm(x[7], x[6], 0x7632), __byte_perm(x[5], x[4], 0x7632), __byte_perm(x[3], x[2], 0x7632), __byte_perm(x[1], x[0], 0x7632));
  }
  if (!(EXP_SIDE & 8)) {
    const int hc = 64 * rd + (cta >> 1), r0 = (cta & 1) * 128 + lane;
    const uint4* src = at<const uint4>(p.a_ssmk, hc * 4096 + r0 * 16);
    uint4* dst = at<uint4>(g_ho, hc * HO_STRIDE + r0 * 16);
    uint4 w[4];
    uint32_t nx[4];
#pragma unroll
    for (int i = 0; i < 4; i++) { w[i] = __ldg(src + 32 * i); nx[i] = r0 + 32 * i < 255 ? __ldg(reinterpret_cast<const uint32_t*>(src + 32 * i + 1)) : 0u; }
#pragma unroll
    for (int i = 0; i < 4; i++)
      dst[32 * i + 2] = make_uint4(__byte_perm(w[i].x, w[i].y, 0x5432), __byte_perm(w[i].y, w[i].z, 0x5432), __byte_perm(w[i].z, w[i].w, 0x5432), __byte_perm(w[i].w, nx[i], 0x5432));
    const uint32_t h0 = __shfl_sync(0xffffffffu, w[0].x, 0);
    if (r0 < 2) dst[0] = make_uint4(0, 0, 0, r0 ? h0 << 16 : 0u);
  }
  __syncwarp();
  if (lane == 0) { if (EXP_SIDE & 2) flag_signal_after_bulk(flag_at(g_flags.x_ready, rd)); else flag_signal(flag_at(g_flags.x_ready, rd)); }
}
__device__ __forceinline__ void side_finish(const Params& p, int cta, int rd) {
  const int lane = threadIdx.x & 31, t0 = 16 * cta + 8 * (lane & 1);
#pragma unroll 1
  for (int ch = 64 * rd + (lane & ~1); ch < 64 * rd + 64; ch += 32) {
    const uint4* src = at<const uint4>(g_xs, ch * 4096 + t0 * 2);
    const uint32_t* qp = at<const uint32_t>(p.a_q, (t0 * DA + ch) * 2);
    uint32_t* op = at<uint32_t>(p.out, (t0 * OUTW + ch) * 2);
    const uint4 z0 = __ldcg(src), z1 = __ldcg(src + 256);
    uint32_t q[8];
#pragma unroll
    for (int i = 0; i < 8; i++) q[i] = __ldg(qp + i * (DA / 2));
    const uint32_t a[4] = {z0.w, z0.z, z0.y, z0.x}, b[4] = {z1.w, z1.z, z1.y, z1.x};
#pragma unroll
    for (int i = 0; i < 4; i++) {
      op[(2 * i) * (OUTW / 2)]     = bmul(q[2 * i], __byte_perm(a[i], b[i], 0x7632));
      op[(2 * i + 1) * (OUTW / 2)] = bmul(q[2 * i + 1], __byte_perm(a[i], b[i], 0x5410));
    }
  }
}
__device__ __forceinline__ void clear_rows(const Params& p, int qt, int part) {
  const int lane = threadIdx.x & 31;
  if (lane < 28) {
    uint4* z = at<uint4>(p.out, ((qt * 128 + part * 16) * OUTW + DA) * 2 + lane * 16);
#pragma unroll
    for (int i = 0; i < 32; i++) z[(i >> 1) * (OUTW / 8) + (i & 1) * 28] = make_uint4(0, 0, 0, 0);
  }
  __syncwarp();
  if (lane == 0) flag_signal(flag_at(g_flags.zero_ready, qt));
}
__device__ __forceinline__ void side_work(const Params& p, int cta, int qt, unsigned epoch) {
#pragma unroll 1
  for (int rd = -SIDE_AHEAD; rd < 7; rd++) {
    if (rd >= 0) {
      if ((threadIdx.x & 31) == 0) flag_wait_slow(flag_at(g_flags.z_ready, rd), 3 * NCONV, epoch);
      __syncwarp();
    }
    if (rd + SIDE_AHEAD < 7) side_prepare(p, cta, rd + SIDE_AHEAD);
    if (rd >= 0 && !(EXP_SIDE & 1)) side_finish(p, cta, rd);
    if (rd == ZERO_RD) clear_rows(p, qt, (cta >> 3) & 7);
  }
}
}

__global__ void __cluster_dims__(2, 1, 1) __launch_bounds__(NTHREADS, 1)
concat_heads__ssm_conv_h3__compressed_kv_cla__prompt_kernel(const __grid_constant__ Params p) {
  extern __shared__ uint8_t smem_raw[];
  const uint32_t sb = (smem_u32(smem_raw) + 1023) & ~1023u;
  const int warp = __shfl_sync(0xffffffffu, threadIdx.x >> 5, 0);
  const int wg = warp >> 2;
  const int cta = blockIdx.x;
  const bool attn = cta < NMAIN;
  int h, u;
  {
    const int c = cta >> 1;
    if (c < 4) { h = 9; u = c; }
    else if (c < 36) { h = (c - 4) & 7; u = (c - 4) >> 3; }
    else { const int i = (c - 36) % 7; h = i == 0 ? 8 : 9 + i; u = (c - 36) / 7; }
  }
  const int j = 2 * u + (cta & 1);
  if (!attn) ssm::init(p, sb, cta - NMAIN);
  if (attn && threadIdx.x == 0) {
    for (int i = 0; i < NSLOT; i++) { mbar_init(bar_addr(sb, B_FULL + i), 1); mbar_init(bar_addr(sb, B_EMPTY + i), 16); }
    for (int i = 0; i < 2; i++) {
      mbar_init(bar_addr(sb, B_XFREE + i), 8); mbar_init(bar_addr(sb, B_QFREE + i), 4); mbar_init(bar_addr(sb, B_QFULL + i), 1);
      mbar_init(bar_addr(sb, B_ST_KV + i), 4); mbar_init(bar_addr(sb, B_ST_KV + 2 + i), 4); mbar_init(bar_addr(sb, B_KVOK + i), 1);
      mbar_init(bar_addr(sb, B_ST_Q + i), 4); mbar_init(bar_addr(sb, B_ST_CTX + i), 4);
      mbar_init(bar_addr(sb, B_CTXOK + i), 1);
    }
    mbar_init(bar_addr(sb, B_PF), 1);
    mbar_init(bar_addr(sb, B_DONE), 2);
    for (int i = 0; i < 8; i++) { mbar_init(bar_addr(sb, B_S2_FULL + i), 4); mbar_init(bar_addr(sb, B_S2_EMPTY + i), 1); }
    asm volatile("fence.mbarrier_init.release.cluster;" ::: "memory");
  }
  if (attn && threadIdx.x == 32) {
    prefetch_map(&p.ckv); prefetch_map(&p.wuk); prefetch_map(&p.wuv); prefetch_map(&p.x); prefetch_map(&p.wq);
    prefetch_map(&p.o); prefetch_map(&p.wo);
  }
  __syncwarp();
  asm volatile("barrier.cluster.arrive.release.aligned;" ::: "memory");
  if (attn && threadIdx.x == 0) {
    for (int k = 0; k < EARLY_LD; k++) {
      const uint32_t full = bar_addr(sb, B_FULL + k);
      mbar_expect_tx(full, 49152);
      if (QFIRST) {
        tma_ld2(sb + QREG + k * 16384, &p.x, full, k * 64, q_tile(h, j, 1) * 128);
        load_tile4(sb + k * SLOT, &p.wq, full, k * 64, att_head(h, 1) * 4, j & 1, false);
      } else {
        tma_ld2(sb + QREG + k * 16384, &p.ckv, full, k * 64, p1_rows(h, j, 0) * 128);
        load_tile4(sb + k * SLOT, &p.wuk, full, k * 64, p1_head(h, 0) * 4, j & 1, false);
      }
    }
  }
  __syncwarp();
  asm volatile("barrier.cluster.wait.acquire.aligned;" ::: "memory");

  const int lane = threadIdx.x & 31;
  if (wg == 0) {
    if (!attn) {
      asm volatile("setmaxnreg.dec.sync.aligned.u32 40;");
      if (lane == 0) {
        if (warp == 0) { ssm::producer(p, sb, cta - NMAIN, load_epoch()); cta_done(32); }
        else ssm::reducer(sb, cta - NMAIN, warp - 1);
        if (warp == 1) GT(14);
      }
      return;
    }
    asm volatile("setmaxnreg.dec.sync.aligned.u32 40;");
    if (warp == 0) {
      if (lane == 0) producer_main(p, sb, h, j);
    } else if (warp < 3) {
      if (PF_Q && warp == 2) {
        mbar_wait(bar_addr(sb, B_PF), 0);
        const uint8_t* xp = at<const uint8_t>(p.b_x, (h * 8 + j) * 16 * DM * 2 + lane * 128);
        const uint8_t* wp = at<const uint8_t>(p.b_wq, ((j * 56 + (lane >> 2)) * NH + h) * HD * 2 + (lane & 3) * 128);
#pragma unroll
        for (int i = 0; i < 7; i++) {
          if (i < 3 || (i == 3 && lane < 16)) asm volatile("prefetch.global.L2 [%0];" :: "l"(xp + i * 4096));
          asm volatile("prefetch.global.L2 [%0];" :: "l"(wp + i * 8 * NH * HD * 2));
          __nanosleep(PF_GAP);
        }
      }
      if (lane == 0) { helper_main(p, sb, h, j, warp - 1); mbar_arrive(bar_addr(sb, B_DONE)); }
    } else {
      ssm::side_work(p, h * 8 + j, q_tile(h, j, 1), load_epoch());
      if (lane == 0) { GT(57); mbar_wait(bar_addr(sb, B_DONE), 0); cta_done(1); }
    }
  } else {
    if (!attn) {
      asm volatile("setmaxnreg.inc.sync.aligned.u32 232;");
      if (p.out != nullptr) ssm::mma_warpgroup(sb, wg - 1);
      return;
    }
    asm volatile("setmaxnreg.inc.sync.aligned.u32 232;");
    if (p.out != nullptr) consumer_main(p, sb, h, j, wg - 1, warp & 3);
  }
}

typedef CUresult (*EncodeTiledFn)(CUtensorMap*, CUtensorMapDataType, cuuint32_t, void*, const cuuint64_t*, const cuuint64_t*,
                                  const cuuint32_t*, const cuuint32_t*, CUtensorMapInterleave, CUtensorMapSwizzle,
                                  CUtensorMapL2promotion, CUtensorMapFloatOOBfill);

void make_map(EncodeTiledFn enc, CUtensorMap* m, const void* ptr, int rank, const uint64_t* dims, const uint64_t* strides, const uint32_t* box) {
  cuuint64_t d[5], s[4]; cuuint32_t b[5], e[5] = {1, 1, 1, 1, 1};
  for (int i = 0; i < rank; i++) { d[i] = dims[i]; b[i] = box[i]; if (i) s[i - 1] = strides[i - 1]; }
  enc(m, CU_TENSOR_MAP_DATA_TYPE_BFLOAT16, rank, const_cast<void*>(ptr), d, s, b, e, CU_TENSOR_MAP_INTERLEAVE_NONE,
      CU_TENSOR_MAP_SWIZZLE_128B, CU_TENSOR_MAP_L2_PROMOTION_L2_256B, CU_TENSOR_MAP_FLOAT_OOB_FILL_NONE);
}
void map2(EncodeTiledFn enc, CUtensorMap* m, const void* ptr, uint64_t cols, uint64_t rows, uint32_t bc, uint32_t br) {
  const uint64_t dims[2] = {cols, rows}, st[1] = {cols * 2}; const uint32_t box[2] = {bc, br};
  make_map(enc, m, ptr, 2, dims, st, box);
}
void map3(EncodeTiledFn enc, CUtensorMap* m, const void* ptr, uint64_t rows, uint32_t nblk) {
  const uint64_t dims[3] = {64, rows, 64}, st[2] = {8192, 128}; const uint32_t box[3] = {64, 64, nblk};
  make_map(enc, m, ptr, 3, dims, st, box);
}

}

extern "C" void kernel_launch(void* const* d_in, const int* in_sizes, int n_in, void* d_out, int out_size) {
  (void)in_sizes; (void)n_in; (void)out_size;
  static EncodeTiledFn enc = nullptr;
  if (!enc) {
    void* fn = nullptr; cudaDriverEntryPointQueryResult qr;
    cudaGetDriverEntryPoint("cuTensorMapEncodeTiled", &fn, cudaEnableDefault, &qr);
    enc = (EncodeTiledFn)fn;
    cudaFuncSetAttribute(concat_heads__ssm_conv_h3__compressed_kv_cla__prompt_kernel, cudaFuncAttributeMaxDynamicSharedMemorySize, SMEM_BYTES);
  }
  Params p;
  p.a_q = (const bf16*)d_in[0]; p.a_k = (const bf16*)d_in[1]; p.a_v = (const bf16*)d_in[2];
  p.a_shift = (const bf16*)d_in[3]; p.a_ssmk = (const bf16*)d_in[4]; p.a_D = (const bf16*)d_in[5];
  p.out = (bf16*)d_out;
  p.b_x = (const bf16*)d_in[6]; p.b_wq = (const bf16*)d_in[8];
  map2(enc, &p.x, d_in[6], DM, SEQ, 64, 128);
  map2(enc, &p.ckv, d_in[7], DC, SEQ, 64, 128);
  map3(enc, &p.wq, d_in[8], DM, 2);
  map3(enc, &p.wuk, d_in[9], DC, 2);
  map3(enc, &p.wuv, d_in[10], DC, 2);
  {
    const uint64_t dims[5] = {DM, 2, 4, 4, NH * HD / 32}, st[4] = {DM * 2, 8 * DM * 2, 2 * DM * 2, 32 * DM * 2}; const uint32_t box[5] = {64, 2, 4, 4, 4};
    make_map(enc, &p.wo, d_in[11], 5, dims, st, box);
  }
  map2(enc, &p.o, d_out, OUTW, SEQ, 64, 64);
  concat_heads__ssm_conv_h3__compressed_kv_cla__prompt_kernel<<<NCTA, NTHREADS, SMEM_BYTES>>>(p);
}
```

```cpp
#include <cuda_runtime.h>
#include <cuda_bf16.h>
#include <cuda.h>
#include <stdint.h>

namespace {

typedef __nv_bfloat16 bf16;

constexpr int SEQ  = 2048;
constexpr int DA   = 448;
constexpr int NH   = 16;
constexpr int HD   = 256;
constexpr int DM   = 448;
constexpr int DC   = 1024;
constexpr int OUTW = DA + DM;
constexpr int NMAIN = 128;
constexpr int NCONV = 4;
constexpr int NCTA  = NMAIN + NCONV;
constexpr int LOG_DONE = 8;
constexpr int NTHREADS = 384;

__device__ __align__(1024) bf16 g_kv[2ull * SEQ * NH * HD];
__device__ __align__(1024) bf16 g_qc[(size_t)NMAIN * 128 * HD];
__device__ __align__(128) uint8_t g_xs[DA * SEQ * 2];
constexpr uint32_t HO_STRIDE = 4224;
__device__ __align__(128) uint8_t g_ho[DA * HO_STRIDE];
struct alignas(128) Flag { unsigned v; unsigned pad[31]; };
struct Flags {
  Flag kv_ready[NH * 2];
  Flag ctx_ready[NMAIN * 2];
  Flag x_ready[7];
  Flag z_ready[7];
  Flag zero_ready[16];
  alignas(128) unsigned long long done;
};
__device__ Flags g_flags;
#define TS(i)
#define TSC(i, cond)
#define TDUMP()
#define GT(i)
#define PT(i)
#define PCLK(var)
#define PACC(acc, t0)

struct alignas(64) Params {
  CUtensorMap ckv;
  CUtensorMap wuk;
  CUtensorMap wuv;
  CUtensorMap x;
  CUtensorMap wq;
  CUtensorMap o;
  CUtensorMap wo;
  const bf16 *a_q, *a_k, *a_v, *a_shift, *a_ssmk, *a_D;
  bf16* out;
};

constexpr uint32_t SLOT     = 32768;
constexpr int      NSLOT    = 5;
constexpr uint32_t QREG     = 163840;
constexpr uint32_t BARS     = 229376;
constexpr uint32_t SMEM_BYTES = BARS + 1024 + 1024;
enum : uint32_t {
  B_FULL = 0, B_EMPTY = 5, B_XFREE = 10, B_KVOK = 12, B_ST_Q = 14, B_ST_CTX = 16, B_DONE = 19, B_QFREE = 20, B_QFULL = 22,
  B_S2_FULL = 24, B_S2_EMPTY = 32, B_CTXOK = 40, B_PF = 42, B_ST_KV = 44
};
constexpr int P1_STEPS = 4 * 16 + 2 * 7, P1_XS = P1_STEPS - 2;

template <typename T> __device__ __forceinline__ T* at(const void* base, uint32_t off) {
  asm volatile("" : "+r"(off));
  return reinterpret_cast<T*>(const_cast<char*>(static_cast<const char*>(base)) + off);
}
__device__ __forceinline__ unsigned* flag_at(Flag* f, uint32_t i) { return at<unsigned>(f, i * (uint32_t)sizeof(Flag)); }
__device__ __forceinline__ uint32_t smem_u32(const void* p) { return (uint32_t)__cvta_generic_to_shared(p); }
__device__ __forceinline__ void mbar_init(uint32_t bar, uint32_t cnt) {
  asm volatile("mbarrier.init.shared::cta.b64 [%0], %1;" :: "r"(bar), "r"(cnt) : "memory");
}
__device__ __forceinline__ void mbar_expect_tx(uint32_t bar, uint32_t bytes) {
  asm volatile("mbarrier.arrive.expect_tx.shared::cta.b64 _, [%0], %1;" :: "r"(bar), "r"(bytes) : "memory");
}
__device__ __forceinline__ void mbar_arrive(uint32_t bar) {
  asm volatile("mbarrier.arrive.shared::cta.b64 _, [%0];" :: "r"(bar) : "memory");
}
__device__ __forceinline__ void mbar_arrive_n(uint32_t bar, uint32_t n) {
  asm volatile("mbarrier.arrive.shared::cta.b64 _, [%0], %1;" :: "r"(bar), "r"(n) : "memory");
}
__device__ __forceinline__ void mbar_arrive_remote(uint32_t bar, uint32_t cta) {
  asm volatile("{\n.reg .b32 ra;\nmapa.shared::cluster.u32 ra, %0, %1;\n"
               "mbarrier.arrive.shared::cluster.b64 _, [ra];\n}" :: "r"(bar), "r"(cta) : "memory");
}
__device__ __forceinline__ bool mbar_try(uint32_t bar, uint32_t parity) {
  uint32_t ok;
  asm volatile("{\n.reg .pred p;\nmbarrier.try_wait.parity.shared::cta.b64 p, [%1], %2;\nselp.u32 %0, 1, 0, p;\n}"
               : "=r"(ok) : "r"(bar), "r"(parity) : "memory");
  return ok;
}
__device__ __forceinline__ uint32_t mbar_test(uint32_t bar, uint32_t parity) {
  uint32_t ok;
  asm volatile("{\n.reg .pred p;\nmbarrier.test_wait.parity.shared::cta.b64 p, [%1], %2;\nselp.u32 %0, 1, 0, p;\n}"
               : "=r"(ok) : "r"(bar), "r"(parity) : "memory");
  return ok;
}
constexpr uint32_t SPIN_LIMIT = 1u << 24;
__device__ __forceinline__ void mbar_wait(uint32_t bar, uint32_t parity) {
  if (mbar_try(bar, parity)) return;
  uint32_t n = 0;
  while (!mbar_try(bar, parity)) { if (++n > SPIN_LIMIT) __trap(); }
}
__device__ __forceinline__ void mbar_wait_unless(uint32_t ready, uint32_t bar, uint32_t parity) {
  asm volatile("{\n.reg .pred p;\n.reg .b32 n;\nsetp.ne.u32 p, %0, 0;\nvote.sync.all.pred p, p, 0xffffffff;\n@p bra.uni WDONE;\nmov.u32 n, 0;\n"
               "WLOOP:\nmbarrier.try_wait.parity.shared::cta.b64 p, [%1], %2;\n@p bra.uni WDONE;\nadd.u32 n, n, 1;\nsetp.lt.u32 p, n, %3;\n@p bra.uni WLOOP;\ntrap;\nWDONE:\n}"
               :: "r"(ready), "r"(bar), "r"(parity), "n"(SPIN_LIMIT) : "memory");
}
__device__ __forceinline__ unsigned load_epoch() {
  unsigned long long d; asm volatile("ld.relaxed.gpu.global.u64 %0, [%1];" : "=l"(d) : "l"(&g_flags.done) : "memory");
  return (unsigned)(d >> LOG_DONE);
}
__device__ __forceinline__ void flag_wait(const unsigned* f, unsigned count, unsigned epoch) {
  const unsigned target = (epoch + 1) * count;
  uint32_t n = 0;
  while (true) {
    unsigned v;
    asm volatile("ld.acquire.gpu.global.u32 %0, [%1];" : "=r"(v) : "l"(f) : "memory");
    if ((int)(v - target) >= 0) break;
    if (++n > SPIN_LIMIT) __trap();
    __nanosleep(20);
  }
}
__device__ __forceinline__ void flag_wait_slow(const unsigned* f, unsigned count, unsigned epoch) {
  const unsigned target = (epoch + 1) * count;
  uint32_t n = 0;
  while (true) {
    unsigned v;
    asm volatile("ld.acquire.gpu.global.u32 %0, [%1];" : "=r"(v) : "l"(f) : "memory");
    if ((int)(v - target) >= 0) break;
    if (++n > SPIN_LIMIT / 16) __trap();
    __nanosleep(1000);
  }
}
__device__ __forceinline__ void cta_done(unsigned long long n) { asm volatile("red.relaxed.gpu.global.add.u64 [%0], %1;" :: "l"(&g_flags.done), "l"(n) : "memory"); }
__device__ __forceinline__ void flag_wait_fast(const unsigned* f, unsigned count, unsigned epoch) {
  const unsigned target = (epoch + 1) * count;
  uint32_t n = 0;
  while (true) {
    unsigned v;
    asm volatile("ld.acquire.gpu.global.u32 %0, [%1];" : "=r"(v) : "l"(f) : "memory");
    if ((int)(v - target) >= 0) break;
    if (++n > SPIN_LIMIT) __trap();
  }
}
__device__ __forceinline__ void fence_async_all() { asm volatile("fence.proxy.async.global;" ::: "memory"); }
__device__ __forceinline__ void flag_signal(unsigned* f) { asm volatile("red.release.gpu.global.add.u32 [%0], 1;" :: "l"(f) : "memory"); }
__device__ __forceinline__ void flag_signal_after_bulk(unsigned* f) {
  asm volatile("red.relaxed.gpu.global.add.u32 [%0], 1;" :: "l"(f) : "memory");
}
__device__ __forceinline__ void fence_async_smem() { asm volatile("fence.proxy.async.shared::cta;" ::: "memory"); }
#define HINTS 40
constexpr uint64_t POL_NORMAL = 0x1000000000000000ull, POL_FIRST = 0x12F0000000000000ull;
__device__ __forceinline__ constexpr uint64_t pol(bool first) { return first ? POL_FIRST : POL_NORMAL; }
__device__ __forceinline__ void tma_ld2(uint32_t dst, const CUtensorMap* m, uint32_t bar, int c0, int c1, uint64_t pl = POL_NORMAL) {
  asm volatile("cp.async.bulk.tensor.2d.shared::cluster.global.mbarrier::complete_tx::bytes.L2::cache_hint [%0], [%1, {%3, %4}], [%2], %5;"
               :: "r"(dst), "l"(m), "r"(bar), "r"(c0), "r"(c1), "l"(pl) : "memory");
}
__device__ __forceinline__ void tma_ld3(uint32_t dst, const CUtensorMap* m, uint32_t bar, int c0, int c1, int c2, uint64_t pl = POL_NORMAL) {
  asm volatile("cp.async.bulk.tensor.3d.shared::cluster.global.mbarrier::complete_tx::bytes.L2::cache_hint [%0], [%1, {%3, %4, %5}], [%2], %6;"
               :: "r"(dst), "l"(m), "r"(bar), "r"(c0), "r"(c1), "r"(c2), "l"(pl) : "memory");
}
__device__ __forceinline__ void tma_ld3_mc(uint32_t dst, const CUtensorMap* m, uint32_t bar, int c0, int c1, int c2, uint64_t pl = POL_NORMAL) {
  asm volatile("cp.async.bulk.tensor.3d.shared::cluster.global.mbarrier::complete_tx::bytes.multicast::cluster.L2::cache_hint [%0], [%1, {%3, %4, %5}], [%2], %6, %7;"
               :: "r"(dst), "l"(m), "r"(bar), "r"(c0), "r"(c1), "r"(c2), "h"((uint16_t)3), "l"(pl) : "memory");
}
__device__ __forceinline__ void bulk_ld(uint32_t dst, const void* src, uint32_t bytes, uint32_t bar) {
  asm volatile("cp.async.bulk.shared::cluster.global.mbarrier::complete_tx::bytes [%0], [%1], %2, [%3];"
               :: "r"(dst), "l"(src), "r"(bytes), "r"(bar) : "memory");
}
__device__ __forceinline__ void bulk_ld_p(uint32_t dst, const void* src, uint32_t bytes, uint32_t bar, uint64_t pl) {
  asm volatile("cp.async.bulk.shared::cluster.global.mbarrier::complete_tx::bytes.L2::cache_hint [%0], [%1], %2, [%3], %4;"
               :: "r"(dst), "l"(src), "r"(bytes), "r"(bar), "l"(pl) : "memory");
}
__device__ __forceinline__ void bulk_ld_mc(uint32_t dst, const void* src, uint32_t bytes, uint32_t bar, uint64_t pl) {
  asm volatile("cp.async.bulk.shared::cluster.global.mbarrier::complete_tx::bytes.multicast::cluster.L2::cache_hint [%0], [%1], %2, [%3], %4, %5;"
               :: "r"(dst), "l"(src), "r"(bytes), "r"(bar), "h"((uint16_t)3), "l"(pl) : "memory");
}
__device__ __forceinline__ void tma_st3(const CUtensorMap* m, uint32_t src, int c0, int c1, int c2) {
  asm volatile("cp.async.bulk.tensor.3d.global.shared::cta.bulk_group.L2::cache_hint [%0, {%2, %3, %4}], [%1], %5;"
               :: "l"(m), "r"(src), "r"(c0), "r"(c1), "r"(c2), "l"(pol(HINTS & 1024)) : "memory");
}
__device__ __forceinline__ void tma_ld2_mc(uint32_t dst, const CUtensorMap* m, uint32_t bar, int c0, int c1, uint64_t pl = POL_NORMAL) {
  asm volatile("cp.async.bulk.tensor.2d.shared::cluster.global.mbarrier::complete_tx::bytes.multicast::cluster.L2::cache_hint [%0], [%1, {%3, %4}], [%2], %5, %6;"
               :: "r"(dst), "l"(m), "r"(bar), "r"(c0), "r"(c1), "h"((uint16_t)3), "l"(pl) : "memory");
}
__device__ __forceinline__ void tma_ld5_mc(uint32_t dst, const CUtensorMap* m, uint32_t bar, int c0, int c4, uint64_t pl = POL_NORMAL) {
  asm volatile("cp.async.bulk.tensor.5d.shared::cluster.global.mbarrier::complete_tx::bytes.multicast::cluster.L2::cache_hint [%0], [%1, {%3, %7, %7, %7, %4}], [%2], %5, %6;"
               :: "r"(dst), "l"(m), "r"(bar), "r"(c0), "r"(c4), "h"((uint16_t)3), "l"(pl), "r"(0) : "memory");
}
__device__ __forceinline__ void tma_st2(const CUtensorMap* m, uint32_t src, int c0, int c1) {
  asm volatile("cp.async.bulk.tensor.2d.global.shared::cta.bulk_group [%0, {%2, %3}], [%1];"
               :: "l"(m), "r"(src), "r"(c0), "r"(c1) : "memory");
}
__device__ __forceinline__ void tma_red2(const CUtensorMap* m, uint32_t src, int c0, int c1) {
  asm volatile("cp.reduce.async.bulk.tensor.2d.global.shared::cta.add.bulk_group [%0, {%2, %3}], [%1];"
               :: "l"(m), "r"(src), "r"(c0), "r"(c1) : "memory");
}
__device__ __forceinline__ void bulk_commit() { asm volatile("cp.async.bulk.commit_group;" ::: "memory"); }
__device__ __forceinline__ void bulk_wait_read() { asm volatile("cp.async.bulk.wait_group.read 0;" ::: "memory"); }
__device__ __forceinline__ void bulk_wait_all() { asm volatile("cp.async.bulk.wait_group 0;" ::: "memory"); }
__device__ __forceinline__ void prefetch_map(const CUtensorMap* m) { asm volatile("prefetch.tensormap [%0];" :: "l"(m) : "memory"); }
__device__ __forceinline__ void wg_fence() { asm volatile("wgmma.fence.sync.aligned;" ::: "memory"); }
__device__ __forceinline__ void wg_commit() { asm volatile("wgmma.commit_group.sync.aligned;" ::: "memory"); }
template <int N> __device__ __forceinline__ void wg_wait() { asm volatile("wgmma.wait_group.sync.aligned %0;" :: "n"(N) : "memory"); }
template <int N> __device__ __forceinline__ void reg_fence(float (&d)[N]) {
#pragma unroll
  for (int i = 0; i < N; i++) asm volatile("" : "+f"(d[i]) :: "memory");
}
template <int N> __device__ __forceinline__ void reg_fence(uint32_t (&d)[N]) {
#pragma unroll
  for (int i = 0; i < N; i++) asm volatile("" : "+r"(d[i]) :: "memory");
}
__device__ __forceinline__ uint32_t fresh_tid() { uint32_t t; asm volatile("mov.u32 %0, %%tid.x;" : "=r"(t)); return t; }
__device__ __forceinline__ uint32_t lane_base16() {
  const uint32_t t = fresh_tid(), lane = t & 31, wq = (t >> 5) & 3;
  return (16 * wq + (lane & 7) + 8 * ((lane >> 3) & 1)) * 128 + (((lane >> 4) ^ (lane & 7)) << 4);
}
__device__ __forceinline__ void cluster_arrive() { asm volatile("barrier.cluster.arrive.relaxed.aligned;" ::: "memory"); }
__device__ __forceinline__ void cluster_wait() { asm volatile("barrier.cluster.wait.acquire.aligned;" ::: "memory"); }
__device__ __forceinline__ void named_sync(int id, int n) { asm volatile("bar.sync %0, %1;" :: "r"(id), "r"(n) : "memory"); }
__device__ __forceinline__ void named_arrive(int id, int n) { asm volatile("bar.arrive %0, %1;" :: "r"(id), "r"(n) : "memory"); }
__device__ __forceinline__ uint32_t pack_bf16(float lo, float hi) {
  uint32_t r; asm("cvt.rn.bf16x2.f32 %0, %1, %2;" : "=r"(r) : "f"(hi), "f"(lo)); return r;
}
__device__ __forceinline__ float ex2(float x) { float y; asm("ex2.approx.ftz.f32 %0, %1;" : "=f"(y) : "f"(x)); return y; }
__device__ __forceinline__ void stsm4(uint32_t addr, uint32_t a, uint32_t b, uint32_t c, uint32_t d) {
  asm volatile("stmatrix.sync.aligned.m8n8.x4.shared.b16 [%0], {%1, %2, %3, %4};" :: "r"(addr), "r"(a), "r"(b), "r"(c), "r"(d) : "memory");
}
__device__ __forceinline__ uint64_t mk_desc(uint32_t addr, uint32_t lbo, uint32_t sbo) {
  return (uint64_t)(((addr & 0x3FFFF) >> 4) | ((lbo >> 4) << 16)) | ((uint64_t)((sbo >> 4) | (1u << 30)) << 32);
}
__device__ __forceinline__ uint64_t desc_k(uint32_t addr)  { return mk_desc(addr, 16, 1024); }
__device__ __forceinline__ uint64_t desc_mn(uint32_t addr) { return mk_desc(addr, 8192, 1024); }
__device__ __forceinline__ uint64_t desc_64(uint32_t addr) { return (uint64_t)(((addr & 0x3FFFF) >> 4) | ((4096u >> 4) << 16)) | ((uint64_t)((512u >> 4) | (2u << 30)) << 32); }
__device__ __forceinline__ uint64_t desc_add(uint64_t d, uint32_t bytes) { return d + (bytes >> 4); }

__device__ __forceinline__ void wgmma_ss_n256_tb(float (&d)[128], uint64_t da, uint64_t db, int sd) {
  asm volatile("{\n.reg .pred p;\nsetp.ne.b32 p, %130, 0;\n"
    "wgmma.mma_async.sync.aligned.m64n256k16.f32.bf16.bf16 "
    "{%0, %1, %2, %3, %4, %5, %6, %7, %8, %9, %10, %11, %12, %13, %14, %15, "
    "%16, %17, %18, %19, %20, %21, %22, %23, %24, %25, %26, %27, %28, %29, %30, %31, "
    "%32, %33, %34, %35, %36, %37, %38, %39, %40, %41, %42, %43, %44, %45, %46, %47, "
    "%48, %49, %50, %51, %52, %53, %54, %55, %56, %57, %58, %59, %60, %61, %62, %63, "
    "%64, %65, %66, %67, %68, %69, %70, %71, %72, %73, %74, %75, %76, %77, %78, %79, "
    "%80, %81, %82, %83, %84, %85, %86, %87, %88, %89, %90, %91, %92, %93, %94, %95, "
    "%96, %97, %98, %99, %100, %101, %102, %103, %104, %105, %106, %107, %108, %109, %110, %111, "
    "%112, %113, %114, %115, %116, %117, %118, %119, %120, %121, %122, %123, %124, %125, %126, %127}, "
    "%128, %129, p, 1, 1, 0, 1;\n}"
    : "+f"(d[0]), "+f"(d[1]), "+f"(d[2]), "+f"(d[3]), "+f"(d[4]), "+f"(d[5]), "+f"(d[6]), "+f"(d[7]),
      "+f"(d[8]), "+f"(d[9]), "+f"(d[10]), "+f"(d[11]), "+f"(d[12]), "+f"(d[13]), "+f"(d[14]), "+f"(d[15]),
      "+f"(d[16]), "+f"(d[17]), "+f"(d[18]), "+f"(d[19]), "+f"(d[20]), "+f"(d[21]), "+f"(d[22]), "+f"(d[23]),
      "+f"(d[24]), "+f"(d[25]), "+f"(d[26]), "+f"(d[27]), "+f"(d[28]), "+f"(d[29]), "+f"(d[30]), "+f"(d[31]),
      "+f"(d[32]), "+f"(d[33]), "+f"(d[34]), "+f"(d[35]), "+f"(d[36]), "+f"(d[37]), "+f"(d[38]), "+f"(d[39]),
      "+f"(d[40]), "+f"(d[41]), "+f"(d[42]), "+f"(d[43]), "+f"(d[44]), "+f"(d[45]), "+f"(d[46]), "+f"(d[47]),
      "+f"(d[48]), "+f"(d[49]), "+f"(d[50]), "+f"(d[51]), "+f"(d[52]), "+f"(d[53]), "+f"(d[54]), "+f"(d[55]),
      "+f"(d[56]), "+f"(d[57]), "+f"(d[58]), "+f"(d[59]), "+f"(d[60]), "+f"(d[61]), "+f"(d[62]), "+f"(d[63]),
      "+f"(d[64]), "+f"(d[65]), "+f"(d[66]), "+f"(d[67]), "+f"(d[68]), "+f"(d[69]), "+f"(d[70]), "+f"(d[71]),
      "+f"(d[72]), "+f"(d[73]), "+f"(d[74]), "+f"(d[75]), "+f"(d[76]), "+f"(d[77]), "+f"(d[78]), "+f"(d[79]),
      "+f"(d[80]), "+f"(d[81]), "+f"(d[82]), "+f"(d[83]), "+f"(d[84]), "+f"(d[85]), "+f"(d[86]), "+f"(d[87]),
      "+f"(d[88]), "+f"(d[89]), "+f"(d[90]), "+f"(d[91]), "+f"(d[92]), "+f"(d[93]), "+f"(d[94]), "+f"(d[95]),
      "+f"(d[96]), "+f"(d[97]), "+f"(d[98]), "+f"(d[99]), "+f"(d[100]), "+f"(d[101]), "+f"(d[102]), "+f"(d[103]),
      "+f"(d[104]), "+f"(d[105]), "+f"(d[106]), "+f"(d[107]), "+f"(d[108]), "+f"(d[109]), "+f"(d[110]), "+f"(d[111]),
      "+f"(d[112]), "+f"(d[113]), "+f"(d[114]), "+f"(d[115]), "+f"(d[116]), "+f"(d[117]), "+f"(d[118]), "+f"(d[119]),
      "+f"(d[120]), "+f"(d[121]), "+f"(d[122]), "+f"(d[123]), "+f"(d[124]), "+f"(d[125]), "+f"(d[126]), "+f"(d[127])
    : "l"(da), "l"(db), "r"(sd));
}
__device__ __forceinline__ void wgmma_ss_n64(float (&d)[32], uint64_t da, uint64_t db, int sd) {
  asm volatile("{\n.reg .pred p;\nsetp.ne.b32 p, %34, 0;\n"
    "wgmma.mma_async.sync.aligned.m64n64k16.f32.bf16.bf16 "
    "{%0, %1, %2, %3, %4, %5, %6, %7, %8, %9, %10, %11, %12, %13, %14, %15, "
    "%16, %17, %18, %19, %20, %21, %22, %23, %24, %25, %26, %27, %28, %29, %30, %31}, "
    "%32, %33, p, 1, 1, 0, 0;\n}"
    : "+f"(d[0]), "+f"(d[1]), "+f"(d[2]), "+f"(d[3]), "+f"(d[4]), "+f"(d[5]), "+f"(d[6]), "+f"(d[7]),
      "+f"(d[8]), "+f"(d[9]), "+f"(d[10]), "+f"(d[11]), "+f"(d[12]), "+f"(d[13]), "+f"(d[14]), "+f"(d[15]),
      "+f"(d[16]), "+f"(d[17]), "+f"(d[18]), "+f"(d[19]), "+f"(d[20]), "+f"(d[21]), "+f"(d[22]), "+f"(d[23]),
      "+f"(d[24]), "+f"(d[25]), "+f"(d[26]), "+f"(d[27]), "+f"(d[28]), "+f"(d[29]), "+f"(d[30]), "+f"(d[31])
    : "l"(da), "l"(db), "r"(sd));
}
__device__ __forceinline__ void wgmma_rs_n256_tb(float (&d)[128], uint32_t a0, uint32_t a1, uint32_t a2, uint32_t a3, uint64_t db, int sd) {
  asm volatile("{\n.reg .pred p;\nsetp.ne.b32 p, %133, 0;\n"
    "wgmma.mma_async.sync.aligned.m64n256k16.f32.bf16.bf16 "
    "{%0, %1, %2, %3, %4, %5, %6, %7, %8, %9, %10, %11, %12, %13, %14, %15, "
    "%16, %17, %18, %19, %20, %21, %22, %23, %24, %25, %26, %27, %28, %29, %30, %31, "
    "%32, %33, %34, %35, %36, %37, %38, %39, %40, %41, %42, %43, %44, %45, %46, %47, "
    "%48, %49, %50, %51, %52, %53, %54, %55, %56, %57, %58, %59, %60, %61, %62, %63, "
    "%64, %65, %66, %67, %68, %69, %70, %71, %72, %73, %74, %75, %76, %77, %78, %79, "
    "%80, %81, %82, %83, %84, %85, %86, %87, %88, %89, %90, %91, %92, %93, %94, %95, "
    "%96, %97, %98, %99, %100, %101, %102, %103, %104, %105, %106, %107, %108, %109, %110, %111, "
    "%112, %113, %114, %115, %116, %117, %118, %119, %120, %121, %122, %123, %124, %125, %126, %127}, "
    "{%128, %129, %130, %131}, %132, p, 1, 1, 1;\n}"
    : "+f"(d[0]), "+f"(d[1]), "+f"(d[2]), "+f"(d[3]), "+f"(d[4]), "+f"(d[5]), "+f"(d[6]), "+f"(d[7]),
      "+f"(d[8]), "+f"(d[9]), "+f"(d[10]), "+f"(d[11]), "+f"(d[12]), "+f"(d[13]), "+f"(d[14]), "+f"(d[15]),
      "+f"(d[16]), "+f"(d[17]), "+f"(d[18]), "+f"(d[19]), "+f"(d[20]), "+f"(d[21]), "+f"(d[22]), "+f"(d[23]),
      "+f"(d[24]), "+f"(d[25]), "+f"(d[26]), "+f"(d[27]), "+f"(d[28]), "+f"(d[29]), "+f"(d[30]), "+f"(d[31]),
      "+f"(d[32]), "+f"(d[33]), "+f"(d[34]), "+f"(d[35]), "+f"(d[36]), "+f"(d[37]), "+f"(d[38]), "+f"(d[39]),
      "+f"(d[40]), "+f"(d[41]), "+f"(d[42]), "+f"(d[43]), "+f"(d[44]), "+f"(d[45]), "+f"(d[46]), "+f"(d[47]),
      "+f"(d[48]), "+f"(d[49]), "+f"(d[50]), "+f"(d[51]), "+f"(d[52]), "+f"(d[53]), "+f"(d[54]), "+f"(d[55]),
      "+f"(d[56]), "+f"(d[57]), "+f"(d[58]), "+f"(d[59]), "+f"(d[60]), "+f"(d[61]), "+f"(d[62]), "+f"(d[63]),
      "+f"(d[64]), "+f"(d[65]), "+f"(d[66]), "+f"(d[67]), "+f"(d[68]), "+f"(d[69]), "+f"(d[70]), "+f"(d[71]),
      "+f"(d[72]), "+f"(d[73]), "+f"(d[74]), "+f"(d[75]), "+f"(d[76]), "+f"(d[77]), "+f"(d[78]), "+f"(d[79]),
      "+f"(d[80]), "+f"(d[81]), "+f"(d[82]), "+f"(d[83]), "+f"(d[84]), "+f"(d[85]), "+f"(d[86]), "+f"(d[87]),
      "+f"(d[88]), "+f"(d[89]), "+f"(d[90]), "+f"(d[91]), "+f"(d[92]), "+f"(d[93]), "+f"(d[94]), "+f"(d[95]),
      "+f"(d[96]), "+f"(d[97]), "+f"(d[98]), "+f"(d[99]), "+f"(d[100]), "+f"(d[101]), "+f"(d[102]), "+f"(d[103]),
      "+f"(d[104]), "+f"(d[105]), "+f"(d[106]), "+f"(d[107]), "+f"(d[108]), "+f"(d[109]), "+f"(d[110]), "+f"(d[111]),
      "+f"(d[112]), "+f"(d[113]), "+f"(d[114]), "+f"(d[115]), "+f"(d[116]), "+f"(d[117]), "+f"(d[118]), "+f"(d[119]),
      "+f"(d[120]), "+f"(d[121]), "+f"(d[122]), "+f"(d[123]), "+f"(d[124]), "+f"(d[125]), "+f"(d[126]), "+f"(d[127])
    : "r"(a0), "r"(a1), "r"(a2), "r"(a3), "l"(db), "r"(sd));
}
__device__ __forceinline__ void wgmma_rs_n64_tb(float (&d)[32], uint32_t a0, uint32_t a1, uint32_t a2, uint32_t a3, uint64_t db, int sd) {
  asm volatile("{\n.reg .pred p;\nsetp.ne.b32 p, %37, 0;\n"
    "wgmma.mma_async.sync.aligned.m64n64k16.f32.bf16.bf16 "
    "{%0, %1, %2, %3, %4, %5, %6, %7, %8, %9, %10, %11, %12, %13, %14, %15, "
    "%16, %17, %18, %19, %20, %21, %22, %23, %24, %25, %26, %27, %28, %29, %30, %31}, "
    "{%32, %33, %34, %35}, %36, p, 1, 1, 1;\n}"
    : "+f"(d[0]), "+f"(d[1]), "+f"(d[2]), "+f"(d[3]), "+f"(d[4]), "+f"(d[5]), "+f"(d[6]), "+f"(d[7]),
      "+f"(d[8]), "+f"(d[9]), "+f"(d[10]), "+f"(d[11]), "+f"(d[12]), "+f"(d[13]), "+f"(d[14]), "+f"(d[15]),
      "+f"(d[16]), "+f"(d[17]), "+f"(d[18]), "+f"(d[19]), "+f"(d[20]), "+f"(d[21]), "+f"(d[22]), "+f"(d[23]),
      "+f"(d[24]), "+f"(d[25]), "+f"(d[26]), "+f"(d[27]), "+f"(d[28]), "+f"(d[29]), "+f"(d[30]), "+f"(d[31])
    : "r"(a0), "r"(a1), "r"(a2), "r"(a3), "l"(db), "r"(sd));
}
__device__ __forceinline__ void wgmma_rs_n32(float (&d)[16], uint32_t a0, uint32_t a1, uint32_t a2, uint32_t a3, uint64_t db, int sd) {
  asm volatile("{\n.reg .pred p;\nsetp.ne.b32 p, %21, 0;\n"
    "wgmma.mma_async.sync.aligned.m64n32k16.f32.bf16.bf16 "
    "{%0, %1, %2, %3, %4, %5, %6, %7, %8, %9, %10, %11, %12, %13, %14, %15}, "
    "{%16, %17, %18, %19}, %20, p, 1, 1, 0;\n}"
    : "+f"(d[0]), "+f"(d[1]), "+f"(d[2]), "+f"(d[3]), "+f"(d[4]), "+f"(d[5]), "+f"(d[6]), "+f"(d[7]),
      "+f"(d[8]), "+f"(d[9]), "+f"(d[10]), "+f"(d[11]), "+f"(d[12]), "+f"(d[13]), "+f"(d[14]), "+f"(d[15])
    : "r"(a0), "r"(a1), "r"(a2), "r"(a3), "l"(db), "r"(sd));
}
__device__ __forceinline__ void wgmma_rs_n64(float (&d)[32], uint32_t a0, uint32_t a1, uint32_t a2, uint32_t a3, uint64_t db, int sd) {
  asm volatile("{\n.reg .pred p;\nsetp.ne.b32 p, %37, 0;\n"
    "wgmma.mma_async.sync.aligned.m64n64k16.f32.bf16.bf16 "
    "{%0, %1, %2, %3, %4, %5, %6, %7, %8, %9, %10, %11, %12, %13, %14, %15, "
    "%16, %17, %18, %19, %20, %21, %22, %23, %24, %25, %26, %27, %28, %29, %30, %31}, "
    "{%32, %33, %34, %35}, %36, p, 1, 1, 0;\n}"
    : "+f"(d[0]), "+f"(d[1]), "+f"(d[2]), "+f"(d[3]), "+f"(d[4]), "+f"(d[5]), "+f"(d[6]), "+f"(d[7]),
      "+f"(d[8]), "+f"(d[9]), "+f"(d[10]), "+f"(d[11]), "+f"(d[12]), "+f"(d[13]), "+f"(d[14]), "+f"(d[15]),
      "+f"(d[16]), "+f"(d[17]), "+f"(d[18]), "+f"(d[19]), "+f"(d[20]), "+f"(d[21]), "+f"(d[22]), "+f"(d[23]),
      "+f"(d[24]), "+f"(d[25]), "+f"(d[26]), "+f"(d[27]), "+f"(d[28]), "+f"(d[29]), "+f"(d[30]), "+f"(d[31])
    : "r"(a0), "r"(a1), "r"(a2), "r"(a3), "l"(db), "r"(sd));
}

__device__ __forceinline__ uint4 lds16(uint32_t a) {
  uint4 v; asm volatile("ld.shared.v4.u32 {%0, %1, %2, %3}, [%4];" : "=r"(v.x), "=r"(v.y), "=r"(v.z), "=r"(v.w) : "r"(a) : "memory"); return v;
}
__device__ __forceinline__ void sts16(uint32_t a, uint32_t x, uint32_t y, uint32_t z, uint32_t w) {
  asm volatile("st.shared.v4.u32 [%0], {%1, %2, %3, %4};" :: "r"(a), "r"(x), "r"(y), "r"(z), "r"(w) : "memory");
}
__device__ __forceinline__ uint32_t lds4(uint32_t a) { uint32_t v; asm volatile("ld.shared.u32 %0, [%1];" : "=r"(v) : "r"(a) : "memory"); return v; }
__device__ __forceinline__ uint32_t lds4v(uint32_t a) { uint32_t v; asm volatile("ld.volatile.shared.u32 %0, [%1];" : "=r"(v) : "r"(a) : "memory"); return v; }
__device__ __forceinline__ uint32_t bmul(uint32_t a, uint32_t b) { uint32_t r; asm("mul.rn.bf16x2 %0, %1, %2;" : "=r"(r) : "r"(a), "r"(b)); return r; }
__device__ __forceinline__ uint32_t badd(uint32_t a, uint32_t b) { uint32_t r; asm("add.rn.bf16x2 %0, %1, %2;" : "=r"(r) : "r"(a), "r"(b)); return r; }

__device__ __forceinline__ void ldsm4(uint32_t (&r)[4], uint32_t a) {
  asm volatile("ldmatrix.sync.aligned.m8n8.x4.shared.b16 {%0, %1, %2, %3}, [%4];" : "=r"(r[0]), "=r"(r[1]), "=r"(r[2]), "=r"(r[3]) : "r"(a) : "memory");
}
__device__ __forceinline__ uint32_t transpose8(uint32_t a) { uint32_t d; asm volatile("movmatrix.sync.aligned.m8n8.trans.b16 %0, %1;" : "=r"(d) : "r"(a)); return d; }

__device__ __forceinline__ void mma16816(float (&d)[4], const uint32_t (&a)[4], uint32_t b0, uint32_t b1) {
  asm volatile("mma.sync.aligned.m16n8k16.row.col.f32.bf16.bf16.f32 {%0, %1, %2, %3}, {%4, %5, %6, %7}, {%8, %9}, {%0, %1, %2, %3};"
               : "+f"(d[0]), "+f"(d[1]), "+f"(d[2]), "+f"(d[3]) : "r"(a[0]), "r"(a[1]), "r"(a[2]), "r"(a[3]), "r"(b0), "r"(b1));
}

#define EXP_SIDE 0
#define SIDE_AHEAD 3
#define ZERO_RD 4
#define CTX_SPLIT 8
#define CONV_EARLY 8
#define CONV_FENCE 12
#define CTX_LD 16
#define HOOK_DEP s[4 * jj]
#define PEEK_JJ 7
#define PF_CTX 2
#define STG_PAT 1
#define KV_ORDER 3
#define QFIRST 0
#define UNICAST 2
#define PF_MAPS 3
#define CONV_ARRIVE 13
#define ARRIVE_KK 12
#define SIDE_DELAY_NS 4000
#define KVH(h) (h)
#define HEAD_MAP 2
#define EARLY_LD 1
constexpr int RED_BAR = 6;
constexpr int CV_BAR = 5;
constexpr int PP_BAR = 3;
template <int V> struct Int { static constexpr int value = V; };
struct Ring {
  uint32_t slot, phase;
  __device__ __forceinline__ void next() { if (++slot == NSLOT) { slot = 0; phase ^= 1; } }
};
__device__ __forceinline__ uint32_t bar_addr(uint32_t sb, uint32_t i) { return sb + BARS + 8 * i; }

__device__ __forceinline__ int q_tile(int h, int j, int which) { return ((h < 8) == (which == 0)) ? 15 - j : j; }

constexpr int T_QB = QFIRST ? 0 : 4, IT_KV = QFIRST ? 7 : 0, IT_QB = QFIRST ? 0 : 64;
constexpr int KV_ISV  = KV_ORDER == 0 ? 0xC : KV_ORDER == 1 ? 0xA : KV_ORDER == 2 ? 0x6 : KV_ORDER == 3 ? 0xA : 0xC;
constexpr int KV_PART = KV_ORDER == 0 ? 0xA : KV_ORDER == 1 ? 0xC : KV_ORDER == 2 ? 0xC : KV_ORDER == 3 ? 0x3 : KV_ORDER == 4 ? 0x5 : 0x9;
constexpr int LAST_PART = KV_PART >> 3;
constexpr int T_FIRST = (((KV_PART >> 2) & 1) != LAST_PART ? 3 : 2) + QFIRST;
constexpr int T_LAST = 4 + QFIRST;
__device__ __forceinline__ int p1_isv(int n) { return (KV_ISV >> n) & 1; }
__device__ __forceinline__ int att_head(int h, int which) { return (h & 7) + 8 * which; }
__device__ __forceinline__ int p1_head(int h, int n) { return (h & 7) + 8 * ((KV_PART >> n) & 1); }
__device__ __forceinline__ int p1_rows(int h, int j, int n) { return q_tile(h, j, 0); }
#define KV_FLAG(h) ((h) & 7)
#define KV_COUNT 32
#define F_PART1 (2 * own - 1)

__device__ __forceinline__ void load_tile4(uint32_t dst, const CUtensorMap* m, uint32_t full, int row, int blk0, int rank, bool shared, uint64_t pl = POL_NORMAL) {
  if (shared) {
    tma_ld3_mc(dst + rank * 16384, m, full, 0, row, blk0 + 2 * rank, pl);
  } else {
    tma_ld3(dst, m, full, 0, row, blk0, pl);
    tma_ld3(dst + 16384, m, full, 0, row, blk0 + 2, pl);
  }
}
__device__ __forceinline__ void producer_main(const Params& p, uint32_t sb, int h, int j) {
  const int rank = j & 1;
  Ring r{EARLY_LD, 0};
  auto wait_slot = [&]() { mbar_wait(bar_addr(sb, B_EMPTY + r.slot), r.phase ^ 1); };
  auto load_a = [&](int it, uint32_t dst, uint32_t full) {
    const unsigned u = it - IT_KV;
    if (u < 64) tma_ld2(dst, &p.ckv, full, (u & 15) * 64, p1_rows(h, j, u >> 4) * 128, pol((HINTS & 2) && u >= 48));
    else tma_ld2(dst, &p.x, full, (it < 71 ? it - IT_QB : it - 71) * 64, q_tile(h, j, it < 71) * 128, pol((HINTS & 64) && it >= 71));
  };
  uint32_t prev = 0;
#pragma unroll 1
  for (int it = EARLY_LD; it < P1_STEPS; it++) {
    wait_slot();
    if (it > EARLY_LD && it <= P1_XS) load_a(it - 1, sb + QREG + ((it - 1) & 3) * 16384, prev);
    const uint32_t full = bar_addr(sb, B_FULL + r.slot), dst = sb + r.slot * SLOT;
    mbar_expect_tx(full, it < P1_XS ? 49152 : 32768);
    const unsigned u = it - IT_KV;
    if (u < 64) load_tile4(dst, p1_isv(u >> 4) ? &p.wuv : &p.wuk, full, (u & 15) * 64, p1_head(h, u >> 4) * 4, rank, !(UNICAST & 2), pol(HINTS & 1));
    else load_tile4(dst, &p.wq, full, (it < 71 ? it - IT_QB : it - 71) * 64, att_head(h, it < 71) * 4, rank, !(UNICAST & 2), pol((HINTS & 4) && it >= 71));
    prev = full;
    r.next();
    if (it == P1_XS) {
      wait_slot();
      const uint32_t f2 = bar_addr(sb, B_FULL + r.slot);
      mbar_expect_tx(f2, 32768);
      load_a(P1_XS, sb + r.slot * SLOT, f2);
      load_a(P1_XS + 1, sb + r.slot * SLOT + 16384, f2);
      r.next();
    }
  }
  const int qa = q_tile(h, j, 0), na = 2 * qa + 2, own = 2 * (qa & ~1) + 2;
#pragma unroll 1
  for (int f = 0; f < 68; f++) {
    const bool isK = (f == 0) || ((f & 1) && f < 67);
    const int i = isK ? (f + 1) >> 1 : (f - 1) >> 1, which = i >= na;
    if (f == 0 || f == F_PART1) mbar_wait(bar_addr(sb, B_KVOK + (f & 1)), 0);
    wait_slot();
    const uint32_t full = bar_addr(sb, B_FULL + r.slot);
    mbar_expect_tx(full, 32768);
    const uint32_t src = (uint32_t)(((isK ? 0 : NH) + KVH(att_head(h, which))) * 32 + (which ? 33 - i : i)) * 32768;
    const uint64_t pl = pol(which ? (HINTS & 32) : (HINTS & 8));
    if (!(UNICAST & 1) && (i & ~1) != own) bulk_ld_mc(sb + r.slot * SLOT + rank * 16384, at<uint8_t>(g_kv, src + rank * 16384), 16384, full, pl);
    else bulk_ld_p(sb + r.slot * SLOT, at<uint8_t>(g_kv, src), 32768, full, pl);
    r.next();
  }
#pragma unroll 1
  for (int f = 0; f < 14; f++) {
    const int ch = f < 12 ? 2 * (f >> 2) + (f & 1) : 6, par = f < 12 ? (f >> 1) & 1 : f & 1;
    wait_slot();
    const uint32_t full = bar_addr(sb, B_FULL + r.slot);
    mbar_expect_tx(full, 32768);
    tma_ld5_mc(sb + r.slot * SLOT + rank * 16384, &p.wo, full, ch * 64, (par ? att_head(h ^ 8, 0) : att_head(h, 1)) * 8 + rank * 4, pol(HINTS & 16));
    r.next();
  }
}

__device__ __forceinline__ void helper_main(const Params& p, uint32_t sb, int h, int j, int w) {
  const unsigned epoch = load_epoch();
  const int cta = h * 8 + j, qb = q_tile(h, j, 1);
  const uint32_t qreg = sb + QREG + w * 32768, qfull = bar_addr(sb, B_QFULL + w);
  auto acquire = [&]() {
    flag_wait(flag_at(g_flags.kv_ready, KV_FLAG(h) * 2 + w), KV_COUNT, epoch);
    fence_async_all();
    mbar_arrive(bar_addr(sb, B_KVOK + w));
  };
  if (QFIRST) mbar_wait(bar_addr(sb, B_ST_Q + w), 0);
  mbar_wait(bar_addr(sb, B_ST_KV + w), 0);
  flag_signal(flag_at(g_flags.kv_ready, KV_FLAG(h) * 2 + (LAST_PART ^ 1)));
  if (w != LAST_PART) acquire();
  mbar_wait(bar_addr(sb, B_ST_KV + 2 + w), 0);
  flag_signal(flag_at(g_flags.kv_ready, KV_FLAG(h) * 2 + LAST_PART));
  const bool late = false;
  if (w == LAST_PART && !late) acquire();
  if (!QFIRST) { mbar_wait(bar_addr(sb, B_ST_Q + w), 0); asm volatile("fence.release.gpu;" ::: "memory"); }
  fence_async_all();
  mbar_wait(bar_addr(sb, B_QFREE + w), 0);
  mbar_expect_tx(qfull, 32768);
  bulk_ld(qreg, at<uint8_t>(g_qc, (cta * 2 + w) * 32768), 32768, qfull);
  if (w == LAST_PART && late) acquire();
  auto publish = [&]() { mbar_wait(bar_addr(sb, B_ST_CTX + w), 0); flag_signal(flag_at(g_flags.ctx_ready, cta * 2 + w)); };
  if (qb >= 8) publish();
  flag_wait(flag_at(g_flags.ctx_ready, (cta ^ 64) * 2 + (w ^ 1)), 1, epoch);
  mbar_arrive(bar_addr(sb, B_CTXOK + w));
  if (qb < 8) publish();
  flag_wait(flag_at(g_flags.zero_ready, qb), 8, epoch);
  fence_async_all();
#pragma unroll 1
  for (int ch = 0; ch < 7; ch++) {
    mbar_wait(bar_addr(sb, B_S2_FULL + w * 4 + (ch & 3)), ch >> 2);
    tma_red2(&p.o, qreg + (ch & 3) * 8192, DA + ch * 64, qb * 128 + (w ^ 1) * 64);
    bulk_commit();
    if (ch < 3) { bulk_wait_read(); mbar_arrive(bar_addr(sb, B_S2_EMPTY + w * 4 + ch)); }
  }
  bulk_wait_read();
  GT(48 + w);
}

__device__ __forceinline__ void store_block(uint32_t base, uint32_t lanebase, const uint32_t (&pk)[16]) {
#pragma unroll
  for (int J = 0; J < 8; J += 2) stsm4(base + (lanebase ^ (J << 4)), pk[2 * J], pk[2 * J + 1], pk[2 * J + 2], pk[2 * J + 3]);
}
__device__ __forceinline__ void pack_chunks(uint32_t (&pk)[64], const float (&acc)[128]) {
#pragma unroll
  for (int i = 0; i < 64; i++) { const int e = 16 * (i >> 3) + 4 * (i & 3) + 2 * ((i >> 2) & 1); pk[i] = pack_bf16(acc[e], acc[e + 1]); }
}
__device__ __forceinline__ uint32_t chunk_off() { const uint32_t t = fresh_tid(); return (t & 96) * 32 + (t & 28) * 16 + (((t ^ (t >> 3)) & 3) << 4); }
__device__ __forceinline__ void warp_arrive(uint32_t bar, int lane) { __syncwarp(); if (lane == 0) mbar_arrive(bar); }

__device__ __forceinline__ void consumer_main(const Params& p, uint32_t sb, int h, int j, int w, int wq) {
  const int lane = threadIdx.x & 31;
  const int rank = j & 1;

  auto turn_begin = [&]() { named_sync(PP_BAR + w, 256); };
  auto turn_end = [&]() { named_arrive(PP_BAR + (w ^ 1), 256); };
  Ring r{0, 0};
  auto take = [&](uint32_t ready = 0) { const uint32_t sl = r.slot; mbar_wait_unless(ready, bar_addr(sb, B_FULL + sl), r.phase); r.next(); return sl; };
  uint32_t rdy0 = 0, rdy1 = 0;
  auto peek2 = [&]() { Ring q = r; rdy0 = mbar_test(bar_addr(sb, B_FULL + q.slot), q.phase); q.next(); rdy1 = mbar_test(bar_addr(sb, B_FULL + q.slot), q.phase); };
  auto give = [&](uint32_t sl) { if (lane < 2) mbar_arrive_remote(bar_addr(sb, B_EMPTY + sl), rank ^ lane); };
  float acc[128];
#pragma unroll
  for (int i = 0; i < 128; i++) acc[i] = 0.f;
  uint32_t pk[64];
#pragma unroll
  for (int i = 0; i < 64; i++) pk[i] = 0;
  reg_fence(acc);
  reg_fence(pk);
  cluster_wait();
  TS(0);
  const uint32_t qreg = sb + QREG + w * 32768;
  {
    uint32_t xs = 0, prev = 0;
    uint4* row = nullptr;
    int it = 0;
#pragma unroll 1
    for (int t = 0; t < 6; t++) {
      const int nk = (t == T_QB || t == 5) ? 7 : 16;
#pragma unroll 1
      for (int k = 0; k < nk; k++, it++) {
        const uint32_t ws = take(rdy0);
        TSC(1, it == 0);
        if (it == P1_XS) xs = take();
        const uint32_t aa = (it < P1_XS ? QREG + (it & 3) * 16384 : xs * SLOT + (it - P1_XS) * 16384) + (w ^ (t == T_QB)) * 8192;
        const uint64_t da = desc_k(sb + aa), db = desc_mn(sb + ws * SLOT);
        turn_begin();
        wg_fence();
#pragma unroll
        for (int kk = 0; kk < 4; kk++) wgmma_ss_n256_tb(acc, desc_add(da, kk * 32), desc_add(db, kk * 2048), (k | kk) != 0);
        wg_commit();
        turn_end();
        rdy0 = mbar_test(bar_addr(sb, B_FULL + r.slot), r.phase);
        wg_wait<1>();
        if (k > 0) give(prev);
        prev = ws;
        if (it >= P1_XS - 2 && !(it & 1) && lane == 0) mbar_arrive(bar_addr(sb, B_XFREE + ((it - (P1_XS - 2)) >> 1)));
        if (t > 0) {
          const int c0 = nk == 16 ? k : (16 * k + 3) * 37 >> 8, c1 = nk == 16 ? k + 1 : (16 * k + 19) * 37 >> 8;
#pragma unroll
          for (int i = 0; i < 16; i++)
            if (i >= c0 && i < c1) row[(i >> 1) * 256 + (i & 1) * 32] = make_uint4(pk[4 * i], pk[4 * i + 1], pk[4 * i + 2], pk[4 * i + 3]);
          if (c0 < 16 && c1 >= 16 && (t == T_QB + 1 || t == T_FIRST || t == T_LAST))
            warp_arrive(bar_addr(sb, (t == T_QB + 1 ? B_ST_Q : t == T_LAST ? B_ST_KV + 2 : B_ST_KV) + w), lane);
        }
      }
      if (t == 5) mbar_wait(bar_addr(sb, B_XFREE + w), 0);
      wg_wait<0>();
      reg_fence(acc);
      give(prev);
      pack_chunks(pk, acc);
      const int n = t - QFIRST;
      row = at<uint4>(t != T_QB ? (const void*)g_kv : (const void*)g_qc, chunk_off() +
                      (t != T_QB ? (uint32_t)((p1_isv(n) * NH + KVH(p1_head(h, n))) * 32 + p1_rows(h, j, n) * 2 + w) : (uint32_t)((h * 8 + j) * 2 + w)) * 32768);
      TS(2 + t);
    }
    give(xs);
    const uint32_t qa = qreg + chunk_off();
#pragma unroll
    for (int i = 0; i < 16; i++) sts16(qa + (i >> 1) * 4096 + (i & 1) * 512, pk[4 * i], pk[4 * i + 1], pk[4 * i + 2], pk[4 * i + 3]);
    fence_async_smem();
  }
  TS(8);

  constexpr float SC = 0.0625f * 1.4426950408889634f;
#pragma unroll 1
  for (int which = 0; which < 2; which++) {
    float s[32];
#pragma unroll
    for (int i = 0; i < 32; i++) s[i] = 0.f;
    uint32_t pa[16], pb[16];
    float m0 = -INFINITY, m1 = -INFINITY, l0 = 0.f, l1 = 0.f;
    const uint64_t dq = desc_64(qreg);
    uint64_t dk = 0, dqq = 0, dv = 0;
    auto prep_qk = [&](uint32_t kaddr) { dk = desc_64(kaddr); dqq = dq + (kaddr >> 31); asm volatile("" : "+l"(dk), "+l"(dqq)); };
    auto prep_pv = [&](uint32_t vaddr) { dv = desc_64(vaddr); asm volatile("" : "+l"(dv)); };
    auto issue_qk = [&]() {
#pragma unroll
      for (int kk = 0; kk < 16; kk++)
        wgmma_ss_n64(s, desc_add(dqq, (kk >> 1) * 4096 + (kk & 1) * 32), desc_add(dk, (kk >> 1) * 4096 + (kk & 1) * 32), kk != 0);
    };
    auto issue_pv = [&](int accumulate) {
#pragma unroll
      for (int kk = 0; kk < 4; kk++)
        wgmma_rs_n256_tb(acc, pa[4 * kk], pa[4 * kk + 1], pa[4 * kk + 2], pa[4 * kk + 3], desc_add(dv, kk * 1024), accumulate | kk);
    };
    auto mask_diag = [&]() {
      const int d = 16 * wq + (lane >> 2) - 2 * (lane & 3);
#pragma unroll
      for (int jj = 0; jj < 8; jj++) {
        if (8 * jj > d)     { s[4 * jj] = -INFINITY;     if (jj < 7) s[4 * jj + 6] = -INFINITY; }
        if (8 * jj + 1 > d) { s[4 * jj + 1] = -INFINITY; if (jj < 7) s[4 * jj + 7] = -INFINITY; }
      }
    };
    float a0, a1;
    auto softmax = [&](auto hook) -> bool {
      float x0 = fmaxf(s[0], s[1]), x1 = fmaxf(s[2], s[3]);
#pragma unroll
      for (int jj = 1; jj < 8; jj++) {
        x0 = fmaxf(x0, fmaxf(s[4 * jj], s[4 * jj + 1]));
        x1 = fmaxf(x1, fmaxf(s[4 * jj + 2], s[4 * jj + 3]));
      }
      x0 = fmaxf(x0, __shfl_xor_sync(0xffffffffu, x0, 1));
      x1 = fmaxf(x1, __shfl_xor_sync(0xffffffffu, x1, 1));
      x0 = fmaxf(x0, __shfl_xor_sync(0xffffffffu, x0, 2));
      x1 = fmaxf(x1, __shfl_xor_sync(0xffffffffu, x1, 2));
      const bool grow = __any_sync(0xffffffffu, fmaxf(x0 - m0, x1 - m1) * SC > 8.f);
      if (grow) {
        x0 = fmaxf(x0, m0); x1 = fmaxf(x1, m1);
        a0 = ex2((m0 - x0) * SC); a1 = ex2((m1 - x1) * SC);
        m0 = x0; m1 = x1;
        l0 *= a0; l1 *= a1;
      }
      const float b0 = -m0 * SC, b1 = -m1 * SC;
      float t0 = 0.f, t1 = 0.f, t2 = 0.f, t3 = 0.f;
#pragma unroll
      for (int jj = 0; jj < 8; jj++) {
        s[4 * jj]     = ex2(fmaf(s[4 * jj], SC, b0));
        s[4 * jj + 1] = ex2(fmaf(s[4 * jj + 1], SC, b0));
        s[4 * jj + 2] = ex2(fmaf(s[4 * jj + 2], SC, b1));
        s[4 * jj + 3] = ex2(fmaf(s[4 * jj + 3], SC, b1));
        t0 += s[4 * jj]; t1 += s[4 * jj + 1]; t2 += s[4 * jj + 2]; t3 += s[4 * jj + 3];
        hook(jj, HOOK_DEP);
      }
      l0 += t0 + t1; l1 += t2 + t3;
      return grow;
    };
    auto softmax_fast = [&]() -> bool {
      const float b0 = -m0 * SC, b1 = -m1 * SC;
      float t0 = 0.f, t1 = 0.f, t2 = 0.f, t3 = 0.f;
#pragma unroll
      for (int jj = 0; jj < 8; jj++) {
        const float e0 = ex2(fmaf(s[4 * jj], SC, b0)), e1 = ex2(fmaf(s[4 * jj + 1], SC, b0));
        const float e2 = ex2(fmaf(s[4 * jj + 2], SC, b1)), e3 = ex2(fmaf(s[4 * jj + 3], SC, b1));
        pb[2 * jj] = pack_bf16(e0, e1); pb[2 * jj + 1] = pack_bf16(e2, e3);
        if (jj == 0) { t0 = e0; t1 = e1; t2 = e2; t3 = e3; } else { t0 += e0; t1 += e1; t2 += e2; t3 += e3; }
      }
      t0 += t1; t2 += t3;
      const bool redo = __any_sync(0xffffffffu, !(t0 + t2 <= 16777216.f));
      if (!redo) { l0 += t0; l1 += t2; }
      return redo;
    };
    auto rescale = [&]() {
#pragma unroll
      for (int i = 0; i < 32; i++) { acc[4 * i] *= a0; acc[4 * i + 1] *= a0; acc[4 * i + 2] *= a1; acc[4 * i + 3] *= a1; }
    };
    auto to_p = [&](uint32_t (&pp)[16]) {
#pragma unroll
      for (int i = 0; i < 16; i++) pp[i] = pack_bf16(s[2 * i], s[2 * i + 1]);
    };
    auto q_free = [&]() { if (lane == 0) mbar_arrive(bar_addr(sb, B_QFREE + w)); };

    const int n = 2 * q_tile(h, j, which) + 1 + (w ^ which);
    uint32_t ks = take(rdy0);
    TS(9 + 5 * which);
    prep_qk(sb + ks * SLOT);
    turn_begin();
    TS(20 + 10 * which);
    wg_fence();
    issue_qk();
    wg_commit();
    turn_end();
    if (which == 1) give(take(rdy1));
    TS(22 + 10 * which);
    wg_wait<0>();
    TS(21 + 10 * which);
    reg_fence(s);
    give(ks);
    if (which == 0 && n == 1) q_free();
    if (which == 1 || n == 1) mask_diag();
    {
      const uint4* dst = at<uint4>(g_qc, (uint32_t)((h * 8 + j) * 2 + w) * 32768 + (fresh_tid() & 127) * 16);
      softmax([&](int jj, float e) {
        if (jj == PEEK_JJ) peek2();
        const int i = CTX_SPLIT + jj;
        if (i < 16)
          asm volatile("{\n.reg .pred p, q;\nsetp.ne.b32 q, %6, 0;\nsetp.geu.and.f32 p, %5, 0fBF800000, q;\n@p st.global.v4.u32 [%0], {%1, %2, %3, %4};\n}"
                       :: "l"(dst + i * 128), "r"(pk[4 * (i & 15)]), "r"(pk[4 * (i & 15) + 1]), "r"(pk[4 * (i & 15) + 2]), "r"(pk[4 * (i & 15) + 3]), "f"(e), "r"(which) : "memory");
      });
    }
    to_p(pa);
    if (which == 1) warp_arrive(bar_addr(sb, B_ST_CTX + w), lane);
    TS(10 + 5 * which);
#pragma unroll 1
    for (int jj = 1; jj < n; jj++) {
      ks = take(rdy0);
      const uint32_t vs = take(rdy1);
      prep_qk(sb + ks * SLOT);
      prep_pv(sb + vs * SLOT);
      TSC(23 + 10 * which, jj == 1);
      turn_begin();
      TSC(24 + 10 * which, jj == 1);
      TSC(26 + 10 * which, jj == n - 1);
      wg_fence();
      issue_qk();
      wg_commit();
      issue_pv(jj > 1);
      wg_commit();
      turn_end();
      wg_wait<1>();
      TSC(25 + 10 * which, jj == 1);
      reg_fence(s);
      give(ks);
      if (jj == n - 1 && which == 0) { q_free(); mask_diag(); }
      if (PF_CTX && which == 1 && jj == max(n - PF_CTX, 1)) {
        const uint8_t* src = at<const uint8_t>(g_qc, (uint32_t)(((h ^ 8) * 8 + j) * 2 + (w ^ 1)) * 32768 + (fresh_tid() & 127) * 128);
        asm volatile("prefetch.global.L2 [%0];" :: "l"(src));
        asm volatile("prefetch.global.L2 [%0];" :: "l"(src + 16384));
      }
      if (softmax_fast()) {
        wg_wait<0>();
        reg_fence(acc);
        if (softmax([](int, float) {})) rescale();
        to_p(pb);
      }
      peek2();
      wg_wait<0>();
      reg_fence(acc);
      reg_fence(pa);
      give(vs);
#pragma unroll
      for (int i = 0; i < 16; i++) pa[i] = pb[i] | (vs >> 8);
    }
    TS(11 + 5 * which);
    if (which == 0) { give(take(rdy0)); rdy0 = rdy1; }
    {
      const uint32_t vs = take(rdy0);
      prep_pv(sb + vs * SLOT);
      TS(27 + 10 * which);
      turn_begin();
      TS(28 + 10 * which);
      wg_fence();
      issue_pv(n > 1);
      wg_commit();
      turn_end();
      l0 += __shfl_xor_sync(0xffffffffu, l0, 1); l1 += __shfl_xor_sync(0xffffffffu, l1, 1);
      l0 += __shfl_xor_sync(0xffffffffu, l0, 2); l1 += __shfl_xor_sync(0xffffffffu, l1, 2);
      asm("rcp.approx.ftz.f32 %0, %0;" : "+f"(l0));
      asm("rcp.approx.ftz.f32 %0, %0;" : "+f"(l1));
      peek2();
      if (which == 0) mbar_wait(bar_addr(sb, B_QFULL + w), 0);
      wg_wait<0>();
      reg_fence(acc);
      reg_fence(pa);
      give(vs);
    }
    TS(12 + 5 * which);
    {
      const uint4* dst = at<uint4>(g_qc, (uint32_t)((h * 8 + j) * 2 + w) * 32768 + (fresh_tid() & 127) * 16);
#pragma unroll
      for (int i = 0; i < 16; i++) {
        const int c = (i & 1) ? (i >> 1) + 8 : i >> 1;
        pk[4 * c]     = pack_bf16(acc[8 * c] * l0, acc[8 * c + 1] * l0);
        pk[4 * c + 1] = pack_bf16(acc[8 * c + 2] * l1, acc[8 * c + 3] * l1);
        pk[4 * c + 2] = pack_bf16(acc[8 * c + 4] * l0, acc[8 * c + 5] * l0);
        pk[4 * c + 3] = pack_bf16(acc[8 * c + 6] * l1, acc[8 * c + 7] * l1);
        if (c < CTX_SPLIT)
          asm volatile("{\n.reg .pred p;\nsetp.eq.b32 p, %5, 0;\n@p st.global.v4.u32 [%0], {%1, %2, %3, %4};\n}"
                       :: "l"(dst + c * 128), "r"(pk[4 * c]), "r"(pk[4 * c + 1]), "r"(pk[4 * c + 2]), "r"(pk[4 * c + 3]), "r"(which) : "memory");
      }
    }
    TS(13 + 5 * which);
  }

  {
    float oa[32], ob[32];
#pragma unroll
    for (int i = 0; i < 32; i++) { oa[i] = 0.f; ob[i] = 0.f; }
    uint32_t pk2[64];
#pragma unroll
    for (int i = 0; i < 64; i++) pk2[i] = 0;
    auto stage = [&](float (&o)[32], int ch) {
      reg_fence(o);
      uint32_t q[16];
#pragma unroll
      for (int i = 0; i < 16; i++) q[i] = pack_bf16(o[2 * i], o[2 * i + 1]);
      if (ch >= 4) mbar_wait(bar_addr(sb, B_S2_EMPTY + w * 4 + (ch & 3)), 0);
      store_block(qreg + (ch & 3) * 8192, lane_base16(), q);
    };
    auto hand_over = [&](int ch) {
      fence_async_smem();
      warp_arrive(bar_addr(sb, B_S2_FULL + w * 4 + (ch & 3)), lane);
    };
    uint32_t prev = 0;
    auto half = [&](int f, float (&o)[32], uint32_t (&a)[64], int accumulate) {
      const uint32_t sl = take(rdy0);
      const uint64_t d = desc_mn(sb + sl * SLOT);
      turn_begin();
      TS(40 + f);
      wg_fence();
#pragma unroll
      for (int kk = 0; kk < 16; kk++) {
        wgmma_rs_n64_tb(o, a[4 * kk], a[4 * kk + 1], a[4 * kk + 2], a[4 * kk + 3], desc_add(d, kk * 2048), accumulate | kk);
        if (kk == ARRIVE_KK && (f < 13 || w == 0)) turn_end();
      }
      wg_commit();
      if (f < 13) rdy0 = mbar_test(bar_addr(sb, B_FULL + r.slot), r.phase);
      wg_wait<1>();
      if (f >= 1 && f <= 9) give(prev);
      prev = sl;
    };
    auto load_ctx = [&](auto h0) {
      constexpr int I0 = decltype(h0)::value ? CTX_LD : 0, NL = decltype(h0)::value ? 16 - CTX_LD : CTX_LD;
      const uint4* src = at<const uint4>(g_qc, (uint32_t)(((h ^ 8) * 8 + j) * 2 + (w ^ 1)) * 32768 + (fresh_tid() & 127) * 16);
#pragma unroll
      for (int i = I0; i < I0 + NL; i++) { const uint4 v = __ldcg(src + i * 128); pk2[4 * i] = v.x; pk2[4 * i + 1] = v.y; pk2[4 * i + 2] = v.z; pk2[4 * i + 3] = v.w; }
    };
#pragma unroll 1
    for (int i = 0; i < 3; i++) {
      half(4 * i, oa, pk, 0);
      if (i == 0) { mbar_wait(bar_addr(sb, B_CTXOK + w), 0); load_ctx(Int<0>()); }
      else { hand_over(2 * i - 2); stage(ob, 2 * i - 1); }
      half(4 * i + 1, ob, pk, 0);
      if (i == 0) load_ctx(Int<1>()); else hand_over(2 * i - 1);
      half(4 * i + 2, oa, pk2, 1);
      half(4 * i + 3, ob, pk2, 1);
      stage(oa, 2 * i);
    }
    half(12, oa, pk, 0);
    hand_over(4);
    stage(ob, 5);
    half(13, oa, pk2, 1);
    hand_over(5);
    wg_wait<0>();
    reg_fence(pk);
    reg_fence(pk2);
    stage(oa, 6);
    hand_over(6);
  }
  TS(19);
  TDUMP();
}

namespace ssm {
constexpr int NCH = DA / NCONV;
constexpr int NS = 8, NP = 6;
constexpr uint32_t X0 = 384;
constexpr uint32_t HO = X0 + 4096;
constexpr uint32_t HE = HO + HO_STRIDE + 64;
constexpr uint32_t SSLOT = HE + 4096 + 64;
constexpr uint32_t PART = 264 * 16;
constexpr uint32_t OFF_P = NS * SSLOT, OFF_D = OFF_P + NP * 4 * PART, END = OFF_D + NCH * 4;
static_assert(SSLOT % 128 == 0 && HO % 128 == 0 && END <= BARS, "smem");
enum : uint32_t { B_FULL = 0, B_EMPTY = NS, B_PFULL = 2 * NS, B_PEMPTY = 2 * NS + NP };
__device__ __forceinline__ int channel(int cidx, int i) { return (i >> 4) * 64 + cidx * 16 + (i & 15); }

__device__ __forceinline__ void producer(const Params& p, uint32_t sb, int cidx, unsigned epoch) {
#pragma unroll 1
  for (int i = 0; i < NCH; i++) {
    const int s = i % NS, ch = channel(cidx, i);
    const uint32_t full = bar_addr(sb, B_FULL + s), dst = sb + s * SSLOT;
    mbar_wait(bar_addr(sb, B_EMPTY + s), ((i / NS) & 1) ^ 1);
    mbar_expect_tx(full, 4096 + 4128 + 4096);
    bulk_ld(dst + HE, at<uint8_t>(p.a_ssmk, ch * 4096), 4096, full);
    if ((i & 15) == 0) { flag_wait(flag_at(g_flags.x_ready, i >> 4), NMAIN, epoch); fence_async_all(); }
    bulk_ld(dst + HO, at<uint8_t>(g_ho, ch * HO_STRIDE), 4128, full);
    bulk_ld(dst + X0, at<uint8_t>(g_xs, ch * 4096), 4096, full);
  }
}

__device__ __forceinline__ void reducer(uint32_t sb, int cidx, int rw) {
  uint32_t n = 0;
#pragma unroll 1
  for (int i = rw; i < NCH; i += 3, n++) {
    const uint32_t b = rw + 3 * (n & 1), pb = sb + OFF_P + b * 4 * PART;
    uint8_t* dst = at<uint8_t>(g_xs, channel(cidx, i) * 4096);
    mbar_wait(bar_addr(sb, B_PFULL + b), (n >> 1) & 1);
    asm volatile("cp.async.bulk.global.shared::cta.bulk_group [%0], [%1], 4096;" :: "l"(dst), "r"(pb + 3 * PART) : "memory");
    bulk_commit();
    bulk_wait_all();
#pragma unroll
    for (int k = 2; k >= 0; k--)
      asm volatile("cp.reduce.async.bulk.global.shared::cta.bulk_group.add.noftz.bf16 [%0], [%1], 4096;" :: "l"(dst), "r"(pb + k * PART) : "memory");
    bulk_commit();
    bulk_wait_read();
    mbar_arrive(bar_addr(sb, B_PEMPTY + b));
    if (((i + 3) >> 4) != (i >> 4)) {
      bulk_wait_all();
      fence_async_all();
      flag_signal(flag_at(g_flags.z_ready, i >> 4));
    }
  }
}

__device__ __forceinline__ void mma_warpgroup(uint32_t sb, int w) {
  const int lane = threadIdx.x & 31, g = lane >> 2, c = lane & 3, wq = (threadIdx.x >> 5) & 3;
  const uint32_t aoff = ((g & 1) ? HO + 30 : HE) + (16 * wq - g + 2 * c) * 2;
  const uint32_t poff = OFF_P + wq * PART + (2 * wq + lane) * 16;
  const uint32_t dmask = (wq == 0 && c == (g >> 1)) ? ((g & 1) ? 0xffff0000u : 0xffffu) : 0u;
  float acc[8][16];
  uint32_t fa[16][4];
#pragma unroll
  for (int e = 0; e < 8; e++)
#pragma unroll
    for (int i = 0; i < 16; i++) acc[e][i] = 0.f;
  auto load_a = [&](int m, uint32_t ad) {
    fa[m][0] = lds4(ad + m * 256 + 16); fa[m][1] = lds4(ad + m * 256 + 144); fa[m][2] = lds4(ad + m * 256); fa[m][3] = lds4(ad + m * 256 + 128);
  };
  if (w == 1) named_arrive(PP_BAR, 256);
  mbar_wait(bar_addr(sb, B_FULL + w), 0);
#pragma unroll
  for (int m = 0; m < 16; m++) load_a(m, sb + w * SSLOT + aoff);
  uint32_t dd = lds4(sb + OFF_D + w * 4);
  if (threadIdx.x == 128) { GT(12); PT(10); }
  uint32_t pb = w, pphase = 1;
#pragma unroll 1
  for (int i = w; i < NCH; i += 2) {
    fa[0][2] = badd(fa[0][2], dd & dmask);
    const uint64_t db = (uint64_t)((((sb + (i % NS) * SSLOT + X0 - 16) & 0x3FFFF) >> 4) | (1u << 16)) | ((uint64_t)8 << 32);
    named_sync(PP_BAR + w, 256);
    wg_fence();
#pragma unroll
    for (int r = 0; r < 16; r++) {
      auto mm = [&](int e, int m) { wgmma_rs_n32(acc[e], fa[m][0], fa[m][1], fa[m][2], fa[m][3], db + (int64_t)(32 * e - 16 * m), m != 0); };
      mm(7, r);
      if (r < 14) mm(6, r); else mm(0, r - 14);
      if (r < 12) mm(5, r); else mm(1, r - 12);
      if (r < 10) mm(4, r); else mm(2, r - 10);
      if ((r & 1) == 0) mm(3, r >> 1);
      if (r == CONV_ARRIVE && (i + 1 < NCH)) named_arrive(PP_BAR + (w ^ 1), 256);
    }
    wg_commit();
    const int nx = i + 2 < NCH ? i + 2 : i;
    mbar_wait(bar_addr(sb, B_FULL + nx % NS), (nx / NS) & 1);
    mbar_wait(bar_addr(sb, B_PEMPTY + pb), pphase);
    const uint32_t ad = sb + (nx % NS) * SSLOT + aoff, pa = sb + pb * 4 * PART + poff;
    wg_wait<0>();
#pragma unroll
    for (int e = 0; e < 8; e++) reg_fence(acc[e]);
#pragma unroll
    for (int m = 0; m < 16; m++) reg_fence(fa[m]);
    if (lane == 0) mbar_arrive(bar_addr(sb, B_EMPTY + i % NS));
#pragma unroll
    for (int e = 0; e < 8; e++) {
      if (e < CONV_EARLY) load_a(e, ad);
      uint32_t u[4];
#pragma unroll
      for (int j = 0; j < 4; j++) {
        const int T = 4 * e + j, U = T - 1;
        float lo = acc[e][4 * j], hi = acc[e][4 * j + 1];
        if (T > 0) { lo += acc[U >> 2][4 * (U & 3) + 2]; hi += acc[U >> 2][4 * (U & 3) + 3]; }
        u[j] = pack_bf16(lo, hi);
      }
      asm volatile("stmatrix.sync.aligned.m8n8.x4.trans.shared.b16 [%0], {%1, %2, %3, %4};" :: "r"(pa + e * 512), "r"(u[0]), "r"(u[1]), "r"(u[2]), "r"(u[3]) : "memory");
    }
    dd = lds4(sb + OFF_D + nx * 4);
#pragma unroll
    for (int m = CONV_EARLY; m < CONV_FENCE; m++) load_a(m, ad);
    fence_async_smem();
    warp_arrive(bar_addr(sb, B_PFULL + pb), lane);
#pragma unroll
    for (int m = CONV_FENCE; m < 16; m++) load_a(m, ad);
    pb += 2;
    if (pb >= NP) { pb -= NP; pphase ^= 1; }
  }
  if (threadIdx.x == 128) { PT(9); GT(13); }
}

__device__ __forceinline__ void init(const Params& p, uint32_t sb, int cidx) {
  const uint32_t t = threadIdx.x;
  if (t < NCH) {
    const uint32_t d = (uint32_t)__ldg(reinterpret_cast<const unsigned short*>(p.a_D + channel(cidx, t))) * 0x10001u;
    asm volatile("st.shared.u32 [%0], %1;" :: "r"(sb + OFF_D + t * 4), "r"(d) : "memory");
  }
#pragma unroll 1
  for (uint32_t u = t; u < NS * 32; u += 128) {
    const uint32_t r = u & 31;
    if (r < 28) sts16(sb + (u >> 5) * SSLOT + (r < 24 ? r * 16 : HE - 64 + (r - 24) * 16), 0, 0, 0, 0);
    if (u < NP * 32) sts16(sb + OFF_P + (u >> 3) * PART + (u & 7) * 16, 0, 0, 0, 0);
  }
  if (t == 0) {
    for (int i = 0; i < NS; i++) { mbar_init(bar_addr(sb, B_FULL + i), 1); mbar_init(bar_addr(sb, B_EMPTY + i), 4); }
    for (int i = 0; i < NP; i++) { mbar_init(bar_addr(sb, B_PFULL + i), 4); mbar_init(bar_addr(sb, B_PEMPTY + i), 1); }
  }
  fence_async_smem();
}

__device__ __forceinline__ void side_prepare(const Params& p, int cta, int rd) {
  const int lane = threadIdx.x & 31, t0 = 16 * cta + 8 * (lane & 1);
  if (EXP_SIDE & 16) { if (lane == 0) flag_signal_after_bulk(flag_at(g_flags.x_ready, rd)); return; }
#pragma unroll 1
  for (int ch = 64 * rd + (lane & ~1); ch < 64 * rd + 64; ch += 32) {
    const uint4 sv = __ldg(at<const uint4>(p.a_shift, ch * 8));
    const uint32_t* kp = at<const uint32_t>(p.a_k, (t0 * DA + ch) * 2);
    const uint32_t* vp = at<const uint32_t>(p.a_v, (t0 * DA + ch) * 2);
    uint32_t k0 = 0, k1 = 0, k2 = 0, kk[8], x[8];
    if (t0 > 0) { k0 = __ldg(kp - 3 * (DA / 2)); k1 = __ldg(kp - 2 * (DA / 2)); k2 = __ldg(kp - DA / 2); }
#pragma unroll
    for (int i = 0; i < 8; i++) { kk[i] = __ldg(kp + i * (DA / 2)); x[i] = __ldg(vp + i * (DA / 2)); }
    const uint32_t sh0 = __byte_perm(sv.x, sv.z, 0x5410), sh1 = __byte_perm(sv.x, sv.z, 0x7632);
    const uint32_t sh2 = __byte_perm(sv.y, sv.w, 0x5410), sh3 = __byte_perm(sv.y, sv.w, 0x7632);
#pragma unroll
    for (int i = 0; i < 8; i++) {
      uint32_t ks = bmul(k0, sh3);
      ks = badd(ks, bmul(k1, sh2)); ks = badd(ks, bmul(k2, sh1)); ks = badd(ks, bmul(kk[i], sh0));
      x[i] = bmul(ks, x[i]);
      k0 = k1; k1 = k2; k2 = kk[i];
    }
    uint4* dst = at<uint4>(g_xs, ch * 4096 + t0 * 2);
    if ((EXP_SIDE & 4) && (x[0] ^ x[1] ^ x[2] ^ x[3] ^ x[4] ^ x[5] ^ x[6] ^ x[7]) != 0x12345) continue;
    dst[0]   = make_uint4(__byte_perm(x[7], x[6], 0x5410), __byte_perm(x[5], x[4], 0x5410), __byte_perm(x[3], x[2], 0x5410), __byte_perm(x[1], x[0], 0x5410));
    dst[256] = make_uint4(__byte_perm(x[7], x[6], 0x7632), __byte_perm(x[5], x[4], 0x7632), __byte_perm(x[3], x[2], 0x7632), __byte_perm(x[1], x[0], 0x7632));
  }
  if (!(EXP_SIDE & 8)) {
    const int hc = 64 * rd + (cta >> 1), r0 = (cta & 1) * 128 + lane;
    const uint4* src = at<const uint4>(p.a_ssmk, hc * 4096 + r0 * 16);
    uint4* dst = at<uint4>(g_ho, hc * HO_STRIDE + r0 * 16);
    uint4 w[4];
    uint32_t nx[4];
#pragma unroll
    for (int i = 0; i < 4; i++) { w[i] = __ldg(src + 32 * i); nx[i] = r0 + 32 * i < 255 ? __ldg(reinterpret_cast<const uint32_t*>(src + 32 * i + 1)) : 0u; }
#pragma unroll
    for (int i = 0; i < 4; i++)
      dst[32 * i + 2] = make_uint4(__byte_perm(w[i].x, w[i].y, 0x5432), __byte_perm(w[i].y, w[i].z, 0x5432), __byte_perm(w[i].z, w[i].w, 0x5432), __byte_perm(w[i].w, nx[i], 0x5432));
    const uint32_t h0 = __shfl_sync(0xffffffffu, w[0].x, 0);
    if (r0 < 2) dst[0] = make_uint4(0, 0, 0, r0 ? h0 << 16 : 0u);
  }
  __syncwarp();
  if (lane == 0) { if (EXP_SIDE & 2) flag_signal_after_bulk(flag_at(g_flags.x_ready, rd)); else flag_signal(flag_at(g_flags.x_ready, rd)); }
}
__device__ __forceinline__ void side_finish(const Params& p, int cta, int rd) {
  const int lane = threadIdx.x & 31, t0 = 16 * cta + 8 * (lane & 1);
#pragma unroll 1
  for (int ch = 64 * rd + (lane & ~1); ch < 64 * rd + 64; ch += 32) {
    const uint4* src = at<const uint4>(g_xs, ch * 4096 + t0 * 2);
    const uint32_t* qp = at<const uint32_t>(p.a_q, (t0 * DA + ch) * 2);
    uint32_t* op = at<uint32_t>(p.out, (t0 * OUTW + ch) * 2);
    const uint4 z0 = __ldcg(src), z1 = __ldcg(src + 256);
    uint32_t q[8];
#pragma unroll
    for (int i = 0; i < 8; i++) q[i] = __ldg(qp + i * (DA / 2));
    const uint32_t a[4] = {z0.w, z0.z, z0.y, z0.x}, b[4] = {z1.w, z1.z, z1.y, z1.x};
#pragma unroll
    for (int i = 0; i < 4; i++) {
      op[(2 * i) * (OUTW / 2)]     = bmul(q[2 * i], __byte_perm(a[i], b[i], 0x7632));
      op[(2 * i + 1) * (OUTW / 2)] = bmul(q[2 * i + 1], __byte_perm(a[i], b[i], 0x5410));
    }
  }
}
__device__ __forceinline__ void clear_rows(const Params& p, int qt, int part) {
  const int lane = threadIdx.x & 31;
  if (lane < 28) {
    uint4* z = at<uint4>(p.out, ((qt * 128 + part * 16) * OUTW + DA) * 2 + lane * 16);
#pragma unroll
    for (int i = 0; i < 32; i++) z[(i >> 1) * (OUTW / 8) + (i & 1) * 28] = make_uint4(0, 0, 0, 0);
  }
  __syncwarp();
  if (lane == 0) flag_signal(flag_at(g_flags.zero_ready, qt));
}
__device__ __forceinline__ void side_work(const Params& p, int cta, int qt, unsigned epoch) {
#pragma unroll 1
  for (int rd = -SIDE_AHEAD; rd < 7; rd++) {
    if (rd >= 0) {
      if ((threadIdx.x & 31) == 0) flag_wait_slow(flag_at(g_flags.z_ready, rd), 3 * NCONV, epoch);
      __syncwarp();
    }
    if (rd + SIDE_AHEAD < 7) side_prepare(p, cta, rd + SIDE_AHEAD);
    if (rd >= 0 && !(EXP_SIDE & 1)) side_finish(p, cta, rd);
    if (rd == ZERO_RD) clear_rows(p, qt, (cta >> 3) & 7);
  }
}
}

__global__ void __cluster_dims__(2, 1, 1) __launch_bounds__(NTHREADS, 1)
concat_heads__ssm_conv_h3__compressed_kv_cla__prompt_kernel(const __grid_constant__ Params p) {
  extern __shared__ uint8_t smem_raw[];
  const uint32_t sb = (smem_u32(smem_raw) + 1023) & ~1023u;
  const int warp = __shfl_sync(0xffffffffu, threadIdx.x >> 5, 0);
  const int wg = warp >> 2;
  const int cta = blockIdx.x;
  const bool attn = cta < NMAIN;
  int h, u;
  {
    const int c = cta >> 1;
    if (c < 4) { h = 9; u = c; }
    else if (c < 36) { h = (c - 4) & 7; u = (c - 4) >> 3; }
    else { const int i = (c - 36) % 7; h = i == 0 ? 8 : 9 + i; u = (c - 36) / 7; }
  }
  const int j = 2 * u + (cta & 1);
  const int lane = threadIdx.x & 31;
  if (wg != 0) {
    if (attn) {
      if (threadIdx.x == NTHREADS - 32) {
        if (PF_MAPS & 2) prefetch_map(QFIRST ? &p.wq : &p.wuk);
        for (int i = 0; i < NSLOT; i++) mbar_init(bar_addr(sb, B_FULL + i), 1);
        asm volatile("fence.mbarrier_init.release.cluster;" ::: "memory");
      }
      __syncwarp();
      cluster_arrive();
      if (wg == 2) named_arrive(PP_BAR, 256);
      if (threadIdx.x == NTHREADS - 32) {
        for (int k = 0; k < EARLY_LD; k++) {
          const uint32_t full = bar_addr(sb, B_FULL + k);
          mbar_expect_tx(full, 49152);
          if (QFIRST) {
            tma_ld2(sb + QREG + k * 16384, &p.x, full, k * 64, q_tile(h, j, 1) * 128);
            load_tile4(sb + k * SLOT, &p.wq, full, k * 64, att_head(h, 1) * 4, j & 1, false);
          } else {
            tma_ld2(sb + QREG + k * 16384, &p.ckv, full, k * 64, p1_rows(h, j, 0) * 128);
            load_tile4(sb + k * SLOT, &p.wuk, full, k * 64, p1_head(h, 0) * 4, j & 1, false);
          }
        }
      }
      __syncwarp();
    }
    asm volatile("setmaxnreg.inc.sync.aligned.u32 232;");
    if (!attn) {
      if (p.out != nullptr) { named_sync(0, NTHREADS); ssm::mma_warpgroup(sb, wg - 1); }
      return;
    }
    if (p.out != nullptr) consumer_main(p, sb, h, j, wg - 1, warp & 3);
  } else {
    asm volatile("setmaxnreg.dec.sync.aligned.u32 40;");
    if (!attn) {
      ssm::init(p, sb, cta - NMAIN);
      named_sync(0, NTHREADS);
      if (lane == 0) {
        if (warp == 0) { ssm::producer(p, sb, cta - NMAIN, load_epoch()); cta_done(32); }
        else ssm::reducer(sb, cta - NMAIN, warp - 1);
        if (warp == 1) GT(14);
      }
      return;
    }
    if (lane == 0) {
      if (warp == 1) {
        for (int i = 0; i < NSLOT; i++) mbar_init(bar_addr(sb, B_EMPTY + i), 16);
        for (int i = 0; i < 2; i++) {
          mbar_init(bar_addr(sb, B_XFREE + i), 8); mbar_init(bar_addr(sb, B_QFREE + i), 4); mbar_init(bar_addr(sb, B_QFULL + i), 1);
          mbar_init(bar_addr(sb, B_KVOK + i), 1); mbar_init(bar_addr(sb, B_CTXOK + i), 1);
        }
      } else if (warp == 2) {
        for (int i = 0; i < 8; i++) { mbar_init(bar_addr(sb, B_S2_FULL + i), 4); mbar_init(bar_addr(sb, B_S2_EMPTY + i), 1); }
      } else if (warp == 0) {
        mbar_init(bar_addr(sb, B_DONE), 2);
        for (int i = 0; i < 2; i++) {
          mbar_init(bar_addr(sb, B_ST_KV + i), 4); mbar_init(bar_addr(sb, B_ST_KV + 2 + i), 4);
          mbar_init(bar_addr(sb, B_ST_Q + i), 4); mbar_init(bar_addr(sb, B_ST_CTX + i), 4);
        }
      }
      asm volatile("fence.mbarrier_init.release.cluster;" ::: "memory");
    }
    __syncwarp();
    cluster_arrive();
    cluster_wait();
    if (warp == 0) {
      if (lane == 0) producer_main(p, sb, h, j);
    } else if (warp < 3) {
      if (lane == 0) {
        if ((PF_MAPS & 1) && warp == 1) { __nanosleep(2000); prefetch_map(&p.wuv); prefetch_map(&p.x); prefetch_map(&p.wq); prefetch_map(&p.o); prefetch_map(&p.wo); }
        helper_main(p, sb, h, j, warp - 1);
        mbar_arrive(bar_addr(sb, B_DONE));
      }
    } else {
      ssm::side_work(p, h * 8 + j, q_tile(h, j, 1), load_epoch());
      if (lane == 0) { GT(57); mbar_wait(bar_addr(sb, B_DONE), 0); cta_done(1); }
    }
  }
}

typedef CUresult (*EncodeTiledFn)(CUtensorMap*, CUtensorMapDataType, cuuint32_t, void*, const cuuint64_t*, const cuuint64_t*,
                                  const cuuint32_t*, const cuuint32_t*, CUtensorMapInterleave, CUtensorMapSwizzle,
                                  CUtensorMapL2promotion, CUtensorMapFloatOOBfill);

void make_map(EncodeTiledFn enc, CUtensorMap* m, const void* ptr, int rank, const uint64_t* dims, const uint64_t* strides, const uint32_t* box) {
  cuuint64_t d[5], s[4]; cuuint32_t b[5], e[5] = {1, 1, 1, 1, 1};
  for (int i = 0; i < rank; i++) { d[i] = dims[i]; b[i] = box[i]; if (i) s[i - 1] = strides[i - 1]; }
  enc(m, CU_TENSOR_MAP_DATA_TYPE_BFLOAT16, rank, const_cast<void*>(ptr), d, s, b, e, CU_TENSOR_MAP_INTERLEAVE_NONE,
      CU_TENSOR_MAP_SWIZZLE_128B, CU_TENSOR_MAP_L2_PROMOTION_L2_256B, CU_TENSOR_MAP_FLOAT_OOB_FILL_NONE);
}
void map2(EncodeTiledFn enc, CUtensorMap* m, const void* ptr, uint64_t cols, uint64_t rows, uint32_t bc, uint32_t br) {
  const uint64_t dims[2] = {cols, rows}, st[1] = {cols * 2}; const uint32_t box[2] = {bc, br};
  make_map(enc, m, ptr, 2, dims, st, box);
}
void map3(EncodeTiledFn enc, CUtensorMap* m, const void* ptr, uint64_t rows, uint32_t nblk) {
  const uint64_t dims[3] = {64, rows, 64}, st[2] = {8192, 128}; const uint32_t box[3] = {64, 64, nblk};
  make_map(enc, m, ptr, 3, dims, st, box);
}

}

extern "C" void kernel_launch(void* const* d_in, const int* in_sizes, int n_in, void* d_out, int out_size) {
  (void)in_sizes; (void)n_in; (void)out_size;
  static EncodeTiledFn enc = nullptr;
  if (!enc) {
    void* fn = nullptr; cudaDriverEntryPointQueryResult qr;
    cudaGetDriverEntryPoint("cuTensorMapEncodeTiled", &fn, cudaEnableDefault, &qr);
    enc = (EncodeTiledFn)fn;
    cudaFuncSetAttribute(concat_heads__ssm_conv_h3__compressed_kv_cla__prompt_kernel, cudaFuncAttributeMaxDynamicSharedMemorySize, SMEM_BYTES);
  }
  Params p;
  p.a_q = (const bf16*)d_in[0]; p.a_k = (const bf16*)d_in[1]; p.a_v = (const bf16*)d_in[2];
  p.a_shift = (const bf16*)d_in[3]; p.a_ssmk = (const bf16*)d_in[4]; p.a_D = (const bf16*)d_in[5];
  p.out = (bf16*)d_out;
  map2(enc, &p.x, d_in[6], DM, SEQ, 64, 128);
  map2(enc, &p.ckv, d_in[7], DC, SEQ, 64, 128);
  map3(enc, &p.wq, d_in[8], DM, 2);
  map3(enc, &p.wuk, d_in[9], DC, 2);
  map3(enc, &p.wuv, d_in[10], DC, 2);
  {
    const uint64_t dims[5] = {DM, 2, 4, 4, NH * HD / 32}, st[4] = {DM * 2, 8 * DM * 2, 2 * DM * 2, 32 * DM * 2}; const uint32_t box[5] = {64, 2, 4, 4, 4};
    make_map(enc, &p.wo, d_in[11], 5, dims, st, box);
  }
  map2(enc, &p.o, d_out, OUTW, SEQ, 64, 64);
  concat_heads__ssm_conv_h3__compressed_kv_cla__prompt_kernel<<<NCTA, NTHREADS, SMEM_BYTES>>>(p);
}
```

```cpp
#include <cuda_runtime.h>
#include <cuda_bf16.h>
#include <cuda.h>
#include <stdint.h>

namespace {

typedef __nv_bfloat16 bf16;

constexpr int SEQ  = 2048;
constexpr int DA   = 448;
constexpr int NH   = 16;
constexpr int HD   = 256;
constexpr int DM   = 448;
constexpr int DC   = 1024;
constexpr int OUTW = DA + DM;
constexpr int NMAIN = 128;
constexpr int NCONV = 4;
constexpr int NCTA  = NMAIN + NCONV;
constexpr int LOG_DONE = 8;
constexpr int NTHREADS = 384;

__device__ __align__(1024) bf16 g_kv[2ull * SEQ * NH * HD];
__device__ __align__(1024) bf16 g_qc[(size_t)NMAIN * 128 * HD];
__device__ __align__(128) uint8_t g_xs[DA * SEQ * 2];
constexpr uint32_t HO_STRIDE = 4224;
__device__ __align__(128) uint8_t g_ho[DA * HO_STRIDE];
struct alignas(128) Flag { unsigned v; unsigned pad[31]; };
struct Flags {
  Flag kv_ready[NH * 2];
  Flag ctx_ready[NMAIN * 2];
  Flag x_ready[7];
  Flag z_ready[7];
  Flag zero_ready[16];
  alignas(128) unsigned long long done;
};
__device__ Flags g_flags;
#define TS(i)
#define TSC(i, cond)
#define TDUMP()
#define GT(i)
#define PT(i)
#define PCLK(var)
#define PACC(acc, t0)

struct alignas(64) Params {
  CUtensorMap ckv;
  CUtensorMap wuk;
  CUtensorMap wuv;
  CUtensorMap x;
  CUtensorMap wq;
  CUtensorMap o;
  CUtensorMap wo;
  const bf16 *a_q, *a_k, *a_v, *a_shift, *a_ssmk, *a_D;
  bf16* out;
};

constexpr uint32_t SLOT     = 32768;
constexpr int      NSLOT    = 5;
constexpr uint32_t QREG     = 163840;
constexpr uint32_t BARS     = 229376;
constexpr uint32_t SMEM_BYTES = BARS + 1024 + 1024;
enum : uint32_t {
  B_FULL = 0, B_EMPTY = 5, B_XFREE = 10, B_KVOK = 12, B_ST_Q = 14, B_ST_CTX = 16, B_DONE = 19, B_QFREE = 20, B_QFULL = 22,
  B_S2_FULL = 24, B_S2_EMPTY = 32, B_CTXOK = 40, B_PF = 42, B_ST_KV = 44
};
constexpr int P1_STEPS = 4 * 16 + 2 * 7, P1_XS = P1_STEPS - 2;

template <typename T> __device__ __forceinline__ T* at(const void* base, uint32_t off) {
  asm volatile("" : "+r"(off));
  return reinterpret_cast<T*>(const_cast<char*>(static_cast<const char*>(base)) + off);
}
__device__ __forceinline__ unsigned* flag_at(Flag* f, uint32_t i) { return at<unsigned>(f, i * (uint32_t)sizeof(Flag)); }
__device__ __forceinline__ uint32_t smem_u32(const void* p) { return (uint32_t)__cvta_generic_to_shared(p); }
__device__ __forceinline__ void mbar_init(uint32_t bar, uint32_t cnt) {
  asm volatile("mbarrier.init.shared::cta.b64 [%0], %1;" :: "r"(bar), "r"(cnt) : "memory");
}
__device__ __forceinline__ void mbar_expect_tx(uint32_t bar, uint32_t bytes) {
  asm volatile("mbarrier.arrive.expect_tx.shared::cta.b64 _, [%0], %1;" :: "r"(bar), "r"(bytes) : "memory");
}
__device__ __forceinline__ void mbar_arrive(uint32_t bar) {
  asm volatile("mbarrier.arrive.shared::cta.b64 _, [%0];" :: "r"(bar) : "memory");
}
__device__ __forceinline__ void mbar_arrive_n(uint32_t bar, uint32_t n) {
  asm volatile("mbarrier.arrive.shared::cta.b64 _, [%0], %1;" :: "r"(bar), "r"(n) : "memory");
}
__device__ __forceinline__ void mbar_arrive_remote(uint32_t bar, uint32_t cta) {
  asm volatile("{\n.reg .b32 ra;\nmapa.shared::cluster.u32 ra, %0, %1;\n"
               "mbarrier.arrive.shared::cluster.b64 _, [ra];\n}" :: "r"(bar), "r"(cta) : "memory");
}
__device__ __forceinline__ bool mbar_try(uint32_t bar, uint32_t parity) {
  uint32_t ok;
  asm volatile("{\n.reg .pred p;\nmbarrier.try_wait.parity.shared::cta.b64 p, [%1], %2;\nselp.u32 %0, 1, 0, p;\n}"
               : "=r"(ok) : "r"(bar), "r"(parity) : "memory");
  return ok;
}
__device__ __forceinline__ uint32_t mbar_test(uint32_t bar, uint32_t parity) {
  uint32_t ok;
  asm volatile("{\n.reg .pred p;\nmbarrier.test_wait.parity.shared::cta.b64 p, [%1], %2;\nselp.u32 %0, 1, 0, p;\n}"
               : "=r"(ok) : "r"(bar), "r"(parity) : "memory");
  return ok;
}
constexpr uint32_t SPIN_LIMIT = 1u << 24;
__device__ __forceinline__ void mbar_wait(uint32_t bar, uint32_t parity) {
  if (mbar_try(bar, parity)) return;
  uint32_t n = 0;
  while (!mbar_try(bar, parity)) { if (++n > SPIN_LIMIT) __trap(); }
}
__device__ __forceinline__ void mbar_wait_unless(uint32_t ready, uint32_t bar, uint32_t parity) {
  asm volatile("{\n.reg .pred p;\n.reg .b32 n;\nsetp.ne.u32 p, %0, 0;\nvote.sync.all.pred p, p, 0xffffffff;\n@p bra.uni WDONE;\nmov.u32 n, 0;\n"
               "WLOOP:\nmbarrier.try_wait.parity.shared::cta.b64 p, [%1], %2;\n@p bra.uni WDONE;\nadd.u32 n, n, 1;\nsetp.lt.u32 p, n, %3;\n@p bra.uni WLOOP;\ntrap;\nWDONE:\n}"
               :: "r"(ready), "r"(bar), "r"(parity), "n"(SPIN_LIMIT) : "memory");
}
__device__ __forceinline__ unsigned load_epoch() {
  unsigned long long d; asm volatile("ld.relaxed.gpu.global.u64 %0, [%1];" : "=l"(d) : "l"(&g_flags.done) : "memory");
  return (unsigned)(d >> LOG_DONE);
}
__device__ __forceinline__ void flag_wait(const unsigned* f, unsigned count, unsigned epoch) {
  const unsigned target = (epoch + 1) * count;
  uint32_t n = 0;
  while (true) {
    unsigned v;
    asm volatile("ld.acquire.gpu.global.u32 %0, [%1];" : "=r"(v) : "l"(f) : "memory");
    if ((int)(v - target) >= 0) break;
    if (++n > SPIN_LIMIT) __trap();
    __nanosleep(20);
  }
}
__device__ __forceinline__ void flag_wait_slow(const unsigned* f, unsigned count, unsigned epoch) {
  const unsigned target = (epoch + 1) * count;
  uint32_t n = 0;
  while (true) {
    unsigned v;
    asm volatile("ld.acquire.gpu.global.u32 %0, [%1];" : "=r"(v) : "l"(f) : "memory");
    if ((int)(v - target) >= 0) break;
    if (++n > SPIN_LIMIT / 16) __trap();
    __nanosleep(1000);
  }
}
__device__ __forceinline__ void cta_done(unsigned long long n) { asm volatile("red.relaxed.gpu.global.add.u64 [%0], %1;" :: "l"(&g_flags.done), "l"(n) : "memory"); }
__device__ __forceinline__ void flag_wait_fast(const unsigned* f, unsigned count, unsigned epoch) {
  const unsigned target = (epoch + 1) * count;
  uint32_t n = 0;
  while (true) {
    unsigned v;
    asm volatile("ld.acquire.gpu.global.u32 %0, [%1];" : "=r"(v) : "l"(f) : "memory");
    if ((int)(v - target) >= 0) break;
    if (++n > SPIN_LIMIT) __trap();
  }
}
__device__ __forceinline__ void fence_async_all() { asm volatile("fence.proxy.async.global;" ::: "memory"); }
__device__ __forceinline__ void flag_signal(unsigned* f) { asm volatile("red.release.gpu.global.add.u32 [%0], 1;" :: "l"(f) : "memory"); }
__device__ __forceinline__ void flag_signal_after_bulk(unsigned* f) {
  asm volatile("red.relaxed.gpu.global.add.u32 [%0], 1;" :: "l"(f) : "memory");
}
__device__ __forceinline__ void fence_async_smem() { asm volatile("fence.proxy.async.shared::cta;" ::: "memory"); }
#define HINTS 40
constexpr uint64_t POL_NORMAL = 0x1000000000000000ull, POL_FIRST = 0x12F0000000000000ull;
__device__ __forceinline__ constexpr uint64_t pol(bool first) { return first ? POL_FIRST : POL_NORMAL; }
__device__ __forceinline__ void tma_ld2(uint32_t dst, const CUtensorMap* m, uint32_t bar, int c0, int c1, uint64_t pl = POL_NORMAL) {
  asm volatile("cp.async.bulk.tensor.2d.shared::cluster.global.mbarrier::complete_tx::bytes.L2::cache_hint [%0], [%1, {%3, %4}], [%2], %5;"
               :: "r"(dst), "l"(m), "r"(bar), "r"(c0), "r"(c1), "l"(pl) : "memory");
}
__device__ __forceinline__ void tma_ld3(uint32_t dst, const CUtensorMap* m, uint32_t bar, int c0, int c1, int c2, uint64_t pl = POL_NORMAL) {
  asm volatile("cp.async.bulk.tensor.3d.shared::cluster.global.mbarrier::complete_tx::bytes.L2::cache_hint [%0], [%1, {%3, %4, %5}], [%2], %6;"
               :: "r"(dst), "l"(m), "r"(bar), "r"(c0), "r"(c1), "r"(c2), "l"(pl) : "memory");
}
__device__ __forceinline__ void tma_ld3_mc(uint32_t dst, const CUtensorMap* m, uint32_t bar, int c0, int c1, int c2, uint64_t pl = POL_NORMAL) {
  asm volatile("cp.async.bulk.tensor.3d.shared::cluster.global.mbarrier::complete_tx::bytes.multicast::cluster.L2::cache_hint [%0], [%1, {%3, %4, %5}], [%2], %6, %7;"
               :: "r"(dst), "l"(m), "r"(bar), "r"(c0), "r"(c1), "r"(c2), "h"((uint16_t)3), "l"(pl) : "memory");
}
__device__ __forceinline__ void bulk_ld(uint32_t dst, const void* src, uint32_t bytes, uint32_t bar) {
  asm volatile("cp.async.bulk.shared::cluster.global.mbarrier::complete_tx::bytes [%0], [%1], %2, [%3];"
               :: "r"(dst), "l"(src), "r"(bytes), "r"(bar) : "memory");
}
__device__ __forceinline__ void bulk_ld_p(uint32_t dst, const void* src, uint32_t bytes, uint32_t bar, uint64_t pl) {
  asm volatile("cp.async.bulk.shared::cluster.global.mbarrier::complete_tx::bytes.L2::cache_hint [%0], [%1], %2, [%3], %4;"
               :: "r"(dst), "l"(src), "r"(bytes), "r"(bar), "l"(pl) : "memory");
}
__device__ __forceinline__ void bulk_ld_mc(uint32_t dst, const void* src, uint32_t bytes, uint32_t bar, uint64_t pl) {
  asm volatile("cp.async.bulk.shared::cluster.global.mbarrier::complete_tx::bytes.multicast::cluster.L2::cache_hint [%0], [%1], %2, [%3], %4, %5;"
               :: "r"(dst), "l"(src), "r"(bytes), "r"(bar), "h"((uint16_t)3), "l"(pl) : "memory");
}
__device__ __forceinline__ void tma_st3(const CUtensorMap* m, uint32_t src, int c0, int c1, int c2) {
  asm volatile("cp.async.bulk.tensor.3d.global.shared::cta.bulk_group.L2::cache_hint [%0, {%2, %3, %4}], [%1], %5;"
               :: "l"(m), "r"(src), "r"(c0), "r"(c1), "r"(c2), "l"(pol(HINTS & 1024)) : "memory");
}
__device__ __forceinline__ void tma_ld2_mc(uint32_t dst, const CUtensorMap* m, uint32_t bar, int c0, int c1, uint64_t pl = POL_NORMAL) {
  asm volatile("cp.async.bulk.tensor.2d.shared::cluster.global.mbarrier::complete_tx::bytes.multicast::cluster.L2::cache_hint [%0], [%1, {%3, %4}], [%2], %5, %6;"
               :: "r"(dst), "l"(m), "r"(bar), "r"(c0), "r"(c1), "h"((uint16_t)3), "l"(pl) : "memory");
}
__device__ __forceinline__ void tma_ld5_mc(uint32_t dst, const CUtensorMap* m, uint32_t bar, int c0, int c4, uint64_t pl = POL_NORMAL) {
  asm volatile("cp.async.bulk.tensor.5d.shared::cluster.global.mbarrier::complete_tx::bytes.multicast::cluster.L2::cache_hint [%0], [%1, {%3, %7, %7, %7, %4}], [%2], %5, %6;"
               :: "r"(dst), "l"(m), "r"(bar), "r"(c0), "r"(c4), "h"((uint16_t)3), "l"(pl), "r"(0) : "memory");
}
__device__ __forceinline__ void tma_st2(const CUtensorMap* m, uint32_t src, int c0, int c1) {
  asm volatile("cp.async.bulk.tensor.2d.global.shared::cta.bulk_group [%0, {%2, %3}], [%1];"
               :: "l"(m), "r"(src), "r"(c0), "r"(c1) : "memory");
}
__device__ __forceinline__ void tma_red2(const CUtensorMap* m, uint32_t src, int c0, int c1) {
  asm volatile("cp.reduce.async.bulk.tensor.2d.global.shared::cta.add.bulk_group [%0, {%2, %3}], [%1];"
               :: "l"(m), "r"(src), "r"(c0), "r"(c1) : "memory");
}
__device__ __forceinline__ void bulk_commit() { asm volatile("cp.async.bulk.commit_group;" ::: "memory"); }
__device__ __forceinline__ void bulk_wait_read() { asm volatile("cp.async.bulk.wait_group.read 0;" ::: "memory"); }
__device__ __forceinline__ void bulk_wait_all() { asm volatile("cp.async.bulk.wait_group 0;" ::: "memory"); }
__device__ __forceinline__ void prefetch_map(const CUtensorMap* m) { asm volatile("prefetch.tensormap [%0];" :: "l"(m) : "memory"); }
__device__ __forceinline__ void wg_fence() { asm volatile("wgmma.fence.sync.aligned;" ::: "memory"); }
__device__ __forceinline__ void wg_commit() { asm volatile("wgmma.commit_group.sync.aligned;" ::: "memory"); }
template <int N> __device__ __forceinline__ void wg_wait() { asm volatile("wgmma.wait_group.sync.aligned %0;" :: "n"(N) : "memory"); }
template <int N> __device__ __forceinline__ void reg_fence(float (&d)[N]) {
#pragma unroll
  for (int i = 0; i < N; i++) asm volatile("" : "+f"(d[i]) :: "memory");
}
template <int N> __device__ __forceinline__ void reg_fence(uint32_t (&d)[N]) {
#pragma unroll
  for (int i = 0; i < N; i++) asm volatile("" : "+r"(d[i]) :: "memory");
}
__device__ __forceinline__ uint32_t fresh_tid() { uint32_t t; asm volatile("mov.u32 %0, %%tid.x;" : "=r"(t)); return t; }
__device__ __forceinline__ uint32_t lane_base16() {
  const uint32_t t = fresh_tid(), lane = t & 31, wq = (t >> 5) & 3;
  return (16 * wq + (lane & 7) + 8 * ((lane >> 3) & 1)) * 128 + (((lane >> 4) ^ (lane & 7)) << 4);
}
__device__ __forceinline__ void cluster_arrive() { asm volatile("barrier.cluster.arrive.relaxed.aligned;" ::: "memory"); }
__device__ __forceinline__ void cluster_wait() { asm volatile("barrier.cluster.wait.acquire.aligned;" ::: "memory"); }
__device__ __forceinline__ void named_sync(int id, int n) { asm volatile("bar.sync %0, %1;" :: "r"(id), "r"(n) : "memory"); }
__device__ __forceinline__ void named_arrive(int id, int n) { asm volatile("bar.arrive %0, %1;" :: "r"(id), "r"(n) : "memory"); }
__device__ __forceinline__ uint32_t pack_bf16(float lo, float hi) {
  uint32_t r; asm("cvt.rn.bf16x2.f32 %0, %1, %2;" : "=r"(r) : "f"(hi), "f"(lo)); return r;
}
__device__ __forceinline__ float ex2(float x) { float y; asm("ex2.approx.ftz.f32 %0, %1;" : "=f"(y) : "f"(x)); return y; }
__device__ __forceinline__ void stsm4(uint32_t addr, uint32_t a, uint32_t b, uint32_t c, uint32_t d) {
  asm volatile("stmatrix.sync.aligned.m8n8.x4.shared.b16 [%0], {%1, %2, %3, %4};" :: "r"(addr), "r"(a), "r"(b), "r"(c), "r"(d) : "memory");
}
__device__ __forceinline__ uint64_t mk_desc(uint32_t addr, uint32_t lbo, uint32_t sbo) {
  return (uint64_t)(((addr & 0x3FFFF) >> 4) | ((lbo >> 4) << 16)) | ((uint64_t)((sbo >> 4) | (1u << 30)) << 32);
}
__device__ __forceinline__ uint64_t desc_k(uint32_t addr)  { return mk_desc(addr, 16, 1024); }
__device__ __forceinline__ uint64_t desc_mn(uint32_t addr) { return mk_desc(addr, 8192, 1024); }
__device__ __forceinline__ uint64_t desc_64(uint32_t addr) { return (uint64_t)(((addr & 0x3FFFF) >> 4) | ((4096u >> 4) << 16)) | ((uint64_t)((512u >> 4) | (2u << 30)) << 32); }
__device__ __forceinline__ uint64_t desc_add(uint64_t d, uint32_t bytes) { return d + (bytes >> 4); }

__device__ __forceinline__ void wgmma_ss_n256_tb(float (&d)[128], uint64_t da, uint64_t db, int sd) {
  asm volatile("{\n.reg .pred p;\nsetp.ne.b32 p, %130, 0;\n"
    "wgmma.mma_async.sync.aligned.m64n256k16.f32.bf16.bf16 "
    "{%0, %1, %2, %3, %4, %5, %6, %7, %8, %9, %10, %11, %12, %13, %14, %15, "
    "%16, %17, %18, %19, %20, %21, %22, %23, %24, %25, %26, %27, %28, %29, %30, %31, "
    "%32, %33, %34, %35, %36, %37, %38, %39, %40, %41, %42, %43, %44, %45, %46, %47, "
    "%48, %49, %50, %51, %52, %53, %54, %55, %56, %57, %58, %59, %60, %61, %62, %63, "
    "%64, %65, %66, %67, %68, %69, %70, %71, %72, %73, %74, %75, %76, %77, %78, %79, "
    "%80, %81, %82, %83, %84, %85, %86, %87, %88, %89, %90, %91, %92, %93, %94, %95, "
    "%96, %97, %98, %99, %100, %101, %102, %103, %104, %105, %106, %107, %108, %109, %110, %111, "
    "%112, %113, %114, %115, %116, %117, %118, %119, %120, %121, %122, %123, %124, %125, %126, %127}, "
    "%128, %129, p, 1, 1, 0, 1;\n}"
    : "+f"(d[0]), "+f"(d[1]), "+f"(d[2]), "+f"(d[3]), "+f"(d[4]), "+f"(d[5]), "+f"(d[6]), "+f"(d[7]),
      "+f"(d[8]), "+f"(d[9]), "+f"(d[10]), "+f"(d[11]), "+f"(d[12]), "+f"(d[13]), "+f"(d[14]), "+f"(d[15]),
      "+f"(d[16]), "+f"(d[17]), "+f"(d[18]), "+f"(d[19]), "+f"(d[20]), "+f"(d[21]), "+f"(d[22]), "+f"(d[23]),
      "+f"(d[24]), "+f"(d[25]), "+f"(d[26]), "+f"(d[27]), "+f"(d[28]), "+f"(d[29]), "+f"(d[30]), "+f"(d[31]),
      "+f"(d[32]), "+f"(d[33]), "+f"(d[34]), "+f"(d[35]), "+f"(d[36]), "+f"(d[37]), "+f"(d[38]), "+f"(d[39]),
      "+f"(d[40]), "+f"(d[41]), "+f"(d[42]), "+f"(d[43]), "+f"(d[44]), "+f"(d[45]), "+f"(d[46]), "+f"(d[47]),
      "+f"(d[48]), "+f"(d[49]), "+f"(d[50]), "+f"(d[51]), "+f"(d[52]), "+f"(d[53]), "+f"(d[54]), "+f"(d[55]),
      "+f"(d[56]), "+f"(d[57]), "+f"(d[58]), "+f"(d[59]), "+f"(d[60]), "+f"(d[61]), "+f"(d[62]), "+f"(d[63]),
      "+f"(d[64]), "+f"(d[65]), "+f"(d[66]), "+f"(d[67]), "+f"(d[68]), "+f"(d[69]), "+f"(d[70]), "+f"(d[71]),
      "+f"(d[72]), "+f"(d[73]), "+f"(d[74]), "+f"(d[75]), "+f"(d[76]), "+f"(d[77]), "+f"(d[78]), "+f"(d[79]),
      "+f"(d[80]), "+f"(d[81]), "+f"(d[82]), "+f"(d[83]), "+f"(d[84]), "+f"(d[85]), "+f"(d[86]), "+f"(d[87]),
      "+f"(d[88]), "+f"(d[89]), "+f"(d[90]), "+f"(d[91]), "+f"(d[92]), "+f"(d[93]), "+f"(d[94]), "+f"(d[95]),
      "+f"(d[96]), "+f"(d[97]), "+f"(d[98]), "+f"(d[99]), "+f"(d[100]), "+f"(d[101]), "+f"(d[102]), "+f"(d[103]),
      "+f"(d[104]), "+f"(d[105]), "+f"(d[106]), "+f"(d[107]), "+f"(d[108]), "+f"(d[109]), "+f"(d[110]), "+f"(d[111]),
      "+f"(d[112]), "+f"(d[113]), "+f"(d[114]), "+f"(d[115]), "+f"(d[116]), "+f"(d[117]), "+f"(d[118]), "+f"(d[119]),
      "+f"(d[120]), "+f"(d[121]), "+f"(d[122]), "+f"(d[123]), "+f"(d[124]), "+f"(d[125]), "+f"(d[126]), "+f"(d[127])
    : "l"(da), "l"(db), "r"(sd));
}
__device__ __forceinline__ void wgmma_ss_n64(float (&d)[32], uint64_t da, uint64_t db, int sd) {
  asm volatile("{\n.reg .pred p;\nsetp.ne.b32 p, %34, 0;\n"
    "wgmma.mma_async.sync.aligned.m64n64k16.f32.bf16.bf16 "
    "{%0, %1, %2, %3, %4, %5, %6, %7, %8, %9, %10, %11, %12, %13, %14, %15, "
    "%16, %17, %18, %19, %20, %21, %22, %23, %24, %25, %26, %27, %28, %29, %30, %31}, "
    "%32, %33, p, 1, 1, 0, 0;\n}"
    : "+f"(d[0]), "+f"(d[1]), "+f"(d[2]), "+f"(d[3]), "+f"(d[4]), "+f"(d[5]), "+f"(d[6]), "+f"(d[7]),
      "+f"(d[8]), "+f"(d[9]), "+f"(d[10]), "+f"(d[11]), "+f"(d[12]), "+f"(d[13]), "+f"(d[14]), "+f"(d[15]),
      "+f"(d[16]), "+f"(d[17]), "+f"(d[18]), "+f"(d[19]), "+f"(d[20]), "+f"(d[21]), "+f"(d[22]), "+f"(d[23]),
      "+f"(d[24]), "+f"(d[25]), "+f"(d[26]), "+f"(d[27]), "+f"(d[28]), "+f"(d[29]), "+f"(d[30]), "+f"(d[31])
    : "l"(da), "l"(db), "r"(sd));
}
__device__ __forceinline__ void wgmma_rs_n256_tb(float (&d)[128], uint32_t a0, uint32_t a1, uint32_t a2, uint32_t a3, uint64_t db, int sd) {
  asm volatile("{\n.reg .pred p;\nsetp.ne.b32 p, %133, 0;\n"
    "wgmma.mma_async.sync.aligned.m64n256k16.f32.bf16.bf16 "
    "{%0, %1, %2, %3, %4, %5, %6, %7, %8, %9, %10, %11, %12, %13, %14, %15, "
    "%16, %17, %18, %19, %20, %21, %22, %23, %24, %25, %26, %27, %28, %29, %30, %31, "
    "%32, %33, %34, %35, %36, %37, %38, %39, %40, %41, %42, %43, %44, %45, %46, %47, "
    "%48, %49, %50, %51, %52, %53, %54, %55, %56, %57, %58, %59, %60, %61, %62, %63, "
    "%64, %65, %66, %67, %68, %69, %70, %71, %72, %73, %74, %75, %76, %77, %78, %79, "
    "%80, %81, %82, %83, %84, %85, %86, %87, %88, %89, %90, %91, %92, %93, %94, %95, "
    "%96, %97, %98, %99, %100, %101, %102, %103, %104, %105, %106, %107, %108, %109, %110, %111, "
    "%112, %113, %114, %115, %116, %117, %118, %119, %120, %121, %122, %123, %124, %125, %126, %127}, "
    "{%128, %129, %130, %131}, %132, p, 1, 1, 1;\n}"
    : "+f"(d[0]), "+f"(d[1]), "+f"(d[2]), "+f"(d[3]), "+f"(d[4]), "+f"(d[5]), "+f"(d[6]), "+f"(d[7]),
      "+f"(d[8]), "+f"(d[9]), "+f"(d[10]), "+f"(d[11]), "+f"(d[12]), "+f"(d[13]), "+f"(d[14]), "+f"(d[15]),
      "+f"(d[16]), "+f"(d[17]), "+f"(d[18]), "+f"(d[19]), "+f"(d[20]), "+f"(d[21]), "+f"(d[22]), "+f"(d[23]),
      "+f"(d[24]), "+f"(d[25]), "+f"(d[26]), "+f"(d[27]), "+f"(d[28]), "+f"(d[29]), "+f"(d[30]), "+f"(d[31]),
      "+f"(d[32]), "+f"(d[33]), "+f"(d[34]), "+f"(d[35]), "+f"(d[36]), "+f"(d[37]), "+f"(d[38]), "+f"(d[39]),
      "+f"(d[40]), "+f"(d[41]), "+f"(d[42]), "+f"(d[43]), "+f"(d[44]), "+f"(d[45]), "+f"(d[46]), "+f"(d[47]),
      "+f"(d[48]), "+f"(d[49]), "+f"(d[50]), "+f"(d[51]), "+f"(d[52]), "+f"(d[53]), "+f"(d[54]), "+f"(d[55]),
      "+f"(d[56]), "+f"(d[57]), "+f"(d[58]), "+f"(d[59]), "+f"(d[60]), "+f"(d[61]), "+f"(d[62]), "+f"(d[63]),
      "+f"(d[64]), "+f"(d[65]), "+f"(d[66]), "+f"(d[67]), "+f"(d[68]), "+f"(d[69]), "+f"(d[70]), "+f"(d[71]),
      "+f"(d[72]), "+f"(d[73]), "+f"(d[74]), "+f"(d[75]), "+f"(d[76]), "+f"(d[77]), "+f"(d[78]), "+f"(d[79]),
      "+f"(d[80]), "+f"(d[81]), "+f"(d[82]), "+f"(d[83]), "+f"(d[84]), "+f"(d[85]), "+f"(d[86]), "+f"(d[87]),
      "+f"(d[88]), "+f"(d[89]), "+f"(d[90]), "+f"(d[91]), "+f"(d[92]), "+f"(d[93]), "+f"(d[94]), "+f"(d[95]),
      "+f"(d[96]), "+f"(d[97]), "+f"(d[98]), "+f"(d[99]), "+f"(d[100]), "+f"(d[101]), "+f"(d[102]), "+f"(d[103]),
      "+f"(d[104]), "+f"(d[105]), "+f"(d[106]), "+f"(d[107]), "+f"(d[108]), "+f"(d[109]), "+f"(d[110]), "+f"(d[111]),
      "+f"(d[112]), "+f"(d[113]), "+f"(d[114]), "+f"(d[115]), "+f"(d[116]), "+f"(d[117]), "+f"(d[118]), "+f"(d[119]),
      "+f"(d[120]), "+f"(d[121]), "+f"(d[122]), "+f"(d[123]), "+f"(d[124]), "+f"(d[125]), "+f"(d[126]), "+f"(d[127])
    : "r"(a0), "r"(a1), "r"(a2), "r"(a3), "l"(db), "r"(sd));
}
__device__ __forceinline__ void wgmma_rs_n64_tb(float (&d)[32], uint32_t a0, uint32_t a1, uint32_t a2, uint32_t a3, uint64_t db, int sd) {
  asm volatile("{\n.reg .pred p;\nsetp.ne.b32 p, %37, 0;\n"
    "wgmma.mma_async.sync.aligned.m64n64k16.f32.bf16.bf16 "
    "{%0, %1, %2, %3, %4, %5, %6, %7, %8, %9, %10, %11, %12, %13, %14, %15, "
    "%16, %17, %18, %19, %20, %21, %22, %23, %24, %25, %26, %27, %28, %29, %30, %31}, "
    "{%32, %33, %34, %35}, %36, p, 1, 1, 1;\n}"
    : "+f"(d[0]), "+f"(d[1]), "+f"(d[2]), "+f"(d[3]), "+f"(d[4]), "+f"(d[5]), "+f"(d[6]), "+f"(d[7]),
      "+f"(d[8]), "+f"(d[9]), "+f"(d[10]), "+f"(d[11]), "+f"(d[12]), "+f"(d[13]), "+f"(d[14]), "+f"(d[15]),
      "+f"(d[16]), "+f"(d[17]), "+f"(d[18]), "+f"(d[19]), "+f"(d[20]), "+f"(d[21]), "+f"(d[22]), "+f"(d[23]),
      "+f"(d[24]), "+f"(d[25]), "+f"(d[26]), "+f"(d[27]), "+f"(d[28]), "+f"(d[29]), "+f"(d[30]), "+f"(d[31])
    : "r"(a0), "r"(a1), "r"(a2), "r"(a3), "l"(db), "r"(sd));
}
__device__ __forceinline__ void wgmma_rs_n32(float (&d)[16], uint32_t a0, uint32_t a1, uint32_t a2, uint32_t a3, uint64_t db, int sd) {
  asm volatile("{\n.reg .pred p;\nsetp.ne.b32 p, %21, 0;\n"
    "wgmma.mma_async.sync.aligned.m64n32k16.f32.bf16.bf16 "
    "{%0, %1, %2, %3, %4, %5, %6, %7, %8, %9, %10, %11, %12, %13, %14, %15}, "
    "{%16, %17, %18, %19}, %20, p, 1, 1, 0;\n}"
    : "+f"(d[0]), "+f"(d[1]), "+f"(d[2]), "+f"(d[3]), "+f"(d[4]), "+f"(d[5]), "+f"(d[6]), "+f"(d[7]),
      "+f"(d[8]), "+f"(d[9]), "+f"(d[10]), "+f"(d[11]), "+f"(d[12]), "+f"(d[13]), "+f"(d[14]), "+f"(d[15])
    : "r"(a0), "r"(a1), "r"(a2), "r"(a3), "l"(db), "r"(sd));
}
__device__ __forceinline__ void wgmma_rs_n64(float (&d)[32], uint32_t a0, uint32_t a1, uint32_t a2, uint32_t a3, uint64_t db, int sd) {
  asm volatile("{\n.reg .pred p;\nsetp.ne.b32 p, %37, 0;\n"
    "wgmma.mma_async.sync.aligned.m64n64k16.f32.bf16.bf16 "
    "{%0, %1, %2, %3, %4, %5, %6, %7, %8, %9, %10, %11, %12, %13, %14, %15, "
    "%16, %17, %18, %19, %20, %21, %22, %23, %24, %25, %26, %27, %28, %29, %30, %31}, "
    "{%32, %33, %34, %35}, %36, p, 1, 1, 0;\n}"
    : "+f"(d[0]), "+f"(d[1]), "+f"(d[2]), "+f"(d[3]), "+f"(d[4]), "+f"(d[5]), "+f"(d[6]), "+f"(d[7]),
      "+f"(d[8]), "+f"(d[9]), "+f"(d[10]), "+f"(d[11]), "+f"(d[12]), "+f"(d[13]), "+f"(d[14]), "+f"(d[15]),
      "+f"(d[16]), "+f"(d[17]), "+f"(d[18]), "+f"(d[19]), "+f"(d[20]), "+f"(d[21]), "+f"(d[22]), "+f"(d[23]),
      "+f"(d[24]), "+f"(d[25]), "+f"(d[26]), "+f"(d[27]), "+f"(d[28]), "+f"(d[29]), "+f"(d[30]), "+f"(d[31])
    : "r"(a0), "r"(a1), "r"(a2), "r"(a3), "l"(db), "r"(sd));
}

__device__ __forceinline__ uint4 lds16(uint32_t a) {
  uint4 v; asm volatile("ld.shared.v4.u32 {%0, %1, %2, %3}, [%4];" : "=r"(v.x), "=r"(v.y), "=r"(v.z), "=r"(v.w) : "r"(a) : "memory"); return v;
}
__device__ __forceinline__ void sts16(uint32_t a, uint32_t x, uint32_t y, uint32_t z, uint32_t w) {
  asm volatile("st.shared.v4.u32 [%0], {%1, %2, %3, %4};" :: "r"(a), "r"(x), "r"(y), "r"(z), "r"(w) : "memory");
}
__device__ __forceinline__ uint32_t lds4(uint32_t a) { uint32_t v; asm volatile("ld.shared.u32 %0, [%1];" : "=r"(v) : "r"(a) : "memory"); return v; }
__device__ __forceinline__ uint32_t lds4v(uint32_t a) { uint32_t v; asm volatile("ld.volatile.shared.u32 %0, [%1];" : "=r"(v) : "r"(a) : "memory"); return v; }
__device__ __forceinline__ uint32_t bmul(uint32_t a, uint32_t b) { uint32_t r; asm("mul.rn.bf16x2 %0, %1, %2;" : "=r"(r) : "r"(a), "r"(b)); return r; }
__device__ __forceinline__ uint32_t badd(uint32_t a, uint32_t b) { uint32_t r; asm("add.rn.bf16x2 %0, %1, %2;" : "=r"(r) : "r"(a), "r"(b)); return r; }

__device__ __forceinline__ void ldsm4(uint32_t (&r)[4], uint32_t a) {
  asm volatile("ldmatrix.sync.aligned.m8n8.x4.shared.b16 {%0, %1, %2, %3}, [%4];" : "=r"(r[0]), "=r"(r[1]), "=r"(r[2]), "=r"(r[3]) : "r"(a) : "memory");
}
__device__ __forceinline__ uint32_t transpose8(uint32_t a) { uint32_t d; asm volatile("movmatrix.sync.aligned.m8n8.trans.b16 %0, %1;" : "=r"(d) : "r"(a)); return d; }

__device__ __forceinline__ void mma16816(float (&d)[4], const uint32_t (&a)[4], uint32_t b0, uint32_t b1) {
  asm volatile("mma.sync.aligned.m16n8k16.row.col.f32.bf16.bf16.f32 {%0, %1, %2, %3}, {%4, %5, %6, %7}, {%8, %9}, {%0, %1, %2, %3};"
               : "+f"(d[0]), "+f"(d[1]), "+f"(d[2]), "+f"(d[3]) : "r"(a[0]), "r"(a[1]), "r"(a[2]), "r"(a[3]), "r"(b0), "r"(b1));
}

#define EXP_SIDE 0
#define SIDE_AHEAD 3
#define ZERO_RD 4
#define CTX_SPLIT 8
#define CONV_EARLY 8
#define CONV_FENCE 12
#define CTX_LD 16
#define PEEK_JJ 7
#define PF_CTX 2
#define STG_PAT 1
#define KV_ORDER 3
#define QFIRST 0
#define UNICAST 2
#define PF_MAPS 3
#define CONV_ARRIVE 13
#define ARRIVE_KK 12
#define SIDE_DELAY_NS 4000
#define KVH(h) (h)
#define HEAD_MAP 2
#define EARLY_LD 1
constexpr int RED_BAR = 6;
constexpr int CV_BAR = 5;
constexpr int PP_BAR = 3;
template <int V> struct Int { static constexpr int value = V; };
struct Ring {
  uint32_t slot, phase;
  __device__ __forceinline__ void next() { if (++slot == NSLOT) { slot = 0; phase ^= 1; } }
};
__device__ __forceinline__ uint32_t bar_addr(uint32_t sb, uint32_t i) { return sb + BARS + 8 * i; }

__device__ __forceinline__ int q_tile(int h, int j, int which) { return ((h < 8) == (which == 0)) ? 15 - j : j; }

constexpr int T_QB = QFIRST ? 0 : 4, IT_KV = QFIRST ? 7 : 0, IT_QB = QFIRST ? 0 : 64;
constexpr int KV_ISV  = KV_ORDER == 0 ? 0xC : KV_ORDER == 1 ? 0xA : KV_ORDER == 2 ? 0x6 : KV_ORDER == 3 ? 0xA : 0xC;
constexpr int KV_PART = KV_ORDER == 0 ? 0xA : KV_ORDER == 1 ? 0xC : KV_ORDER == 2 ? 0xC : KV_ORDER == 3 ? 0x3 : KV_ORDER == 4 ? 0x5 : 0x9;
constexpr int LAST_PART = KV_PART >> 3;
constexpr int T_FIRST = (((KV_PART >> 2) & 1) != LAST_PART ? 3 : 2) + QFIRST;
constexpr int T_LAST = 4 + QFIRST;
__device__ __forceinline__ int p1_isv(int n) { return (KV_ISV >> n) & 1; }
__device__ __forceinline__ int att_head(int h, int which) { return (h & 7) + 8 * which; }
__device__ __forceinline__ int p1_head(int h, int n) { return (h & 7) + 8 * ((KV_PART >> n) & 1); }
__device__ __forceinline__ int p1_rows(int h, int j, int n) { return q_tile(h, j, 0); }
#define KV_FLAG(h) ((h) & 7)
#define KV_COUNT 32
#define F_PART1 (2 * own - 1)

__device__ __forceinline__ void load_tile4(uint32_t dst, const CUtensorMap* m, uint32_t full, int row, int blk0, int rank, bool shared, uint64_t pl = POL_NORMAL) {
  if (shared) {
    tma_ld3_mc(dst + rank * 16384, m, full, 0, row, blk0 + 2 * rank, pl);
  } else {
    tma_ld3(dst, m, full, 0, row, blk0, pl);
    tma_ld3(dst + 16384, m, full, 0, row, blk0 + 2, pl);
  }
}
__device__ __forceinline__ void producer_main(const Params& p, uint32_t sb, int h, int j) {
  const int rank = j & 1;
  Ring r{EARLY_LD, 0};
  auto wait_slot = [&]() { mbar_wait(bar_addr(sb, B_EMPTY + r.slot), r.phase ^ 1); };
  auto load_a = [&](int it, uint32_t dst, uint32_t full) {
    const unsigned u = it - IT_KV;
    if (u < 64) tma_ld2(dst, &p.ckv, full, (u & 15) * 64, p1_rows(h, j, u >> 4) * 128, pol((HINTS & 2) && u >= 48));
    else tma_ld2(dst, &p.x, full, (it < 71 ? it - IT_QB : it - 71) * 64, q_tile(h, j, it < 71) * 128, pol((HINTS & 64) && it >= 71));
  };
  uint32_t prev = 0;
#pragma unroll 1
  for (int it = EARLY_LD; it < P1_STEPS; it++) {
    wait_slot();
    if (it > EARLY_LD && it <= P1_XS) load_a(it - 1, sb + QREG + ((it - 1) & 3) * 16384, prev);
    const uint32_t full = bar_addr(sb, B_FULL + r.slot), dst = sb + r.slot * SLOT;
    mbar_expect_tx(full, it < P1_XS ? 49152 : 32768);
    const unsigned u = it - IT_KV;
    if (u < 64) load_tile4(dst, p1_isv(u >> 4) ? &p.wuv : &p.wuk, full, (u & 15) * 64, p1_head(h, u >> 4) * 4, rank, !(UNICAST & 2), pol(HINTS & 1));
    else load_tile4(dst, &p.wq, full, (it < 71 ? it - IT_QB : it - 71) * 64, att_head(h, it < 71) * 4, rank, !(UNICAST & 2), pol((HINTS & 4) && it >= 71));
    prev = full;
    r.next();
    if (it == P1_XS) {
      wait_slot();
      const uint32_t f2 = bar_addr(sb, B_FULL + r.slot);
      mbar_expect_tx(f2, 32768);
      load_a(P1_XS, sb + r.slot * SLOT, f2);
      load_a(P1_XS + 1, sb + r.slot * SLOT + 16384, f2);
      r.next();
    }
  }
  const int qa = q_tile(h, j, 0), na = 2 * qa + 2, own = 2 * (qa & ~1) + 2;
#pragma unroll 1
  for (int f = 0; f < 68; f++) {
    const bool isK = (f == 0) || ((f & 1) && f < 67);
    const int i = isK ? (f + 1) >> 1 : (f - 1) >> 1, which = i >= na;
    if (f == 0 || f == F_PART1) mbar_wait(bar_addr(sb, B_KVOK + (f & 1)), 0);
    wait_slot();
    const uint32_t full = bar_addr(sb, B_FULL + r.slot);
    mbar_expect_tx(full, 32768);
    const uint32_t src = (uint32_t)(((isK ? 0 : NH) + KVH(att_head(h, which))) * 32 + (which ? 33 - i : i)) * 32768;
    const uint64_t pl = pol(which ? (HINTS & 32) : (HINTS & 8));
    if (!(UNICAST & 1) && (i & ~1) != own) bulk_ld_mc(sb + r.slot * SLOT + rank * 16384, at<uint8_t>(g_kv, src + rank * 16384), 16384, full, pl);
    else bulk_ld_p(sb + r.slot * SLOT, at<uint8_t>(g_kv, src), 32768, full, pl);
    r.next();
  }
#pragma unroll 1
  for (int f = 0; f < 14; f++) {
    const int ch = f < 12 ? 2 * (f >> 2) + (f & 1) : 6, par = f < 12 ? (f >> 1) & 1 : f & 1;
    wait_slot();
    const uint32_t full = bar_addr(sb, B_FULL + r.slot);
    mbar_expect_tx(full, 32768);
    tma_ld5_mc(sb + r.slot * SLOT + rank * 16384, &p.wo, full, ch * 64, (par ? att_head(h ^ 8, 0) : att_head(h, 1)) * 8 + rank * 4, pol(HINTS & 16));
    r.next();
  }
}

__device__ __forceinline__ void helper_main(const Params& p, uint32_t sb, int h, int j, int w) {
  const unsigned epoch = load_epoch();
  const int cta = h * 8 + j, qb = q_tile(h, j, 1);
  const uint32_t qreg = sb + QREG + w * 32768, qfull = bar_addr(sb, B_QFULL + w);
  auto acquire = [&]() {
    flag_wait(flag_at(g_flags.kv_ready, KV_FLAG(h) * 2 + w), KV_COUNT, epoch);
    fence_async_all();
    mbar_arrive(bar_addr(sb, B_KVOK + w));
  };
  if (QFIRST) mbar_wait(bar_addr(sb, B_ST_Q + w), 0);
  mbar_wait(bar_addr(sb, B_ST_KV + w), 0);
  flag_signal(flag_at(g_flags.kv_ready, KV_FLAG(h) * 2 + (LAST_PART ^ 1)));
  if (w != LAST_PART) acquire();
  mbar_wait(bar_addr(sb, B_ST_KV + 2 + w), 0);
  flag_signal(flag_at(g_flags.kv_ready, KV_FLAG(h) * 2 + LAST_PART));
  const bool late = false;
  if (w == LAST_PART && !late) acquire();
  if (!QFIRST) { mbar_wait(bar_addr(sb, B_ST_Q + w), 0); asm volatile("fence.release.gpu;" ::: "memory"); }
  fence_async_all();
  mbar_wait(bar_addr(sb, B_QFREE + w), 0);
  mbar_expect_tx(qfull, 32768);
  bulk_ld(qreg, at<uint8_t>(g_qc, (cta * 2 + w) * 32768), 32768, qfull);
  if (w == LAST_PART && late) acquire();
  auto publish = [&]() { mbar_wait(bar_addr(sb, B_ST_CTX + w), 0); flag_signal(flag_at(g_flags.ctx_ready, cta * 2 + w)); };
  if (qb >= 8) publish();
  flag_wait(flag_at(g_flags.ctx_ready, (cta ^ 64) * 2 + (w ^ 1)), 1, epoch);
  mbar_arrive(bar_addr(sb, B_CTXOK + w));
  if (qb < 8) publish();
  flag_wait(flag_at(g_flags.zero_ready, qb), 8, epoch);
  fence_async_all();
#pragma unroll 1
  for (int ch = 0; ch < 7; ch++) {
    mbar_wait(bar_addr(sb, B_S2_FULL + w * 4 + (ch & 3)), ch >> 2);
    tma_red2(&p.o, qreg + (ch & 3) * 8192, DA + ch * 64, qb * 128 + (w ^ 1) * 64);
    bulk_commit();
    if (ch < 3) { bulk_wait_read(); mbar_arrive(bar_addr(sb, B_S2_EMPTY + w * 4 + ch)); }
  }
  bulk_wait_read();
  GT(48 + w);
}

__device__ __forceinline__ void store_block(uint32_t base, uint32_t lanebase, const uint32_t (&pk)[16]) {
#pragma unroll
  for (int J = 0; J < 8; J += 2) stsm4(base + (lanebase ^ (J << 4)), pk[2 * J], pk[2 * J + 1], pk[2 * J + 2], pk[2 * J + 3]);
}
__device__ __forceinline__ void pack_chunks(uint32_t (&pk)[64], const float (&acc)[128]) {
#pragma unroll
  for (int i = 0; i < 64; i++) { const int e = 16 * (i >> 3) + 4 * (i & 3) + 2 * ((i >> 2) & 1); pk[i] = pack_bf16(acc[e], acc[e + 1]); }
}
__device__ __forceinline__ uint32_t chunk_off() { const uint32_t t = fresh_tid(); return (t & 96) * 32 + (t & 28) * 16 + (((t ^ (t >> 3)) & 3) << 4); }
__device__ __forceinline__ void warp_arrive(uint32_t bar, int lane) { __syncwarp(); if (lane == 0) mbar_arrive(bar); }

__device__ __forceinline__ void consumer_main(const Params& p, uint32_t sb, int h, int j, int w, int wq) {
  const int lane = threadIdx.x & 31;
  const int rank = j & 1;

  auto turn_begin = [&]() { named_sync(PP_BAR + w, 256); };
  auto turn_end = [&]() { named_arrive(PP_BAR + (w ^ 1), 256); };
  Ring r{0, 0};
  auto take = [&](uint32_t ready = 0) { const uint32_t sl = r.slot; mbar_wait_unless(ready, bar_addr(sb, B_FULL + sl), r.phase); r.next(); return sl; };
  uint32_t rdy0 = 0, rdy1 = 0;
  auto peek2 = [&]() { Ring q = r; rdy0 = mbar_test(bar_addr(sb, B_FULL + q.slot), q.phase); q.next(); rdy1 = mbar_test(bar_addr(sb, B_FULL + q.slot), q.phase); };
  auto give = [&](uint32_t sl) { if (lane < 2) mbar_arrive_remote(bar_addr(sb, B_EMPTY + sl), rank ^ lane); };
  float acc[128];
#pragma unroll
  for (int i = 0; i < 128; i++) acc[i] = 0.f;
  uint32_t pk[64];
#pragma unroll
  for (int i = 0; i < 64; i++) pk[i] = 0;
  reg_fence(acc);
  reg_fence(pk);
  cluster_wait();
  TS(0);
  const uint32_t qreg = sb + QREG + w * 32768;
  {
    uint32_t xs = 0, prev = 0;
    uint4* row = nullptr;
    int it = 0;
#pragma unroll 1
    for (int t = 0; t < 6; t++) {
      const int nk = (t == T_QB || t == 5) ? 7 : 16;
#pragma unroll 1
      for (int k = 0; k < nk; k++, it++) {
        const uint32_t ws = take(rdy0);
        TSC(1, it == 0);
        if (it == P1_XS) xs = take();
        const uint32_t aa = (it < P1_XS ? QREG + (it & 3) * 16384 : xs * SLOT + (it - P1_XS) * 16384) + (w ^ (t == T_QB)) * 8192;
        const uint64_t da = desc_k(sb + aa), db = desc_mn(sb + ws * SLOT);
        turn_begin();
        wg_fence();
#pragma unroll
        for (int kk = 0; kk < 4; kk++) wgmma_ss_n256_tb(acc, desc_add(da, kk * 32), desc_add(db, kk * 2048), (k | kk) != 0);
        wg_commit();
        turn_end();
        rdy0 = mbar_test(bar_addr(sb, B_FULL + r.slot), r.phase);
        wg_wait<1>();
        if (k > 0) give(prev);
        prev = ws;
        if (it >= P1_XS - 2 && !(it & 1) && lane == 0) mbar_arrive(bar_addr(sb, B_XFREE + ((it - (P1_XS - 2)) >> 1)));
        if (t > 0) {
          const int c0 = nk == 16 ? k : (16 * k + 3) * 37 >> 8, c1 = nk == 16 ? k + 1 : (16 * k + 19) * 37 >> 8;
#pragma unroll
          for (int i = 0; i < 16; i++)
            if (i >= c0 && i < c1) row[(i >> 1) * 256 + (i & 1) * 32] = make_uint4(pk[4 * i], pk[4 * i + 1], pk[4 * i + 2], pk[4 * i + 3]);
          if (c0 < 16 && c1 >= 16 && (t == T_QB + 1 || t == T_FIRST || t == T_LAST))
            warp_arrive(bar_addr(sb, (t == T_QB + 1 ? B_ST_Q : t == T_LAST ? B_ST_KV + 2 : B_ST_KV) + w), lane);
        }
      }
      if (t == 5) mbar_wait(bar_addr(sb, B_XFREE + w), 0);
      wg_wait<0>();
      reg_fence(acc);
      give(prev);
      pack_chunks(pk, acc);
      const int n = t - QFIRST;
      row = at<uint4>(t != T_QB ? (const void*)g_kv : (const void*)g_qc, chunk_off() +
                      (t != T_QB ? (uint32_t)((p1_isv(n) * NH + KVH(p1_head(h, n))) * 32 + p1_rows(h, j, n) * 2 + w) : (uint32_t)((h * 8 + j) * 2 + w)) * 32768);
      TS(2 + t);
    }
    give(xs);
    const uint32_t qa = qreg + chunk_off();
#pragma unroll
    for (int i = 0; i < 16; i++) sts16(qa + (i >> 1) * 4096 + (i & 1) * 512, pk[4 * i], pk[4 * i + 1], pk[4 * i + 2], pk[4 * i + 3]);
    fence_async_smem();
  }
  TS(8);

  constexpr float SC = 0.0625f * 1.4426950408889634f;
#pragma unroll 1
  for (int which = 0; which < 2; which++) {
    float s[32];
#pragma unroll
    for (int i = 0; i < 32; i++) s[i] = 0.f;
    uint32_t pa[16], pb[16];
    float m0 = 0.f, m1 = 0.f, l0 = 0.f, l1 = 0.f;
    const uint64_t dq = desc_64(qreg);
    uint64_t dk = 0, dqq = 0, dv = 0;
    auto prep_qk = [&](uint32_t kaddr) { dk = desc_64(kaddr); dqq = dq + (kaddr >> 31); asm volatile("" : "+l"(dk), "+l"(dqq)); };
    auto prep_pv = [&](uint32_t vaddr) { dv = desc_64(vaddr); asm volatile("" : "+l"(dv)); };
    auto issue_qk = [&]() {
#pragma unroll
      for (int kk = 0; kk < 16; kk++)
        wgmma_ss_n64(s, desc_add(dqq, (kk >> 1) * 4096 + (kk & 1) * 32), desc_add(dk, (kk >> 1) * 4096 + (kk & 1) * 32), kk != 0);
    };
    auto issue_pv = [&](int accumulate) {
#pragma unroll
      for (int kk = 0; kk < 4; kk++)
        wgmma_rs_n256_tb(acc, pa[4 * kk], pa[4 * kk + 1], pa[4 * kk + 2], pa[4 * kk + 3], desc_add(dv, kk * 1024), accumulate | kk);
    };
    auto mask_diag = [&]() {
      const int d = 16 * wq + (lane >> 2) - 2 * (lane & 3);
#pragma unroll
      for (int jj = 0; jj < 8; jj++) {
        if (8 * jj > d)     { s[4 * jj] = -INFINITY;     if (jj < 7) s[4 * jj + 6] = -INFINITY; }
        if (8 * jj + 1 > d) { s[4 * jj + 1] = -INFINITY; if (jj < 7) s[4 * jj + 7] = -INFINITY; }
      }
    };
    float a0, a1;
    auto softmax = [&]() -> bool {
      float x0 = fmaxf(s[0], s[1]), x1 = fmaxf(s[2], s[3]);
#pragma unroll
      for (int jj = 1; jj < 8; jj++) {
        x0 = fmaxf(x0, fmaxf(s[4 * jj], s[4 * jj + 1]));
        x1 = fmaxf(x1, fmaxf(s[4 * jj + 2], s[4 * jj + 3]));
      }
      x0 = fmaxf(x0, __shfl_xor_sync(0xffffffffu, x0, 1));
      x1 = fmaxf(x1, __shfl_xor_sync(0xffffffffu, x1, 1));
      x0 = fmaxf(x0, __shfl_xor_sync(0xffffffffu, x0, 2));
      x1 = fmaxf(x1, __shfl_xor_sync(0xffffffffu, x1, 2));
      const bool grow = __any_sync(0xffffffffu, fmaxf(x0 - m0, x1 - m1) * SC > 8.f);
      if (grow) {
        x0 = fmaxf(x0, m0); x1 = fmaxf(x1, m1);
        a0 = ex2((m0 - x0) * SC); a1 = ex2((m1 - x1) * SC);
        m0 = x0; m1 = x1;
        l0 *= a0; l1 *= a1;
      }
      const float b0 = -m0 * SC, b1 = -m1 * SC;
      float t0 = 0.f, t1 = 0.f, t2 = 0.f, t3 = 0.f;
#pragma unroll
      for (int jj = 0; jj < 8; jj++) {
        s[4 * jj]     = ex2(fmaf(s[4 * jj], SC, b0));
        s[4 * jj + 1] = ex2(fmaf(s[4 * jj + 1], SC, b0));
        s[4 * jj + 2] = ex2(fmaf(s[4 * jj + 2], SC, b1));
        s[4 * jj + 3] = ex2(fmaf(s[4 * jj + 3], SC, b1));
        t0 += s[4 * jj]; t1 += s[4 * jj + 1]; t2 += s[4 * jj + 2]; t3 += s[4 * jj + 3];
      }
      l0 += t0 + t1; l1 += t2 + t3;
      return grow;
    };
    auto softmax_fast = [&](uint32_t (&pp)[16], auto first, auto hook) -> bool {
      const float b0 = -m0 * SC, b1 = -m1 * SC;
      float t0 = 0.f, t1 = 0.f, t2 = 0.f, t3 = 0.f;
#pragma unroll
      for (int jj = 0; jj < 8; jj++) {
        const float e0 = ex2(fmaf(s[4 * jj], SC, b0)), e1 = ex2(fmaf(s[4 * jj + 1], SC, b0));
        const float e2 = ex2(fmaf(s[4 * jj + 2], SC, b1)), e3 = ex2(fmaf(s[4 * jj + 3], SC, b1));
        hook(jj, e0);
        pp[2 * jj] = pack_bf16(e0, e1); pp[2 * jj + 1] = pack_bf16(e2, e3);
        if (jj == 0) { t0 = e0; t1 = e1; t2 = e2; t3 = e3; } else { t0 += e0; t1 += e1; t2 += e2; t3 += e3; }
      }
      t0 += t1; t2 += t3;
      bool redo = __any_sync(0xffffffffu, !(t0 + t2 <= 16777216.f));
      if (decltype(first)::value) {
        uint32_t u0 = __ballot_sync(0xffffffffu, t0 >= 1.52587890625e-05f), u1 = __ballot_sync(0xffffffffu, t2 >= 1.52587890625e-05f);
        u0 |= u0 >> 1; u1 |= u1 >> 1;
        redo |= (((u0 | (u0 >> 2)) & (u1 | (u1 >> 2))) & 0x11111111u) != 0x11111111u;
      }
      if (!redo) { l0 += t0; l1 += t2; }
      return redo;
    };
    auto rescale = [&]() {
#pragma unroll
      for (int i = 0; i < 32; i++) { acc[4 * i] *= a0; acc[4 * i + 1] *= a0; acc[4 * i + 2] *= a1; acc[4 * i + 3] *= a1; }
    };
    auto to_p = [&](uint32_t (&pp)[16]) {
#pragma unroll
      for (int i = 0; i < 16; i++) pp[i] = pack_bf16(s[2 * i], s[2 * i + 1]);
    };
    auto q_free = [&]() { if (lane == 0) mbar_arrive(bar_addr(sb, B_QFREE + w)); };

    const int n = 2 * q_tile(h, j, which) + 1 + (w ^ which);
    uint32_t ks = take(rdy0);
    TS(9 + 5 * which);
    prep_qk(sb + ks * SLOT);
    turn_begin();
    TS(20 + 10 * which);
    wg_fence();
    issue_qk();
    wg_commit();
    turn_end();
    if (which == 1) give(take(rdy1));
    TS(22 + 10 * which);
    wg_wait<0>();
    TS(21 + 10 * which);
    reg_fence(s);
    give(ks);
    if (which == 0 && n == 1) q_free();
    if (which == 1 || n == 1) mask_diag();
    {
      const uint4* dst = at<uint4>(g_qc, (uint32_t)((h * 8 + j) * 2 + w) * 32768 + (fresh_tid() & 127) * 16);
      const bool redo = softmax_fast(pa, Int<1>(), [&](int jj, float e) {
        if (jj == PEEK_JJ) peek2();
        const int i = CTX_SPLIT + jj;
        if (i < 16)
          asm volatile("{\n.reg .pred p, q;\nsetp.ne.b32 q, %6, 0;\nsetp.geu.and.f32 p, %5, 0fBF800000, q;\n@p st.global.v4.u32 [%0], {%1, %2, %3, %4};\n}"
                       :: "l"(dst + i * 128), "r"(pk[4 * (i & 15)]), "r"(pk[4 * (i & 15) + 1]), "r"(pk[4 * (i & 15) + 2]), "r"(pk[4 * (i & 15) + 3]), "f"(e), "r"(which) : "memory");
      });
      if (redo) {
        m0 = -INFINITY; m1 = -INFINITY;
        softmax();
        to_p(pa);
      }
    }
    if (which == 1) warp_arrive(bar_addr(sb, B_ST_CTX + w), lane);
    TS(10 + 5 * which);
#pragma unroll 1
    for (int jj = 1; jj < n; jj++) {
      ks = take(rdy0);
      const uint32_t vs = take(rdy1);
      prep_qk(sb + ks * SLOT);
      prep_pv(sb + vs * SLOT);
      TSC(23 + 10 * which, jj == 1);
      turn_begin();
      TSC(24 + 10 * which, jj == 1);
      TSC(26 + 10 * which, jj == n - 1);
      wg_fence();
      issue_qk();
      wg_commit();
      issue_pv(jj > 1);
      wg_commit();
      turn_end();
      wg_wait<1>();
      TSC(25 + 10 * which, jj == 1);
      reg_fence(s);
      give(ks);
      if (jj == n - 1 && which == 0) { q_free(); mask_diag(); }
      if (PF_CTX && which == 1 && jj == max(n - PF_CTX, 1)) {
        const uint8_t* src = at<const uint8_t>(g_qc, (uint32_t)(((h ^ 8) * 8 + j) * 2 + (w ^ 1)) * 32768 + (fresh_tid() & 127) * 128);
        asm volatile("prefetch.global.L2 [%0];" :: "l"(src));
        asm volatile("prefetch.global.L2 [%0];" :: "l"(src + 16384));
      }
      if (softmax_fast(pb, Int<0>(), [](int, float) {})) {
        wg_wait<0>();
        reg_fence(acc);
        if (softmax()) rescale();
        to_p(pb);
      }
      peek2();
      wg_wait<0>();
      reg_fence(acc);
      reg_fence(pa);
      give(vs);
#pragma unroll
      for (int i = 0; i < 16; i++) pa[i] = pb[i] | (vs >> 8);
    }
    TS(11 + 5 * which);
    if (which == 0) { give(take(rdy0)); rdy0 = rdy1; }
    {
      const uint32_t vs = take(rdy0);
      prep_pv(sb + vs * SLOT);
      TS(27 + 10 * which);
      turn_begin();
      TS(28 + 10 * which);
      wg_fence();
      issue_pv(n > 1);
      wg_commit();
      turn_end();
      l0 += __shfl_xor_sync(0xffffffffu, l0, 1); l1 += __shfl_xor_sync(0xffffffffu, l1, 1);
      l0 += __shfl_xor_sync(0xffffffffu, l0, 2); l1 += __shfl_xor_sync(0xffffffffu, l1, 2);
      asm("rcp.approx.ftz.f32 %0, %0;" : "+f"(l0));
      asm("rcp.approx.ftz.f32 %0, %0;" : "+f"(l1));
      peek2();
      if (which == 0) mbar_wait(bar_addr(sb, B_QFULL + w), 0);
      wg_wait<0>();
      reg_fence(acc);
      reg_fence(pa);
      give(vs);
    }
    TS(12 + 5 * which);
    {
      const uint4* dst = at<uint4>(g_qc, (uint32_t)((h * 8 + j) * 2 + w) * 32768 + (fresh_tid() & 127) * 16);
#pragma unroll
      for (int i = 0; i < 16; i++) {
        const int c = (i & 1) ? (i >> 1) + 8 : i >> 1;
        pk[4 * c]     = pack_bf16(acc[8 * c] * l0, acc[8 * c + 1] * l0);
        pk[4 * c + 1] = pack_bf16(acc[8 * c + 2] * l1, acc[8 * c + 3] * l1);
        pk[4 * c + 2] = pack_bf16(acc[8 * c + 4] * l0, acc[8 * c + 5] * l0);
        pk[4 * c + 3] = pack_bf16(acc[8 * c + 6] * l1, acc[8 * c + 7] * l1);
        if (c < CTX_SPLIT)
          asm volatile("{\n.reg .pred p;\nsetp.eq.b32 p, %5, 0;\n@p st.global.v4.u32 [%0], {%1, %2, %3, %4};\n}"
                       :: "l"(dst + c * 128), "r"(pk[4 * c]), "r"(pk[4 * c + 1]), "r"(pk[4 * c + 2]), "r"(pk[4 * c + 3]), "r"(which) : "memory");
      }
    }
    TS(13 + 5 * which);
  }

  {
    float oa[32], ob[32];
#pragma unroll
    for (int i = 0; i < 32; i++) { oa[i] = 0.f; ob[i] = 0.f; }
    uint32_t pk2[64];
#pragma unroll
    for (int i = 0; i < 64; i++) pk2[i] = 0;
    auto stage = [&](float (&o)[32], int ch) {
      reg_fence(o);
      uint32_t q[16];
#pragma unroll
      for (int i = 0; i < 16; i++) q[i] = pack_bf16(o[2 * i], o[2 * i + 1]);
      if (ch >= 4) mbar_wait(bar_addr(sb, B_S2_EMPTY + w * 4 + (ch & 3)), 0);
      store_block(qreg + (ch & 3) * 8192, lane_base16(), q);
    };
    auto hand_over = [&](int ch) {
      fence_async_smem();
      warp_arrive(bar_addr(sb, B_S2_FULL + w * 4 + (ch & 3)), lane);
    };
    uint32_t prev = 0;
    auto half = [&](int f, float (&o)[32], uint32_t (&a)[64], int accumulate) {
      const uint32_t sl = take(rdy0);
      const uint64_t d = desc_mn(sb + sl * SLOT);
      turn_begin();
      TS(40 + f);
      wg_fence();
#pragma unroll
      for (int kk = 0; kk < 16; kk++) {
        wgmma_rs_n64_tb(o, a[4 * kk], a[4 * kk + 1], a[4 * kk + 2], a[4 * kk + 3], desc_add(d, kk * 2048), accumulate | kk);
        if (kk == ARRIVE_KK && (f < 13 || w == 0)) turn_end();
      }
      wg_commit();
      if (f < 13) rdy0 = mbar_test(bar_addr(sb, B_FULL + r.slot), r.phase);
      wg_wait<1>();
      if (f >= 1 && f <= 9) give(prev);
      prev = sl;
    };
    auto load_ctx = [&](auto h0) {
      constexpr int I0 = decltype(h0)::value ? CTX_LD : 0, NL = decltype(h0)::value ? 16 - CTX_LD : CTX_LD;
      const uint4* src = at<const uint4>(g_qc, (uint32_t)(((h ^ 8) * 8 + j) * 2 + (w ^ 1)) * 32768 + (fresh_tid() & 127) * 16);
#pragma unroll
      for (int i = I0; i < I0 + NL; i++) { const uint4 v = __ldcg(src + i * 128); pk2[4 * i] = v.x; pk2[4 * i + 1] = v.y; pk2[4 * i + 2] = v.z; pk2[4 * i + 3] = v.w; }
    };
#pragma unroll 1
    for (int i = 0; i < 3; i++) {
      half(4 * i, oa, pk, 0);
      if (i == 0) { mbar_wait(bar_addr(sb, B_CTXOK + w), 0); load_ctx(Int<0>()); }
      else { hand_over(2 * i - 2); stage(ob, 2 * i - 1); }
      half(4 * i + 1, ob, pk, 0);
      if (i == 0) load_ctx(Int<1>()); else hand_over(2 * i - 1);
      half(4 * i + 2, oa, pk2, 1);
      half(4 * i + 3, ob, pk2, 1);
      stage(oa, 2 * i);
    }
    half(12, oa, pk, 0);
    hand_over(4);
    stage(ob, 5);
    half(13, oa, pk2, 1);
    hand_over(5);
    wg_wait<0>();
    reg_fence(pk);
    reg_fence(pk2);
    stage(oa, 6);
    hand_over(6);
  }
  TS(19);
  TDUMP();
}

namespace ssm {
constexpr int NCH = DA / NCONV;
constexpr int NS = 8, NP = 6;
constexpr uint32_t X0 = 384;
constexpr uint32_t HO = X0 + 4096;
constexpr uint32_t HE = HO + HO_STRIDE + 64;
constexpr uint32_t SSLOT = HE + 4096 + 64;
constexpr uint32_t PART = 264 * 16;
constexpr uint32_t OFF_P = NS * SSLOT, OFF_D = OFF_P + NP * 4 * PART, END = OFF_D + NCH * 4;
static_assert(SSLOT % 128 == 0 && HO % 128 == 0 && END <= BARS, "smem");
enum : uint32_t { B_FULL = 0, B_EMPTY = NS, B_PFULL = 2 * NS, B_PEMPTY = 2 * NS + NP };
__device__ __forceinline__ int channel(int cidx, int i) { return (i >> 4) * 64 + cidx * 16 + (i & 15); }

__device__ __forceinline__ void producer(const Params& p, uint32_t sb, int cidx, unsigned epoch) {
#pragma unroll 1
  for (int i = 0; i < NCH; i++) {
    const int s = i % NS, ch = channel(cidx, i);
    const uint32_t full = bar_addr(sb, B_FULL + s), dst = sb + s * SSLOT;
    mbar_wait(bar_addr(sb, B_EMPTY + s), ((i / NS) & 1) ^ 1);
    mbar_expect_tx(full, 4096 + 4128 + 4096);
    bulk_ld(dst + HE, at<uint8_t>(p.a_ssmk, ch * 4096), 4096, full);
    if ((i & 15) == 0) { flag_wait(flag_at(g_flags.x_ready, i >> 4), NMAIN, epoch); fence_async_all(); }
    bulk_ld(dst + HO, at<uint8_t>(g_ho, ch * HO_STRIDE), 4128, full);
    bulk_ld(dst + X0, at<uint8_t>(g_xs, ch * 4096), 4096, full);
  }
}

__device__ __forceinline__ void reducer(uint32_t sb, int cidx, int rw) {
  uint32_t n = 0;
#pragma unroll 1
  for (int i = rw; i < NCH; i += 3, n++) {
    const uint32_t b = rw + 3 * (n & 1), pb = sb + OFF_P + b * 4 * PART;
    uint8_t* dst = at<uint8_t>(g_xs, channel(cidx, i) * 4096);
    mbar_wait(bar_addr(sb, B_PFULL + b), (n >> 1) & 1);
    asm volatile("cp.async.bulk.global.shared::cta.bulk_group [%0], [%1], 4096;" :: "l"(dst), "r"(pb + 3 * PART) : "memory");
    bulk_commit();
    bulk_wait_all();
#pragma unroll
    for (int k = 2; k >= 0; k--)
      asm volatile("cp.reduce.async.bulk.global.shared::cta.bulk_group.add.noftz.bf16 [%0], [%1], 4096;" :: "l"(dst), "r"(pb + k * PART) : "memory");
    bulk_commit();
    bulk_wait_read();
    mbar_arrive(bar_addr(sb, B_PEMPTY + b));
    if (((i + 3) >> 4) != (i >> 4)) {
      bulk_wait_all();
      fence_async_all();
      flag_signal(flag_at(g_flags.z_ready, i >> 4));
    }
  }
}

__device__ __forceinline__ void mma_warpgroup(uint32_t sb, int w) {
  const int lane = threadIdx.x & 31, g = lane >> 2, c = lane & 3, wq = (threadIdx.x >> 5) & 3;
  const uint32_t aoff = ((g & 1) ? HO + 30 : HE) + (16 * wq - g + 2 * c) * 2;
  const uint32_t poff = OFF_P + wq * PART + (2 * wq + lane) * 16;
  const uint32_t dmask = (wq == 0 && c == (g >> 1)) ? ((g & 1) ? 0xffff0000u : 0xffffu) : 0u;
  float acc[8][16];
  uint32_t fa[16][4];
#pragma unroll
  for (int e = 0; e < 8; e++)
#pragma unroll
    for (int i = 0; i < 16; i++) acc[e][i] = 0.f;
  auto load_a = [&](int m, uint32_t ad) {
    fa[m][0] = lds4(ad + m * 256 + 16); fa[m][1] = lds4(ad + m * 256 + 144); fa[m][2] = lds4(ad + m * 256); fa[m][3] = lds4(ad + m * 256 + 128);
  };
  if (w == 1) named_arrive(PP_BAR, 256);
  mbar_wait(bar_addr(sb, B_FULL + w), 0);
#pragma unroll
  for (int m = 0; m < 16; m++) load_a(m, sb + w * SSLOT + aoff);
  uint32_t dd = lds4(sb + OFF_D + w * 4);
  if (threadIdx.x == 128) { GT(12); PT(10); }
  uint32_t pb = w, pphase = 1;
#pragma unroll 1
  for (int i = w; i < NCH; i += 2) {
    fa[0][2] = badd(fa[0][2], dd & dmask);
    const uint64_t db = (uint64_t)((((sb + (i % NS) * SSLOT + X0 - 16) & 0x3FFFF) >> 4) | (1u << 16)) | ((uint64_t)8 << 32);
    named_sync(PP_BAR + w, 256);
    wg_fence();
#pragma unroll
    for (int r = 0; r < 16; r++) {
      auto mm = [&](int e, int m) { wgmma_rs_n32(acc[e], fa[m][0], fa[m][1], fa[m][2], fa[m][3], db + (int64_t)(32 * e - 16 * m), m != 0); };
      mm(7, r);
      if (r < 14) mm(6, r); else mm(0, r - 14);
      if (r < 12) mm(5, r); else mm(1, r - 12);
      if (r < 10) mm(4, r); else mm(2, r - 10);
      if ((r & 1) == 0) mm(3, r >> 1);
      if (r == CONV_ARRIVE && (i + 1 < NCH)) named_arrive(PP_BAR + (w ^ 1), 256);
    }
    wg_commit();
    const int nx = i + 2 < NCH ? i + 2 : i;
    mbar_wait(bar_addr(sb, B_FULL + nx % NS), (nx / NS) & 1);
    mbar_wait(bar_addr(sb, B_PEMPTY + pb), pphase);
    const uint32_t ad = sb + (nx % NS) * SSLOT + aoff, pa = sb + pb * 4 * PART + poff;
    wg_wait<0>();
#pragma unroll
    for (int e = 0; e < 8; e++) reg_fence(acc[e]);
#pragma unroll
    for (int m = 0; m < 16; m++) reg_fence(fa[m]);
    if (lane == 0) mbar_arrive(bar_addr(sb, B_EMPTY + i % NS));
#pragma unroll
    for (int e = 0; e < 8; e++) {
      if (e < CONV_EARLY) load_a(e, ad);
      uint32_t u[4];
#pragma unroll
      for (int j = 0; j < 4; j++) {
        const int T = 4 * e + j, U = T - 1;
        float lo = acc[e][4 * j], hi = acc[e][4 * j + 1];
        if (T > 0) { lo += acc[U >> 2][4 * (U & 3) + 2]; hi += acc[U >> 2][4 * (U & 3) + 3]; }
        u[j] = pack_bf16(lo, hi);
      }
      asm volatile("stmatrix.sync.aligned.m8n8.x4.trans.shared.b16 [%0], {%1, %2, %3, %4};" :: "r"(pa + e * 512), "r"(u[0]), "r"(u[1]), "r"(u[2]), "r"(u[3]) : "memory");
    }
    dd = lds4(sb + OFF_D + nx * 4);
#pragma unroll
    for (int m = CONV_EARLY; m < CONV_FENCE; m++) load_a(m, ad);
    fence_async_smem();
    warp_arrive(bar_addr(sb, B_PFULL + pb), lane);
#pragma unroll
    for (int m = CONV_FENCE; m < 16; m++) load_a(m, ad);
    pb += 2;
    if (pb >= NP) { pb -= NP; pphase ^= 1; }
  }
  if (threadIdx.x == 128) { PT(9); GT(13); }
}

__device__ __forceinline__ void init(const Params& p, uint32_t sb, int cidx) {
  const uint32_t t = threadIdx.x;
  if (t < NCH) {
    const uint32_t d = (uint32_t)__ldg(reinterpret_cast<const unsigned short*>(p.a_D + channel(cidx, t))) * 0x10001u;
    asm volatile("st.shared.u32 [%0], %1;" :: "r"(sb + OFF_D + t * 4), "r"(d) : "memory");
  }
#pragma unroll 1
  for (uint32_t u = t; u < NS * 32; u += 128) {
    const uint32_t r = u & 31;
    if (r < 28) sts16(sb + (u >> 5) * SSLOT + (r < 24 ? r * 16 : HE - 64 + (r - 24) * 16), 0, 0, 0, 0);
    if (u < NP * 32) sts16(sb + OFF_P + (u >> 3) * PART + (u & 7) * 16, 0, 0, 0, 0);
  }
  if (t == 0) {
    for (int i = 0; i < NS; i++) { mbar_init(bar_addr(sb, B_FULL + i), 1); mbar_init(bar_addr(sb, B_EMPTY + i), 4); }
    for (int i = 0; i < NP; i++) { mbar_init(bar_addr(sb, B_PFULL + i), 4); mbar_init(bar_addr(sb, B_PEMPTY + i), 1); }
  }
  fence_async_smem();
}

__device__ __forceinline__ void side_prepare(const Params& p, int cta, int rd) {
  const int lane = threadIdx.x & 31, t0 = 16 * cta + 8 * (lane & 1);
  if (EXP_SIDE & 16) { if (lane == 0) flag_signal_after_bulk(flag_at(g_flags.x_ready, rd)); return; }
#pragma unroll 1
  for (int ch = 64 * rd + (lane & ~1); ch < 64 * rd + 64; ch += 32) {
    const uint4 sv = __ldg(at<const uint4>(p.a_shift, ch * 8));
    const uint32_t* kp = at<const uint32_t>(p.a_k, (t0 * DA + ch) * 2);
    const uint32_t* vp = at<const uint32_t>(p.a_v, (t0 * DA + ch) * 2);
    uint32_t k0 = 0, k1 = 0, k2 = 0, kk[8], x[8];
    if (t0 > 0) { k0 = __ldg(kp - 3 * (DA / 2)); k1 = __ldg(kp - 2 * (DA / 2)); k2 = __ldg(kp - DA / 2); }
#pragma unroll
    for (int i = 0; i < 8; i++) { kk[i] = __ldg(kp + i * (DA / 2)); x[i] = __ldg(vp + i * (DA / 2)); }
    const uint32_t sh0 = __byte_perm(sv.x, sv.z, 0x5410), sh1 = __byte_perm(sv.x, sv.z, 0x7632);
    const uint32_t sh2 = __byte_perm(sv.y, sv.w, 0x5410), sh3 = __byte_perm(sv.y, sv.w, 0x7632);
#pragma unroll
    for (int i = 0; i < 8; i++) {
      uint32_t ks = bmul(k0, sh3);
      ks = badd(ks, bmul(k1, sh2)); ks = badd(ks, bmul(k2, sh1)); ks = badd(ks, bmul(kk[i], sh0));
      x[i] = bmul(ks, x[i]);
      k0 = k1; k1 = k2; k2 = kk[i];
    }
    uint4* dst = at<uint4>(g_xs, ch * 4096 + t0 * 2);
    if ((EXP_SIDE & 4) && (x[0] ^ x[1] ^ x[2] ^ x[3] ^ x[4] ^ x[5] ^ x[6] ^ x[7]) != 0x12345) continue;
    dst[0]   = make_uint4(__byte_perm(x[7], x[6], 0x5410), __byte_perm(x[5], x[4], 0x5410), __byte_perm(x[3], x[2], 0x5410), __byte_perm(x[1], x[0], 0x5410));
    dst[256] = make_uint4(__byte_perm(x[7], x[6], 0x7632), __byte_perm(x[5], x[4], 0x7632), __byte_perm(x[3], x[2], 0x7632), __byte_perm(x[1], x[0], 0x7632));
  }
  if (!(EXP_SIDE & 8)) {
    const int hc = 64 * rd + (cta >> 1), r0 = (cta & 1) * 128 + lane;
    const uint4* src = at<const uint4>(p.a_ssmk, hc * 4096 + r0 * 16);
    uint4* dst = at<uint4>(g_ho, hc * HO_STRIDE + r0 * 16);
    uint4 w[4];
    uint32_t nx[4];
#pragma unroll
    for (int i = 0; i < 4; i++) { w[i] = __ldg(src + 32 * i); nx[i] = r0 + 32 * i < 255 ? __ldg(reinterpret_cast<const uint32_t*>(src + 32 * i + 1)) : 0u; }
#pragma unroll
    for (int i = 0; i < 4; i++)
      dst[32 * i + 2] = make_uint4(__byte_perm(w[i].x, w[i].y, 0x5432), __byte_perm(w[i].y, w[i].z, 0x5432), __byte_perm(w[i].z, w[i].w, 0x5432), __byte_perm(w[i].w, nx[i], 0x5432));
    const uint32_t h0 = __shfl_sync(0xffffffffu, w[0].x, 0);
    if (r0 < 2) dst[0] = make_uint4(0, 0, 0, r0 ? h0 << 16 : 0u);
  }
  __syncwarp();
  if (lane == 0) { if (EXP_SIDE & 2) flag_signal_after_bulk(flag_at(g_flags.x_ready, rd)); else flag_signal(flag_at(g_flags.x_ready, rd)); }
}
__device__ __forceinline__ void side_finish(const Params& p, int cta, int rd) {
  const int lane = threadIdx.x & 31, t0 = 16 * cta + 8 * (lane & 1);
#pragma unroll 1
  for (int ch = 64 * rd + (lane & ~1); ch < 64 * rd + 64; ch += 32) {
    const uint4* src = at<const uint4>(g_xs, ch * 4096 + t0 * 2);
    const uint32_t* qp = at<const uint32_t>(p.a_q, (t0 * DA + ch) * 2);
    uint32_t* op = at<uint32_t>(p.out, (t0 * OUTW + ch) * 2);
    const uint4 z0 = __ldcg(src), z1 = __ldcg(src + 256);
    uint32_t q[8];
#pragma unroll
    for (int i = 0; i < 8; i++) q[i] = __ldg(qp + i * (DA / 2));
    const uint32_t a[4] = {z0.w, z0.z, z0.y, z0.x}, b[4] = {z1.w, z1.z, z1.y, z1.x};
#pragma unroll
    for (int i = 0; i < 4; i++) {
      op[(2 * i) * (OUTW / 2)]     = bmul(q[2 * i], __byte_perm(a[i], b[i], 0x7632));
      op[(2 * i + 1) * (OUTW / 2)] = bmul(q[2 * i + 1], __byte_perm(a[i], b[i], 0x5410));
    }
  }
}
__device__ __forceinline__ void clear_rows(const Params& p, int qt, int part) {
  const int lane = threadIdx.x & 31;
  if (lane < 28) {
    uint4* z = at<uint4>(p.out, ((qt * 128 + part * 16) * OUTW + DA) * 2 + lane * 16);
#pragma unroll
    for (int i = 0; i < 32; i++) z[(i >> 1) * (OUTW / 8) + (i & 1) * 28] = make_uint4(0, 0, 0, 0);
  }
  __syncwarp();
  if (lane == 0) flag_signal(flag_at(g_flags.zero_ready, qt));
}
__device__ __forceinline__ void side_work(const Params& p, int cta, int qt, unsigned epoch) {
#pragma unroll 1
  for (int rd = -SIDE_AHEAD; rd < 7; rd++) {
    if (rd >= 0) {
      if ((threadIdx.x & 31) == 0) flag_wait_slow(flag_at(g_flags.z_ready, rd), 3 * NCONV, epoch);
      __syncwarp();
    }
    if (rd + SIDE_AHEAD < 7) side_prepare(p, cta, rd + SIDE_AHEAD);
    if (rd >= 0 && !(EXP_SIDE & 1)) side_finish(p, cta, rd);
    if (rd == ZERO_RD) clear_rows(p, qt, (cta >> 3) & 7);
  }
}
}

__global__ void __cluster_dims__(2, 1, 1) __launch_bounds__(NTHREADS, 1)
concat_heads__ssm_conv_h3__compressed_kv_cla__prompt_kernel(const __grid_constant__ Params p) {
  extern __shared__ uint8_t smem_raw[];
  const uint32_t sb = (smem_u32(smem_raw) + 1023) & ~1023u;
  const int warp = __shfl_sync(0xffffffffu, threadIdx.x >> 5, 0);
  const int wg = warp >> 2;
  const int cta = blockIdx.x;
  const bool attn = cta < NMAIN;
  int h, u;
  {
    const int c = cta >> 1;
    if (c < 4) { h = 9; u = c; }
    else if (c < 36) { h = (c - 4) & 7; u = (c - 4) >> 3; }
    else { const int i = (c - 36) % 7; h = i == 0 ? 8 : 9 + i; u = (c - 36) / 7; }
  }
  const int j = 2 * u + (cta & 1);
  const int lane = threadIdx.x & 31;
  if (wg != 0) {
    if (attn) {
      if (threadIdx.x == NTHREADS - 32) {
        if (PF_MAPS & 2) prefetch_map(QFIRST ? &p.wq : &p.wuk);
        for (int i = 0; i < NSLOT; i++) mbar_init(bar_addr(sb, B_FULL + i), 1);
        asm volatile("fence.mbarrier_init.release.cluster;" ::: "memory");
      }
      __syncwarp();
      cluster_arrive();
      if (wg == 2) named_arrive(PP_BAR, 256);
      if (threadIdx.x == NTHREADS - 32) {
        for (int k = 0; k < EARLY_LD; k++) {
          const uint32_t full = bar_addr(sb, B_FULL + k);
          mbar_expect_tx(full, 49152);
          if (QFIRST) {
            tma_ld2(sb + QREG + k * 16384, &p.x, full, k * 64, q_tile(h, j, 1) * 128);
            load_tile4(sb + k * SLOT, &p.wq, full, k * 64, att_head(h, 1) * 4, j & 1, false);
          } else {
            tma_ld2(sb + QREG + k * 16384, &p.ckv, full, k * 64, p1_rows(h, j, 0) * 128);
            load_tile4(sb + k * SLOT, &p.wuk, full, k * 64, p1_head(h, 0) * 4, j & 1, false);
          }
        }
      }
      __syncwarp();
    }
    asm volatile("setmaxnreg.inc.sync.aligned.u32 232;");
    if (!attn) {
      if (p.out != nullptr) { named_sync(0, NTHREADS); ssm::mma_warpgroup(sb, wg - 1); }
      return;
    }
    if (p.out != nullptr) consumer_main(p, sb, h, j, wg - 1, warp & 3);
  } else {
    asm volatile("setmaxnreg.dec.sync.aligned.u32 40;");
    if (!attn) {
      ssm::init(p, sb, cta - NMAIN);
      named_sync(0, NTHREADS);
      if (lane == 0) {
        if (warp == 0) { ssm::producer(p, sb, cta - NMAIN, load_epoch()); cta_done(32); }
        else ssm::reducer(sb, cta - NMAIN, warp - 1);
        if (warp == 1) GT(14);
      }
      return;
    }
    if (lane == 0) {
      if (warp == 1) {
        for (int i = 0; i < NSLOT; i++) mbar_init(bar_addr(sb, B_EMPTY + i), 16);
        for (int i = 0; i < 2; i++) {
          mbar_init(bar_addr(sb, B_XFREE + i), 8); mbar_init(bar_addr(sb, B_QFREE + i), 4); mbar_init(bar_addr(sb, B_QFULL + i), 1);
          mbar_init(bar_addr(sb, B_KVOK + i), 1); mbar_init(bar_addr(sb, B_CTXOK + i), 1);
        }
      } else if (warp == 2) {
        for (int i = 0; i < 8; i++) { mbar_init(bar_addr(sb, B_S2_FULL + i), 4); mbar_init(bar_addr(sb, B_S2_EMPTY + i), 1); }
      } else if (warp == 0) {
        mbar_init(bar_addr(sb, B_DONE), 2);
        for (int i = 0; i < 2; i++) {
          mbar_init(bar_addr(sb, B_ST_KV + i), 4); mbar_init(bar_addr(sb, B_ST_KV + 2 + i), 4);
          mbar_init(bar_addr(sb, B_ST_Q + i), 4); mbar_init(bar_addr(sb, B_ST_CTX + i), 4);
        }
      }
      asm volatile("fence.mbarrier_init.release.cluster;" ::: "memory");
    }
    __syncwarp();
    cluster_arrive();
    cluster_wait();
    if (warp == 0) {
      if (lane == 0) producer_main(p, sb, h, j);
    } else if (warp < 3) {
      if (lane == 0) {
        if ((PF_MAPS & 1) && warp == 1) { __nanosleep(2000); prefetch_map(&p.wuv); prefetch_map(&p.x); prefetch_map(&p.wq); prefetch_map(&p.o); prefetch_map(&p.wo); }
        helper_main(p, sb, h, j, warp - 1);
        mbar_arrive(bar_addr(sb, B_DONE));
      }
    } else {
      ssm::side_work(p, h * 8 + j, q_tile(h, j, 1), load_epoch());
      if (lane == 0) { GT(57); mbar_wait(bar_addr(sb, B_DONE), 0); cta_done(1); }
    }
  }
}

typedef CUresult (*EncodeTiledFn)(CUtensorMap*, CUtensorMapDataType, cuuint32_t, void*, const cuuint64_t*, const cuuint64_t*,
                                  const cuuint32_t*, const cuuint32_t*, CUtensorMapInterleave, CUtensorMapSwizzle,
                                  CUtensorMapL2promotion, CUtensorMapFloatOOBfill);

void make_map(EncodeTiledFn enc, CUtensorMap* m, const void* ptr, int rank, const uint64_t* dims, const uint64_t* strides, const uint32_t* box) {
  cuuint64_t d[5], s[4]; cuuint32_t b[5], e[5] = {1, 1, 1, 1, 1};
  for (int i = 0; i < rank; i++) { d[i] = dims[i]; b[i] = box[i]; if (i) s[i - 1] = strides[i - 1]; }
  enc(m, CU_TENSOR_MAP_DATA_TYPE_BFLOAT16, rank, const_cast<void*>(ptr), d, s, b, e, CU_TENSOR_MAP_INTERLEAVE_NONE,
      CU_TENSOR_MAP_SWIZZLE_128B, CU_TENSOR_MAP_L2_PROMOTION_L2_256B, CU_TENSOR_MAP_FLOAT_OOB_FILL_NONE);
}
void map2(EncodeTiledFn enc, CUtensorMap* m, const void* ptr, uint64_t cols, uint64_t rows, uint32_t bc, uint32_t br) {
  const uint64_t dims[2] = {cols, rows}, st[1] = {cols * 2}; const uint32_t box[2] = {bc, br};
  make_map(enc, m, ptr, 2, dims, st, box);
}
void map3(EncodeTiledFn enc, CUtensorMap* m, const void* ptr, uint64_t rows, uint32_t nblk) {
  const uint64_t dims[3] = {64, rows, 64}, st[2] = {8192, 128}; const uint32_t box[3] = {64, 64, nblk};
  make_map(enc, m, ptr, 3, dims, st, box);
}

}

extern "C" void kernel_launch(void* const* d_in, const int* in_sizes, int n_in, void* d_out, int out_size) {
  (void)in_sizes; (void)n_in; (void)out_size;
  static EncodeTiledFn enc = nullptr;
  if (!enc) {
    void* fn = nullptr; cudaDriverEntryPointQueryResult qr;
    cudaGetDriverEntryPoint("cuTensorMapEncodeTiled", &fn, cudaEnableDefault, &qr);
    enc = (EncodeTiledFn)fn;
    cudaFuncSetAttribute(concat_heads__ssm_conv_h3__compressed_kv_cla__prompt_kernel, cudaFuncAttributeMaxDynamicSharedMemorySize, SMEM_BYTES);
  }
  Params p;
  p.a_q = (const bf16*)d_in[0]; p.a_k = (const bf16*)d_in[1]; p.a_v = (const bf16*)d_in[2];
  p.a_shift = (const bf16*)d_in[3]; p.a_ssmk = (const bf16*)d_in[4]; p.a_D = (const bf16*)d_in[5];
  p.out = (bf16*)d_out;
  map2(enc, &p.x, d_in[6], DM, SEQ, 64, 128);
  map2(enc, &p.ckv, d_in[7], DC, SEQ, 64, 128);
  map3(enc, &p.wq, d_in[8], DM, 2);
  map3(enc, &p.wuk, d_in[9], DC, 2);
  map3(enc, &p.wuv, d_in[10], DC, 2);
  {
    const uint64_t dims[5] = {DM, 2, 4, 4, NH * HD / 32}, st[4] = {DM * 2, 8 * DM * 2, 2 * DM * 2, 32 * DM * 2}; const uint32_t box[5] = {64, 2, 4, 4, 4};
    make_map(enc, &p.wo, d_in[11], 5, dims, st, box);
  }
  map2(enc, &p.o, d_out, OUTW, SEQ, 64, 64);
  concat_heads__ssm_conv_h3__compressed_kv_cla__prompt_kernel<<<NCTA, NTHREADS, SMEM_BYTES>>>(p);
}
```

```cpp
#include <cuda_runtime.h>
#include <cuda_bf16.h>
#include <cuda.h>
#include <stdint.h>

namespace {

typedef __nv_bfloat16 bf16;

constexpr int SEQ  = 2048;
constexpr int DA   = 448;
constexpr int NH   = 16;
constexpr int HD   = 256;
constexpr int DM   = 448;
constexpr int DC   = 1024;
constexpr int OUTW = DA + DM;
constexpr int NMAIN = 128;
constexpr int NCONV = 4;
constexpr int NCTA  = NMAIN + NCONV;
constexpr int LOG_DONE = 8;
constexpr int NTHREADS = 384;

__device__ __align__(1024) bf16 g_kv[2ull * SEQ * NH * HD];
__device__ __align__(1024) bf16 g_qc[(size_t)NMAIN * 128 * HD];
__device__ __align__(128) uint8_t g_xs[DA * SEQ * 2];
constexpr uint32_t HO_STRIDE = 4224;
__device__ __align__(128) uint8_t g_ho[DA * HO_STRIDE];
struct alignas(128) Flag { unsigned v; unsigned pad[31]; };
struct Flags {
  Flag kv_ready[NH * 2];
  Flag ctx_ready[NMAIN * 2];
  Flag x_ready[7];
  Flag z_ready[7];
  Flag zero_ready[16];
  alignas(128) unsigned long long done;
};
__device__ Flags g_flags;
#define TS(i)
#define TSC(i, cond)
#define TDUMP()
#define GT(i)
#define PT(i)
#define PCLK(var)
#define PACC(acc, t0)

struct alignas(64) Params {
  CUtensorMap ckv;
  CUtensorMap wuk;
  CUtensorMap wuv;
  CUtensorMap x;
  CUtensorMap wq;
  CUtensorMap o;
  CUtensorMap wo;
  const bf16 *a_q, *a_k, *a_v, *a_shift, *a_ssmk, *a_D;
  bf16* out;
};

constexpr uint32_t SLOT     = 32768;
constexpr int      NSLOT    = 5;
constexpr uint32_t QREG     = 163840;
constexpr uint32_t BARS     = 229376;
constexpr uint32_t SMEM_BYTES = BARS + 1024 + 1024;
enum : uint32_t {
  B_FULL = 0, B_EMPTY = 5, B_KVOK = 12, B_ST_Q = 14, B_ST_CTX = 16, B_DONE = 19, B_QFREE = 20, B_QFULL = 22,
  B_S2_FULL = 24, B_S2_EMPTY = 32, B_CTXOK = 40, B_PF = 42, B_ST_KV = 44
};
constexpr int P1_STEPS = 4 * 16 + 2 * 7, P1_XS = P1_STEPS - 2;

template <typename T> __device__ __forceinline__ T* at(const void* base, uint32_t off) {
  asm volatile("" : "+r"(off));
  return reinterpret_cast<T*>(const_cast<char*>(static_cast<const char*>(base)) + off);
}
__device__ __forceinline__ unsigned* flag_at(Flag* f, uint32_t i) { return at<unsigned>(f, i * (uint32_t)sizeof(Flag)); }
__device__ __forceinline__ uint32_t smem_u32(const void* p) { return (uint32_t)__cvta_generic_to_shared(p); }
__device__ __forceinline__ void mbar_init(uint32_t bar, uint32_t cnt) {
  asm volatile("mbarrier.init.shared::cta.b64 [%0], %1;" :: "r"(bar), "r"(cnt) : "memory");
}
__device__ __forceinline__ void mbar_expect_tx(uint32_t bar, uint32_t bytes) {
  asm volatile("mbarrier.arrive.expect_tx.shared::cta.b64 _, [%0], %1;" :: "r"(bar), "r"(bytes) : "memory");
}
__device__ __forceinline__ void mbar_arrive(uint32_t bar) {
  asm volatile("mbarrier.arrive.shared::cta.b64 _, [%0];" :: "r"(bar) : "memory");
}
__device__ __forceinline__ void mbar_arrive_n(uint32_t bar, uint32_t n) {
  asm volatile("mbarrier.arrive.shared::cta.b64 _, [%0], %1;" :: "r"(bar), "r"(n) : "memory");
}
__device__ __forceinline__ void mbar_arrive_remote(uint32_t bar, uint32_t cta) {
  asm volatile("{\n.reg .b32 ra;\nmapa.shared::cluster.u32 ra, %0, %1;\n"
               "mbarrier.arrive.shared::cluster.b64 _, [ra];\n}" :: "r"(bar), "r"(cta) : "memory");
}
__device__ __forceinline__ bool mbar_try(uint32_t bar, uint32_t parity) {
  uint32_t ok;
  asm volatile("{\n.reg .pred p;\nmbarrier.try_wait.parity.shared::cta.b64 p, [%1], %2;\nselp.u32 %0, 1, 0, p;\n}"
               : "=r"(ok) : "r"(bar), "r"(parity) : "memory");
  return ok;
}
__device__ __forceinline__ uint32_t mbar_test(uint32_t bar, uint32_t parity) {
  uint32_t ok;
  asm volatile("{\n.reg .pred p;\nmbarrier.test_wait.parity.shared::cta.b64 p, [%1], %2;\nselp.u32 %0, 1, 0, p;\n}"
               : "=r"(ok) : "r"(bar), "r"(parity) : "memory");
  return ok;
}
constexpr uint32_t SPIN_LIMIT = 1u << 24;
__device__ __forceinline__ void mbar_wait(uint32_t bar, uint32_t parity) {
  if (mbar_try(bar, parity)) return;
  uint32_t n = 0;
  while (!mbar_try(bar, parity)) { if (++n > SPIN_LIMIT) __trap(); }
}
__device__ __forceinline__ void mbar_wait_unless(uint32_t ready, uint32_t bar, uint32_t parity) {
  asm volatile("{\n.reg .pred p;\n.reg .b32 n;\nsetp.ne.u32 p, %0, 0;\nvote.sync.all.pred p, p, 0xffffffff;\n@p bra.uni WDONE;\nmov.u32 n, 0;\n"
               "WLOOP:\nmbarrier.try_wait.parity.shared::cta.b64 p, [%1], %2;\n@p bra.uni WDONE;\nadd.u32 n, n, 1;\nsetp.lt.u32 p, n, %3;\n@p bra.uni WLOOP;\ntrap;\nWDONE:\n}"
               :: "r"(ready), "r"(bar), "r"(parity), "n"(SPIN_LIMIT) : "memory");
}
__device__ __forceinline__ unsigned load_epoch() {
  unsigned long long d; asm volatile("ld.relaxed.gpu.global.u64 %0, [%1];" : "=l"(d) : "l"(&g_flags.done) : "memory");
  return (unsigned)(d >> LOG_DONE);
}
__device__ __forceinline__ void flag_wait(const unsigned* f, unsigned count, unsigned epoch) {
  const unsigned target = (epoch + 1) * count;
  uint32_t n = 0;
  while (true) {
    unsigned v;
    asm volatile("ld.acquire.gpu.global.u32 %0, [%1];" : "=r"(v) : "l"(f) : "memory");
    if ((int)(v - target) >= 0) break;
    if (++n > SPIN_LIMIT) __trap();
    __nanosleep(20);
  }
}
__device__ __forceinline__ void flag_wait_slow(const unsigned* f, unsigned count, unsigned epoch) {
  const unsigned target = (epoch + 1) * count;
  uint32_t n = 0;
  while (true) {
    unsigned v;
    asm volatile("ld.acquire.gpu.global.u32 %0, [%1];" : "=r"(v) : "l"(f) : "memory");
    if ((int)(v - target) >= 0) break;
    if (++n > SPIN_LIMIT / 16) __trap();
    __nanosleep(1000);
  }
}
__device__ __forceinline__ void cta_done(unsigned long long n) { asm volatile("red.relaxed.gpu.global.add.u64 [%0], %1;" :: "l"(&g_flags.done), "l"(n) : "memory"); }
__device__ __forceinline__ void flag_wait_fast(const unsigned* f, unsigned count, unsigned epoch) {
  const unsigned target = (epoch + 1) * count;
  uint32_t n = 0;
  while (true) {
    unsigned v;
    asm volatile("ld.acquire.gpu.global.u32 %0, [%1];" : "=r"(v) : "l"(f) : "memory");
    if ((int)(v - target) >= 0) break;
    if (++n > SPIN_LIMIT) __trap();
  }
}
__device__ __forceinline__ void fence_async_all() { asm volatile("fence.proxy.async.global;" ::: "memory"); }
__device__ __forceinline__ void flag_signal(unsigned* f) { asm volatile("red.release.gpu.global.add.u32 [%0], 1;" :: "l"(f) : "memory"); }
__device__ __forceinline__ void flag_signal_after_bulk(unsigned* f) {
  asm volatile("red.relaxed.gpu.global.add.u32 [%0], 1;" :: "l"(f) : "memory");
}
__device__ __forceinline__ void fence_async_smem() { asm volatile("fence.proxy.async.shared::cta;" ::: "memory"); }
#define HINTS 40
constexpr uint64_t POL_NORMAL = 0x1000000000000000ull, POL_FIRST = 0x12F0000000000000ull;
__device__ __forceinline__ constexpr uint64_t pol(bool first) { return first ? POL_FIRST : POL_NORMAL; }
__device__ __forceinline__ void tma_ld2(uint32_t dst, const CUtensorMap* m, uint32_t bar, int c0, int c1, uint64_t pl = POL_NORMAL) {
  asm volatile("cp.async.bulk.tensor.2d.shared::cluster.global.mbarrier::complete_tx::bytes.L2::cache_hint [%0], [%1, {%3, %4}], [%2], %5;"
               :: "r"(dst), "l"(m), "r"(bar), "r"(c0), "r"(c1), "l"(pl) : "memory");
}
__device__ __forceinline__ void tma_ld3(uint32_t dst, const CUtensorMap* m, uint32_t bar, int c0, int c1, int c2, uint64_t pl = POL_NORMAL) {
  asm volatile("cp.async.bulk.tensor.3d.shared::cluster.global.mbarrier::complete_tx::bytes.L2::cache_hint [%0], [%1, {%3, %4, %5}], [%2], %6;"
               :: "r"(dst), "l"(m), "r"(bar), "r"(c0), "r"(c1), "r"(c2), "l"(pl) : "memory");
}
__device__ __forceinline__ void tma_ld3_mc(uint32_t dst, const CUtensorMap* m, uint32_t bar, int c0, int c1, int c2, uint64_t pl = POL_NORMAL) {
  asm volatile("cp.async.bulk.tensor.3d.shared::cluster.global.mbarrier::complete_tx::bytes.multicast::cluster.L2::cache_hint [%0], [%1, {%3, %4, %5}], [%2], %6, %7;"
               :: "r"(dst), "l"(m), "r"(bar), "r"(c0), "r"(c1), "r"(c2), "h"((uint16_t)3), "l"(pl) : "memory");
}
__device__ __forceinline__ void bulk_ld(uint32_t dst, const void* src, uint32_t bytes, uint32_t bar) {
  asm volatile("cp.async.bulk.shared::cluster.global.mbarrier::complete_tx::bytes [%0], [%1], %2, [%3];"
               :: "r"(dst), "l"(src), "r"(bytes), "r"(bar) : "memory");
}
__device__ __forceinline__ void bulk_ld_p(uint32_t dst, const void* src, uint32_t bytes, uint32_t bar, uint64_t pl) {
  asm volatile("cp.async.bulk.shared::cluster.global.mbarrier::complete_tx::bytes.L2::cache_hint [%0], [%1], %2, [%3], %4;"
               :: "r"(dst), "l"(src), "r"(bytes), "r"(bar), "l"(pl) : "memory");
}
__device__ __forceinline__ void bulk_ld_mc(uint32_t dst, const void* src, uint32_t bytes, uint32_t bar, uint64_t pl) {
  asm volatile("cp.async.bulk.shared::cluster.global.mbarrier::complete_tx::bytes.multicast::cluster.L2::cache_hint [%0], [%1], %2, [%3], %4, %5;"
               :: "r"(dst), "l"(src), "r"(bytes), "r"(bar), "h"((uint16_t)3), "l"(pl) : "memory");
}
__device__ __forceinline__ void tma_st3(const CUtensorMap* m, uint32_t src, int c0, int c1, int c2) {
  asm volatile("cp.async.bulk.tensor.3d.global.shared::cta.bulk_group.L2::cache_hint [%0, {%2, %3, %4}], [%1], %5;"
               :: "l"(m), "r"(src), "r"(c0), "r"(c1), "r"(c2), "l"(pol(HINTS & 1024)) : "memory");
}
__device__ __forceinline__ void tma_ld2_mc(uint32_t dst, const CUtensorMap* m, uint32_t bar, int c0, int c1, uint64_t pl = POL_NORMAL) {
  asm volatile("cp.async.bulk.tensor.2d.shared::cluster.global.mbarrier::complete_tx::bytes.multicast::cluster.L2::cache_hint [%0], [%1, {%3, %4}], [%2], %5, %6;"
               :: "r"(dst), "l"(m), "r"(bar), "r"(c0), "r"(c1), "h"((uint16_t)3), "l"(pl) : "memory");
}
__device__ __forceinline__ void tma_ld5_mc(uint32_t dst, const CUtensorMap* m, uint32_t bar, int c0, int c4, uint64_t pl = POL_NORMAL) {
  asm volatile("cp.async.bulk.tensor.5d.shared::cluster.global.mbarrier::complete_tx::bytes.multicast::cluster.L2::cache_hint [%0], [%1, {%3, %7, %7, %7, %4}], [%2], %5, %6;"
               :: "r"(dst), "l"(m), "r"(bar), "r"(c0), "r"(c4), "h"((uint16_t)3), "l"(pl), "r"(0) : "memory");
}
__device__ __forceinline__ void tma_ld5(uint32_t dst, const CUtensorMap* m, uint32_t bar, int c0, int c4, uint64_t pl = POL_NORMAL) {
  asm volatile("cp.async.bulk.tensor.5d.shared::cluster.global.mbarrier::complete_tx::bytes.L2::cache_hint [%0], [%1, {%3, %6, %6, %6, %4}], [%2], %5;"
               :: "r"(dst), "l"(m), "r"(bar), "r"(c0), "r"(c4), "l"(pl), "r"(0) : "memory");
}
__device__ __forceinline__ void tma_st2(const CUtensorMap* m, uint32_t src, int c0, int c1) {
  asm volatile("cp.async.bulk.tensor.2d.global.shared::cta.bulk_group [%0, {%2, %3}], [%1];"
               :: "l"(m), "r"(src), "r"(c0), "r"(c1) : "memory");
}
__device__ __forceinline__ void tma_red2(const CUtensorMap* m, uint32_t src, int c0, int c1) {
  asm volatile("cp.reduce.async.bulk.tensor.2d.global.shared::cta.add.bulk_group [%0, {%2, %3}], [%1];"
               :: "l"(m), "r"(src), "r"(c0), "r"(c1) : "memory");
}
__device__ __forceinline__ void bulk_commit() { asm volatile("cp.async.bulk.commit_group;" ::: "memory"); }
__device__ __forceinline__ void bulk_wait_read() { asm volatile("cp.async.bulk.wait_group.read 0;" ::: "memory"); }
__device__ __forceinline__ void bulk_wait_all() { asm volatile("cp.async.bulk.wait_group 0;" ::: "memory"); }
__device__ __forceinline__ void prefetch_map(const CUtensorMap* m) { asm volatile("prefetch.tensormap [%0];" :: "l"(m) : "memory"); }
__device__ __forceinline__ void wg_fence() { asm volatile("wgmma.fence.sync.aligned;" ::: "memory"); }
__device__ __forceinline__ void wg_commit() { asm volatile("wgmma.commit_group.sync.aligned;" ::: "memory"); }
template <int N> __device__ __forceinline__ void wg_wait() { asm volatile("wgmma.wait_group.sync.aligned %0;" :: "n"(N) : "memory"); }
template <int N> __device__ __forceinline__ void reg_fence(float (&d)[N]) {
#pragma unroll
  for (int i = 0; i < N; i++) asm volatile("" : "+f"(d[i]) :: "memory");
}
template <int N> __device__ __forceinline__ void reg_fence(uint32_t (&d)[N]) {
#pragma unroll
  for (int i = 0; i < N; i++) asm volatile("" : "+r"(d[i]) :: "memory");
}
__device__ __forceinline__ uint32_t fresh_tid() { uint32_t t; asm volatile("mov.u32 %0, %%tid.x;" : "=r"(t)); return t; }
__device__ __forceinline__ uint32_t lane_base16() {
  const uint32_t t = fresh_tid(), lane = t & 31, wq = (t >> 5) & 3;
  return (16 * wq + (lane & 7) + 8 * ((lane >> 3) & 1)) * 128 + (((lane >> 4) ^ (lane & 7)) << 4);
}
__device__ __forceinline__ void cluster_arrive() { asm volatile("barrier.cluster.arrive.relaxed.aligned;" ::: "memory"); }
__device__ __forceinline__ void cluster_wait() { asm volatile("barrier.cluster.wait.acquire.aligned;" ::: "memory"); }
__device__ __forceinline__ void named_sync(int id, int n) { asm volatile("bar.sync %0, %1;" :: "r"(id), "r"(n) : "memory"); }
__device__ __forceinline__ void named_arrive(int id, int n) { asm volatile("bar.arrive %0, %1;" :: "r"(id), "r"(n) : "memory"); }
__device__ __forceinline__ uint32_t pack_bf16(float lo, float hi) {
  uint32_t r; asm("cvt.rn.bf16x2.f32 %0, %1, %2;" : "=r"(r) : "f"(hi), "f"(lo)); return r;
}
__device__ __forceinline__ float ex2(float x) { float y; asm("ex2.approx.ftz.f32 %0, %1;" : "=f"(y) : "f"(x)); return y; }
__device__ __forceinline__ void stsm4(uint32_t addr, uint32_t a, uint32_t b, uint32_t c, uint32_t d) {
  asm volatile("stmatrix.sync.aligned.m8n8.x4.shared.b16 [%0], {%1, %2, %3, %4};" :: "r"(addr), "r"(a), "r"(b), "r"(c), "r"(d) : "memory");
}
__device__ __forceinline__ uint64_t mk_desc(uint32_t addr, uint32_t lbo, uint32_t sbo) {
  return (uint64_t)(((addr & 0x3FFFF) >> 4) | ((lbo >> 4) << 16)) | ((uint64_t)((sbo >> 4) | (1u << 30)) << 32);
}
__device__ __forceinline__ uint64_t desc_k(uint32_t addr)  { return mk_desc(addr, 16, 1024); }
__device__ __forceinline__ uint64_t desc_mn(uint32_t addr) { return mk_desc(addr, 8192, 1024); }
__device__ __forceinline__ uint64_t desc_64(uint32_t addr) { return (uint64_t)(((addr & 0x3FFFF) >> 4) | ((4096u >> 4) << 16)) | ((uint64_t)((512u >> 4) | (2u << 30)) << 32); }
__device__ __forceinline__ uint64_t desc_add(uint64_t d, uint32_t bytes) { return d + (bytes >> 4); }

__device__ __forceinline__ void wgmma_ss_n256_tb(float (&d)[128], uint64_t da, uint64_t db, int sd) {
  asm volatile("{\n.reg .pred p;\nsetp.ne.b32 p, %130, 0;\n"
    "wgmma.mma_async.sync.aligned.m64n256k16.f32.bf16.bf16 "
    "{%0, %1, %2, %3, %4, %5, %6, %7, %8, %9, %10, %11, %12, %13, %14, %15, "
    "%16, %17, %18, %19, %20, %21, %22, %23, %24, %25, %26, %27, %28, %29, %30, %31, "
    "%32, %33, %34, %35, %36, %37, %38, %39, %40, %41, %42, %43, %44, %45, %46, %47, "
    "%48, %49, %50, %51, %52, %53, %54, %55, %56, %57, %58, %59, %60, %61, %62, %63, "
    "%64, %65, %66, %67, %68, %69, %70, %71, %72, %73, %74, %75, %76, %77, %78, %79, "
    "%80, %81, %82, %83, %84, %85, %86, %87, %88, %89, %90, %91, %92, %93, %94, %95, "
    "%96, %97, %98, %99, %100, %101, %102, %103, %104, %105, %106, %107, %108, %109, %110, %111, "
    "%112, %113, %114, %115, %116, %117, %118, %119, %120, %121, %122, %123, %124, %125, %126, %127}, "
    "%128, %129, p, 1, 1, 0, 1;\n}"
    : "+f"(d[0]), "+f"(d[1]), "+f"(d[2]), "+f"(d[3]), "+f"(d[4]), "+f"(d[5]), "+f"(d[6]), "+f"(d[7]),
      "+f"(d[8]), "+f"(d[9]), "+f"(d[10]), "+f"(d[11]), "+f"(d[12]), "+f"(d[13]), "+f"(d[14]), "+f"(d[15]),
      "+f"(d[16]), "+f"(d[17]), "+f"(d[18]), "+f"(d[19]), "+f"(d[20]), "+f"(d[21]), "+f"(d[22]), "+f"(d[23]),
      "+f"(d[24]), "+f"(d[25]), "+f"(d[26]), "+f"(d[27]), "+f"(d[28]), "+f"(d[29]), "+f"(d[30]), "+f"(d[31]),
      "+f"(d[32]), "+f"(d[33]), "+f"(d[34]), "+f"(d[35]), "+f"(d[36]), "+f"(d[37]), "+f"(d[38]), "+f"(d[39]),
      "+f"(d[40]), "+f"(d[41]), "+f"(d[42]), "+f"(d[43]), "+f"(d[44]), "+f"(d[45]), "+f"(d[46]), "+f"(d[47]),
      "+f"(d[48]), "+f"(d[49]), "+f"(d[50]), "+f"(d[51]), "+f"(d[52]), "+f"(d[53]), "+f"(d[54]), "+f"(d[55]),
      "+f"(d[56]), "+f"(d[57]), "+f"(d[58]), "+f"(d[59]), "+f"(d[60]), "+f"(d[61]), "+f"(d[62]), "+f"(d[63]),
      "+f"(d[64]), "+f"(d[65]), "+f"(d[66]), "+f"(d[67]), "+f"(d[68]), "+f"(d[69]), "+f"(d[70]), "+f"(d[71]),
      "+f"(d[72]), "+f"(d[73]), "+f"(d[74]), "+f"(d[75]), "+f"(d[76]), "+f"(d[77]), "+f"(d[78]), "+f"(d[79]),
      "+f"(d[80]), "+f"(d[81]), "+f"(d[82]), "+f"(d[83]), "+f"(d[84]), "+f"(d[85]), "+f"(d[86]), "+f"(d[87]),
      "+f"(d[88]), "+f"(d[89]), "+f"(d[90]), "+f"(d[91]), "+f"(d[92]), "+f"(d[93]), "+f"(d[94]), "+f"(d[95]),
      "+f"(d[96]), "+f"(d[97]), "+f"(d[98]), "+f"(d[99]), "+f"(d[100]), "+f"(d[101]), "+f"(d[102]), "+f"(d[103]),
      "+f"(d[104]), "+f"(d[105]), "+f"(d[106]), "+f"(d[107]), "+f"(d[108]), "+f"(d[109]), "+f"(d[110]), "+f"(d[111]),
      "+f"(d[112]), "+f"(d[113]), "+f"(d[114]), "+f"(d[115]), "+f"(d[116]), "+f"(d[117]), "+f"(d[118]), "+f"(d[119]),
      "+f"(d[120]), "+f"(d[121]), "+f"(d[122]), "+f"(d[123]), "+f"(d[124]), "+f"(d[125]), "+f"(d[126]), "+f"(d[127])
    : "l"(da), "l"(db), "r"(sd));
}
__device__ __forceinline__ void wgmma_ss_n64(float (&d)[32], uint64_t da, uint64_t db, int sd) {
  asm volatile("{\n.reg .pred p;\nsetp.ne.b32 p, %34, 0;\n"
    "wgmma.mma_async.sync.aligned.m64n64k16.f32.bf16.bf16 "
    "{%0, %1, %2, %3, %4, %5, %6, %7, %8, %9, %10, %11, %12, %13, %14, %15, "
    "%16, %17, %18, %19, %20, %21, %22, %23, %24, %25, %26, %27, %28, %29, %30, %31}, "
    "%32, %33, p, 1, 1, 0, 0;\n}"
    : "+f"(d[0]), "+f"(d[1]), "+f"(d[2]), "+f"(d[3]), "+f"(d[4]), "+f"(d[5]), "+f"(d[6]), "+f"(d[7]),
      "+f"(d[8]), "+f"(d[9]), "+f"(d[10]), "+f"(d[11]), "+f"(d[12]), "+f"(d[13]), "+f"(d[14]), "+f"(d[15]),
      "+f"(d[16]), "+f"(d[17]), "+f"(d[18]), "+f"(d[19]), "+f"(d[20]), "+f"(d[21]), "+f"(d[22]), "+f"(d[23]),
      "+f"(d[24]), "+f"(d[25]), "+f"(d[26]), "+f"(d[27]), "+f"(d[28]), "+f"(d[29]), "+f"(d[30]), "+f"(d[31])
    : "l"(da), "l"(db), "r"(sd));
}
__device__ __forceinline__ void wgmma_rs_n256_tb(float (&d)[128], uint32_t a0, uint32_t a1, uint32_t a2, uint32_t a3, uint64_t db, int sd) {
  asm volatile("{\n.reg .pred p;\nsetp.ne.b32 p, %133, 0;\n"
    "wgmma.mma_async.sync.aligned.m64n256k16.f32.bf16.bf16 "
    "{%0, %1, %2, %3, %4, %5, %6, %7, %8, %9, %10, %11, %12, %13, %14, %15, "
    "%16, %17, %18, %19, %20, %21, %22, %23, %24, %25, %26, %27, %28, %29, %30, %31, "
    "%32, %33, %34, %35, %36, %37, %38, %39, %40, %41, %42, %43, %44, %45, %46, %47, "
    "%48, %49, %50, %51, %52, %53, %54, %55, %56, %57, %58, %59, %60, %61, %62, %63, "
    "%64, %65, %66, %67, %68, %69, %70, %71, %72, %73, %74, %75, %76, %77, %78, %79, "
    "%80, %81, %82, %83, %84, %85, %86, %87, %88, %89, %90, %91, %92, %93, %94, %95, "
    "%96, %97, %98, %99, %100, %101, %102, %103, %104, %105, %106, %107, %108, %109, %110, %111, "
    "%112, %113, %114, %115, %116, %117, %118, %119, %120, %121, %122, %123, %124, %125, %126, %127}, "
    "{%128, %129, %130, %131}, %132, p, 1, 1, 1;\n}"
    : "+f"(d[0]), "+f"(d[1]), "+f"(d[2]), "+f"(d[3]), "+f"(d[4]), "+f"(d[5]), "+f"(d[6]), "+f"(d[7]),
      "+f"(d[8]), "+f"(d[9]), "+f"(d[10]), "+f"(d[11]), "+f"(d[12]), "+f"(d[13]), "+f"(d[14]), "+f"(d[15]),
      "+f"(d[16]), "+f"(d[17]), "+f"(d[18]), "+f"(d[19]), "+f"(d[20]), "+f"(d[21]), "+f"(d[22]), "+f"(d[23]),
      "+f"(d[24]), "+f"(d[25]), "+f"(d[26]), "+f"(d[27]), "+f"(d[28]), "+f"(d[29]), "+f"(d[30]), "+f"(d[31]),
      "+f"(d[32]), "+f"(d[33]), "+f"(d[34]), "+f"(d[35]), "+f"(d[36]), "+f"(d[37]), "+f"(d[38]), "+f"(d[39]),
      "+f"(d[40]), "+f"(d[41]), "+f"(d[42]), "+f"(d[43]), "+f"(d[44]), "+f"(d[45]), "+f"(d[46]), "+f"(d[47]),
      "+f"(d[48]), "+f"(d[49]), "+f"(d[50]), "+f"(d[51]), "+f"(d[52]), "+f"(d[53]), "+f"(d[54]), "+f"(d[55]),
      "+f"(d[56]), "+f"(d[57]), "+f"(d[58]), "+f"(d[59]), "+f"(d[60]), "+f"(d[61]), "+f"(d[62]), "+f"(d[63]),
      "+f"(d[64]), "+f"(d[65]), "+f"(d[66]), "+f"(d[67]), "+f"(d[68]), "+f"(d[69]), "+f"(d[70]), "+f"(d[71]),
      "+f"(d[72]), "+f"(d[73]), "+f"(d[74]), "+f"(d[75]), "+f"(d[76]), "+f"(d[77]), "+f"(d[78]), "+f"(d[79]),
      "+f"(d[80]), "+f"(d[81]), "+f"(d[82]), "+f"(d[83]), "+f"(d[84]), "+f"(d[85]), "+f"(d[86]), "+f"(d[87]),
      "+f"(d[88]), "+f"(d[89]), "+f"(d[90]), "+f"(d[91]), "+f"(d[92]), "+f"(d[93]), "+f"(d[94]), "+f"(d[95]),
      "+f"(d[96]), "+f"(d[97]), "+f"(d[98]), "+f"(d[99]), "+f"(d[100]), "+f"(d[101]), "+f"(d[102]), "+f"(d[103]),
      "+f"(d[104]), "+f"(d[105]), "+f"(d[106]), "+f"(d[107]), "+f"(d[108]), "+f"(d[109]), "+f"(d[110]), "+f"(d[111]),
      "+f"(d[112]), "+f"(d[113]), "+f"(d[114]), "+f"(d[115]), "+f"(d[116]), "+f"(d[117]), "+f"(d[118]), "+f"(d[119]),
      "+f"(d[120]), "+f"(d[121]), "+f"(d[122]), "+f"(d[123]), "+f"(d[124]), "+f"(d[125]), "+f"(d[126]), "+f"(d[127])
    : "r"(a0), "r"(a1), "r"(a2), "r"(a3), "l"(db), "r"(sd));
}
__device__ __forceinline__ void wgmma_rs_n64_tb(float (&d)[32], uint32_t a0, uint32_t a1, uint32_t a2, uint32_t a3, uint64_t db, int sd) {
  asm volatile("{\n.reg .pred p;\nsetp.ne.b32 p, %37, 0;\n"
    "wgmma.mma_async.sync.aligned.m64n64k16.f32.bf16.bf16 "
    "{%0, %1, %2, %3, %4, %5, %6, %7, %8, %9, %10, %11, %12, %13, %14, %15, "
    "%16, %17, %18, %19, %20, %21, %22, %23, %24, %25, %26, %27, %28, %29, %30, %31}, "
    "{%32, %33, %34, %35}, %36, p, 1, 1, 1;\n}"
    : "+f"(d[0]), "+f"(d[1]), "+f"(d[2]), "+f"(d[3]), "+f"(d[4]), "+f"(d[5]), "+f"(d[6]), "+f"(d[7]),
      "+f"(d[8]), "+f"(d[9]), "+f"(d[10]), "+f"(d[11]), "+f"(d[12]), "+f"(d[13]), "+f"(d[14]), "+f"(d[15]),
      "+f"(d[16]), "+f"(d[17]), "+f"(d[18]), "+f"(d[19]), "+f"(d[20]), "+f"(d[21]), "+f"(d[22]), "+f"(d[23]),
      "+f"(d[24]), "+f"(d[25]), "+f"(d[26]), "+f"(d[27]), "+f"(d[28]), "+f"(d[29]), "+f"(d[30]), "+f"(d[31])
    : "r"(a0), "r"(a1), "r"(a2), "r"(a3), "l"(db), "r"(sd));
}
__device__ __forceinline__ void wgmma_rs_n32(float (&d)[16], uint32_t a0, uint32_t a1, uint32_t a2, uint32_t a3, uint64_t db, int sd) {
  asm volatile("{\n.reg .pred p;\nsetp.ne.b32 p, %21, 0;\n"
    "wgmma.mma_async.sync.aligned.m64n32k16.f32.bf16.bf16 "
    "{%0, %1, %2, %3, %4, %5, %6, %7, %8, %9, %10, %11, %12, %13, %14, %15}, "
    "{%16, %17, %18, %19}, %20, p, 1, 1, 0;\n}"
    : "+f"(d[0]), "+f"(d[1]), "+f"(d[2]), "+f"(d[3]), "+f"(d[4]), "+f"(d[5]), "+f"(d[6]), "+f"(d[7]),
      "+f"(d[8]), "+f"(d[9]), "+f"(d[10]), "+f"(d[11]), "+f"(d[12]), "+f"(d[13]), "+f"(d[14]), "+f"(d[15])
    : "r"(a0), "r"(a1), "r"(a2), "r"(a3), "l"(db), "r"(sd));
}
__device__ __forceinline__ void wgmma_rs_n64(float (&d)[32], uint32_t a0, uint32_t a1, uint32_t a2, uint32_t a3, uint64_t db, int sd) {
  asm volatile("{\n.reg .pred p;\nsetp.ne.b32 p, %37, 0;\n"
    "wgmma.mma_async.sync.aligned.m64n64k16.f32.bf16.bf16 "
    "{%0, %1, %2, %3, %4, %5, %6, %7, %8, %9, %10, %11, %12, %13, %14, %15, "
    "%16, %17, %18, %19, %20, %21, %22, %23, %24, %25, %26, %27, %28, %29, %30, %31}, "
    "{%32, %33, %34, %35}, %36, p, 1, 1, 0;\n}"
    : "+f"(d[0]), "+f"(d[1]), "+f"(d[2]), "+f"(d[3]), "+f"(d[4]), "+f"(d[5]), "+f"(d[6]), "+f"(d[7]),
      "+f"(d[8]), "+f"(d[9]), "+f"(d[10]), "+f"(d[11]), "+f"(d[12]), "+f"(d[13]), "+f"(d[14]), "+f"(d[15]),
      "+f"(d[16]), "+f"(d[17]), "+f"(d[18]), "+f"(d[19]), "+f"(d[20]), "+f"(d[21]), "+f"(d[22]), "+f"(d[23]),
      "+f"(d[24]), "+f"(d[25]), "+f"(d[26]), "+f"(d[27]), "+f"(d[28]), "+f"(d[29]), "+f"(d[30]), "+f"(d[31])
    : "r"(a0), "r"(a1), "r"(a2), "r"(a3), "l"(db), "r"(sd));
}

__device__ __forceinline__ uint4 lds16(uint32_t a) {
  uint4 v; asm volatile("ld.shared.v4.u32 {%0, %1, %2, %3}, [%4];" : "=r"(v.x), "=r"(v.y), "=r"(v.z), "=r"(v.w) : "r"(a) : "memory"); return v;
}
__device__ __forceinline__ void sts16(uint32_t a, uint32_t x, uint32_t y, uint32_t z, uint32_t w) {
  asm volatile("st.shared.v4.u32 [%0], {%1, %2, %3, %4};" :: "r"(a), "r"(x), "r"(y), "r"(z), "r"(w) : "memory");
}
__device__ __forceinline__ uint32_t lds4(uint32_t a) { uint32_t v; asm volatile("ld.shared.u32 %0, [%1];" : "=r"(v) : "r"(a) : "memory"); return v; }
__device__ __forceinline__ uint32_t lds4v(uint32_t a) { uint32_t v; asm volatile("ld.volatile.shared.u32 %0, [%1];" : "=r"(v) : "r"(a) : "memory"); return v; }
__device__ __forceinline__ uint32_t bmul(uint32_t a, uint32_t b) { uint32_t r; asm("mul.rn.bf16x2 %0, %1, %2;" : "=r"(r) : "r"(a), "r"(b)); return r; }
__device__ __forceinline__ uint32_t badd(uint32_t a, uint32_t b) { uint32_t r; asm("add.rn.bf16x2 %0, %1, %2;" : "=r"(r) : "r"(a), "r"(b)); return r; }

__device__ __forceinline__ void ldsm4(uint32_t (&r)[4], uint32_t a) {
  asm volatile("ldmatrix.sync.aligned.m8n8.x4.shared.b16 {%0, %1, %2, %3}, [%4];" : "=r"(r[0]), "=r"(r[1]), "=r"(r[2]), "=r"(r[3]) : "r"(a) : "memory");
}
__device__ __forceinline__ uint32_t transpose8(uint32_t a) { uint32_t d; asm volatile("movmatrix.sync.aligned.m8n8.trans.b16 %0, %1;" : "=r"(d) : "r"(a)); return d; }

__device__ __forceinline__ void mma16816(float (&d)[4], const uint32_t (&a)[4], uint32_t b0, uint32_t b1) {
  asm volatile("mma.sync.aligned.m16n8k16.row.col.f32.bf16.bf16.f32 {%0, %1, %2, %3}, {%4, %5, %6, %7}, {%8, %9}, {%0, %1, %2, %3};"
               : "+f"(d[0]), "+f"(d[1]), "+f"(d[2]), "+f"(d[3]) : "r"(a[0]), "r"(a[1]), "r"(a[2]), "r"(a[3]), "r"(b0), "r"(b1));
}

#define EXP_SIDE 0
#define SIDE_AHEAD 3
#define ZERO_RD 4
#define CTX_SPLIT 8
#define CONV_EARLY 8
#define CONV_FENCE 12
#define CTX_LD 16
#define PEEK_JJ 7
#define PF_CTX 2
#define KV_ORDER 3
#define QFIRST 0
#define UNICAST 2
#define PF_MAPS 3
#define SINGLE0 2
#define CONV_ARRIVE 13
#define ARRIVE_KK 12
#define SIDE_DELAY_NS 4000
#define KVH(h) (h)
#define HEAD_MAP 2
#define EARLY_LD 1
constexpr int RED_BAR = 6;
constexpr int CV_BAR = 5;
constexpr int PP_BAR = 3;
template <int V> struct Int { static constexpr int value = V; };
struct Ring {
  uint32_t slot, phase;
  __device__ __forceinline__ void next() { if (++slot == NSLOT) { slot = 0; phase ^= 1; } }
};
__device__ __forceinline__ uint32_t bar_addr(uint32_t sb, uint32_t i) { return sb + BARS + 8 * i; }

__device__ __forceinline__ int q_tile(int h, int j, int which) { return ((h < 8) == (which == 0)) ? 15 - j : j; }

constexpr int T_QB = QFIRST ? 0 : 4, IT_KV = QFIRST ? 7 : 0, IT_QB = QFIRST ? 0 : 64;
constexpr int KV_ISV  = KV_ORDER == 0 ? 0xC : KV_ORDER == 1 ? 0xA : KV_ORDER == 2 ? 0x6 : KV_ORDER == 3 ? 0xA : 0xC;
constexpr int KV_PART = KV_ORDER == 0 ? 0xA : KV_ORDER == 1 ? 0xC : KV_ORDER == 2 ? 0xC : KV_ORDER == 3 ? 0x3 : KV_ORDER == 4 ? 0x5 : 0x9;
constexpr int LAST_PART = KV_PART >> 3;
constexpr int T_FIRST = (((KV_PART >> 2) & 1) != LAST_PART ? 3 : 2) + QFIRST;
constexpr int T_LAST = 4 + QFIRST;
__device__ __forceinline__ int p1_isv(int n) { return (KV_ISV >> n) & 1; }
__device__ __forceinline__ int att_head(int h, int which) { return (h & 7) + 8 * which; }
__device__ __forceinline__ int p1_head(int h, int n) { return (h & 7) + 8 * ((KV_PART >> n) & 1); }
__device__ __forceinline__ int p1_rows(int h, int j, int n) { return q_tile(h, j, 0); }
#define KV_FLAG(h) ((h) & 7)
#define KV_COUNT 32
#define F_PART1 (2 * own - 1)

__device__ __forceinline__ void load_tile4(uint32_t dst, const CUtensorMap* m, uint32_t full, int row, int blk0, int rank, bool shared, uint64_t pl = POL_NORMAL) {
  if (shared) {
    tma_ld3_mc(dst + rank * 16384, m, full, 0, row, blk0 + 2 * rank, pl);
  } else {
    tma_ld3(dst, m, full, 0, row, blk0, pl);
    tma_ld3(dst + 16384, m, full, 0, row, blk0 + 2, pl);
  }
}
__device__ __forceinline__ void producer_main(const Params& p, uint32_t sb, int h, int j) {
  const int rank = j & 1;
  Ring r{EARLY_LD, 0};
  auto wait_slot = [&]() { mbar_wait(bar_addr(sb, B_EMPTY + r.slot), r.phase ^ 1); };
  auto load_a = [&](int it, uint32_t dst, uint32_t full) {
    const unsigned u = it - IT_KV;
    if (u < 64) tma_ld2(dst, &p.ckv, full, (u & 15) * 64, p1_rows(h, j, u >> 4) * 128, pol((HINTS & 2) && u >= 48));
    else tma_ld2(dst, &p.x, full, (it < 71 ? it - IT_QB : it - 71) * 64, q_tile(h, j, it < 71) * 128, pol((HINTS & 64) && it >= 71));
  };
  uint32_t prev = 0;
#pragma unroll 1
  for (int it = EARLY_LD; it < P1_STEPS; it++) {
    wait_slot();
    if (it > EARLY_LD && it <= P1_XS) load_a(it - 1, sb + QREG + ((it - 1) & 3) * 16384, prev);
    const uint32_t full = bar_addr(sb, B_FULL + r.slot), dst = sb + r.slot * SLOT;
    mbar_expect_tx(full, it < P1_XS ? 49152 : 32768);
    const unsigned u = it - IT_KV;
    if (u < 64) load_tile4(dst, p1_isv(u >> 4) ? &p.wuv : &p.wuk, full, (u & 15) * 64, p1_head(h, u >> 4) * 4, rank, !(UNICAST & 2), pol(HINTS & 1));
    else load_tile4(dst, &p.wq, full, (it < 71 ? it - IT_QB : it - 71) * 64, att_head(h, it < 71) * 4, rank, !(UNICAST & 2), pol((HINTS & 4) && it >= 71));
    prev = full;
    r.next();
    if (it == P1_XS) {
      wait_slot();
      const uint32_t f2 = bar_addr(sb, B_FULL + r.slot);
      mbar_expect_tx(f2, 32768);
      load_a(P1_XS, sb + r.slot * SLOT, f2);
      load_a(P1_XS + 1, sb + r.slot * SLOT + 16384, f2);
      r.next();
    }
  }
  const int qa = q_tile(h, j, 0), na = 2 * qa + 2, own = 2 * (qa & ~1) + 2;
#pragma unroll 1
  for (int f = 0; f < 68; f++) {
    const bool isK = (f == 0) || ((f & 1) && f < 67);
    const int i = isK ? (f + 1) >> 1 : (f - 1) >> 1, which = i >= na;
    if (f == 0 || f == F_PART1) mbar_wait(bar_addr(sb, B_KVOK + (f & 1)), 0);
    wait_slot();
    const uint32_t full = bar_addr(sb, B_FULL + r.slot);
    mbar_expect_tx(full, 32768);
    const uint32_t src = (uint32_t)(((isK ? 0 : NH) + KVH(att_head(h, which))) * 32 + (which ? 33 - i : i)) * 32768;
    const uint64_t pl = pol(which ? (HINTS & 32) : (HINTS & 8));
    if (!(UNICAST & 1) && (i & ~1) != own) bulk_ld_mc(sb + r.slot * SLOT + rank * 16384, at<uint8_t>(g_kv, src + rank * 16384), 16384, full, pl);
    else bulk_ld_p(sb + r.slot * SLOT, at<uint8_t>(g_kv, src), 32768, full, pl);
    r.next();
  }
#pragma unroll 1
  for (int f = 0; f < 14; f++) {
    const int ch = f < 12 ? 2 * (f >> 2) + (f & 1) : 6, par = f < 12 ? (f >> 1) & 1 : f & 1;
    wait_slot();
    const uint32_t full = bar_addr(sb, B_FULL + r.slot);
    mbar_expect_tx(full, 32768);
    if (UNICAST & 4) {
      tma_ld5(sb + r.slot * SLOT, &p.wo, full, ch * 64, (par ? att_head(h ^ 8, 0) : att_head(h, 1)) * 8, pol(HINTS & 16));
      tma_ld5(sb + r.slot * SLOT + 16384, &p.wo, full, ch * 64, (par ? att_head(h ^ 8, 0) : att_head(h, 1)) * 8 + 4, pol(HINTS & 16));
    } else {
      tma_ld5_mc(sb + r.slot * SLOT + rank * 16384, &p.wo, full, ch * 64, (par ? att_head(h ^ 8, 0) : att_head(h, 1)) * 8 + rank * 4, pol(HINTS & 16));
    }
    r.next();
  }
}

__device__ __forceinline__ void helper_main(const Params& p, uint32_t sb, int h, int j, int w) {
  const unsigned epoch = load_epoch();
  const int cta = h * 8 + j, qb = q_tile(h, j, 1);
  const uint32_t qreg = sb + QREG + w * 32768, qfull = bar_addr(sb, B_QFULL + w);
  auto acquire = [&]() {
    flag_wait(flag_at(g_flags.kv_ready, KV_FLAG(h) * 2 + w), KV_COUNT, epoch);
    fence_async_all();
    mbar_arrive(bar_addr(sb, B_KVOK + w));
  };
  if (QFIRST) mbar_wait(bar_addr(sb, B_ST_Q + w), 0);
  mbar_wait(bar_addr(sb, B_ST_KV + w), 0);
  flag_signal(flag_at(g_flags.kv_ready, KV_FLAG(h) * 2 + (LAST_PART ^ 1)));
  if (w != LAST_PART) acquire();
  mbar_wait(bar_addr(sb, B_ST_KV + 2 + w), 0);
  flag_signal(flag_at(g_flags.kv_ready, KV_FLAG(h) * 2 + LAST_PART));
  const bool late = false;
  if (w == LAST_PART && !late) acquire();
  if (!QFIRST) { mbar_wait(bar_addr(sb, B_ST_Q + w), 0); asm volatile("fence.release.gpu;" ::: "memory"); }
  fence_async_all();
  mbar_wait(bar_addr(sb, B_QFREE + w), 0);
  mbar_expect_tx(qfull, 32768);
  bulk_ld(qreg, at<uint8_t>(g_qc, (cta * 2 + w) * 32768), 32768, qfull);
  if (w == LAST_PART && late) acquire();
  auto publish = [&]() { mbar_wait(bar_addr(sb, B_ST_CTX + w), 0); flag_signal(flag_at(g_flags.ctx_ready, cta * 2 + w)); };
  if (qb >= 8) publish();
  flag_wait(flag_at(g_flags.ctx_ready, (cta ^ 64) * 2 + (w ^ 1)), 1, epoch);
  mbar_arrive(bar_addr(sb, B_CTXOK + w));
  if (qb < 8) publish();
  flag_wait(flag_at(g_flags.zero_ready, qb), 8, epoch);
  fence_async_all();
#pragma unroll 1
  for (int ch = 0; ch < 7; ch++) {
    mbar_wait(bar_addr(sb, B_S2_FULL + w * 4 + (ch & 3)), ch >> 2);
    tma_red2(&p.o, qreg + (ch & 3) * 8192, DA + ch * 64, qb * 128 + (w ^ 1) * 64);
    bulk_commit();
    if (ch < 3) { bulk_wait_read(); mbar_arrive(bar_addr(sb, B_S2_EMPTY + w * 4 + ch)); }
  }
  bulk_wait_read();
  GT(48 + w);
}

__device__ __forceinline__ void store_block(uint32_t base, uint32_t lanebase, const uint32_t (&pk)[16]) {
#pragma unroll
  for (int J = 0; J < 8; J += 2) stsm4(base + (lanebase ^ (J << 4)), pk[2 * J], pk[2 * J + 1], pk[2 * J + 2], pk[2 * J + 3]);
}
__device__ __forceinline__ void pack_chunks(uint32_t (&pk)[64], const float (&acc)[128]) {
#pragma unroll
  for (int i = 0; i < 64; i++) { const int e = 16 * (i >> 3) + 4 * (i & 3) + 2 * ((i >> 2) & 1); pk[i] = pack_bf16(acc[e], acc[e + 1]); }
}
__device__ __forceinline__ uint32_t chunk_off() { const uint32_t t = fresh_tid(); return (t & 96) * 32 + (t & 28) * 16 + (((t ^ (t >> 3)) & 3) << 4); }
__device__ __forceinline__ void warp_arrive(uint32_t bar, int lane) { __syncwarp(); if (lane == 0) mbar_arrive(bar); }

__device__ __forceinline__ void consumer_main(const Params& p, uint32_t sb, int h, int j, int w, int wq) {
  const int lane = threadIdx.x & 31;
  const int rank = j & 1;

  auto turn_begin = [&]() { named_sync(PP_BAR + w, 256); };
  auto turn_end = [&]() { named_arrive(PP_BAR + (w ^ 1), 256); };
  Ring r{0, 0};
  auto take = [&](uint32_t ready = 0) { const uint32_t sl = r.slot; mbar_wait_unless(ready, bar_addr(sb, B_FULL + sl), r.phase); r.next(); return sl; };
  uint32_t rdy0 = 0, rdy1 = 0;
  auto peek2 = [&]() { Ring q = r; rdy0 = mbar_test(bar_addr(sb, B_FULL + q.slot), q.phase); q.next(); rdy1 = mbar_test(bar_addr(sb, B_FULL + q.slot), q.phase); };
  auto give = [&](uint32_t sl) {
    if (UNICAST & 8) { if (lane == 0) mbar_arrive(bar_addr(sb, B_EMPTY + sl)); }
    else if (lane < 2) mbar_arrive_remote(bar_addr(sb, B_EMPTY + sl), rank ^ lane);
  };
  float acc[128];
#pragma unroll
  for (int i = 0; i < 128; i++) acc[i] = 0.f;
  uint32_t pk[64];
#pragma unroll
  for (int i = 0; i < 64; i++) pk[i] = 0;
  reg_fence(acc);
  reg_fence(pk);
  cluster_wait();
  TS(0);
  const uint32_t qreg = sb + QREG + w * 32768;
  {
    uint32_t xs = 0;
    uint4* row = nullptr;
    int it = 0;
#pragma unroll 1
    for (int t = 0; t < 6; t++) {
      const bool isq = t == T_QB || t == 5;
      const uint32_t abase = sb + QREG + (w ^ (t == T_QB)) * 8192;
#pragma unroll 1
      for (int u = 0, end = it + (isq ? 7 : 16); it < end; u++) {
        const bool two = !(isq && u == 1) && it >= SINGLE0, last = it == P1_XS;
        const uint32_t w0 = take(rdy0);
        TSC(1, it == 0);
        if (last) { xs = take(rdy1); rdy1 = 0; }
        const uint32_t xb = sb + xs * SLOT + w * 8192;
        const uint64_t da = desc_k(last ? xb : abase + (it & 3) * 16384), db = desc_mn(sb + w0 * SLOT);
        turn_begin();
        wg_fence();
#pragma unroll
        for (int kk = 0; kk < 4; kk++) wgmma_ss_n256_tb(acc, desc_add(da, kk * 32), desc_add(db, kk * 2048), (u | kk) != 0);
        wg_commit();
        uint32_t w1 = w0;
        if (two) {
          w1 = take(rdy1);
          const uint64_t da1 = desc_k(last ? xb + 16384 : abase + ((it + 1) & 3) * 16384), db1 = desc_mn(sb + w1 * SLOT);
          wg_fence();
#pragma unroll
          for (int kk = 0; kk < 4; kk++) wgmma_ss_n256_tb(acc, desc_add(da1, kk * 32), desc_add(db1, kk * 2048), 1);
          wg_commit();
          turn_end();
          wg_wait<1>();
          give(w0);
        } else {
          turn_end();
        }
        if (t > 0) {
          uint32_t m = isq ? 0xC0380403u >> (8 * u) : 1u << u;
          asm volatile("" : "+r"(m));
#pragma unroll
          for (int i = 0; i < 16; i++)
            if (m & (1u << (i >> 1))) row[(i >> 1) * 256 + (i & 1) * 32] = make_uint4(pk[4 * i], pk[4 * i + 1], pk[4 * i + 2], pk[4 * i + 3]);
        }
        peek2();
        wg_wait<0>();
        give(w1);
        it += 1 + two;
      }
      reg_fence(acc);
      if (t == T_QB + 1 || t == T_FIRST || t == T_LAST)
        warp_arrive(bar_addr(sb, (t == T_QB + 1 ? B_ST_Q : t == T_LAST ? B_ST_KV + 2 : B_ST_KV) + w), lane);
      pack_chunks(pk, acc);
      const int n = t - QFIRST;
      row = at<uint4>(t != T_QB ? (const void*)g_kv : (const void*)g_qc, chunk_off() +
                      (t != T_QB ? (uint32_t)((p1_isv(n) * NH + KVH(p1_head(h, n))) * 32 + p1_rows(h, j, n) * 2 + w) : (uint32_t)((h * 8 + j) * 2 + w)) * 32768);
      TS(2 + t);
    }
    give(xs);
    const uint32_t qa = qreg + chunk_off();
#pragma unroll
    for (int i = 0; i < 16; i++) sts16(qa + (i >> 1) * 4096 + (i & 1) * 512, pk[4 * i], pk[4 * i + 1], pk[4 * i + 2], pk[4 * i + 3]);
    fence_async_smem();
  }
  TS(8);

  constexpr float SC = 0.0625f * 1.4426950408889634f;
#pragma unroll 1
  for (int which = 0; which < 2; which++) {
    float s[32];
#pragma unroll
    for (int i = 0; i < 32; i++) s[i] = 0.f;
    uint32_t pa[16], pb[16];
    float m0 = 0.f, m1 = 0.f, l0 = 0.f, l1 = 0.f;
    const uint64_t dq = desc_64(qreg);
    uint64_t dk = 0, dqq = 0, dv = 0;
    auto prep_qk = [&](uint32_t kaddr) { dk = desc_64(kaddr); dqq = dq + (kaddr >> 31); asm volatile("" : "+l"(dk), "+l"(dqq)); };
    auto prep_pv = [&](uint32_t vaddr) { dv = desc_64(vaddr); asm volatile("" : "+l"(dv)); };
    auto issue_qk = [&]() {
#pragma unroll
      for (int kk = 0; kk < 16; kk++)
        wgmma_ss_n64(s, desc_add(dqq, (kk >> 1) * 4096 + (kk & 1) * 32), desc_add(dk, (kk >> 1) * 4096 + (kk & 1) * 32), kk != 0);
    };
    auto issue_pv = [&](int accumulate) {
#pragma unroll
      for (int kk = 0; kk < 4; kk++)
        wgmma_rs_n256_tb(acc, pa[4 * kk], pa[4 * kk + 1], pa[4 * kk + 2], pa[4 * kk + 3], desc_add(dv, kk * 1024), accumulate | kk);
    };
    auto mask_diag = [&]() {
      const int d = 16 * wq + (lane >> 2) - 2 * (lane & 3);
#pragma unroll
      for (int jj = 0; jj < 8; jj++) {
        if (8 * jj > d)     { s[4 * jj] = -INFINITY;     if (jj < 7) s[4 * jj + 6] = -INFINITY; }
        if (8 * jj + 1 > d) { s[4 * jj + 1] = -INFINITY; if (jj < 7) s[4 * jj + 7] = -INFINITY; }
      }
    };
    float a0, a1;
    auto softmax = [&]() -> bool {
      float x0 = fmaxf(s[0], s[1]), x1 = fmaxf(s[2], s[3]);
#pragma unroll
      for (int jj = 1; jj < 8; jj++) {
        x0 = fmaxf(x0, fmaxf(s[4 * jj], s[4 * jj + 1]));
        x1 = fmaxf(x1, fmaxf(s[4 * jj + 2], s[4 * jj + 3]));
      }
      x0 = fmaxf(x0, __shfl_xor_sync(0xffffffffu, x0, 1));
      x1 = fmaxf(x1, __shfl_xor_sync(0xffffffffu, x1, 1));
      x0 = fmaxf(x0, __shfl_xor_sync(0xffffffffu, x0, 2));
      x1 = fmaxf(x1, __shfl_xor_sync(0xffffffffu, x1, 2));
      const bool grow = __any_sync(0xffffffffu, fmaxf(x0 - m0, x1 - m1) * SC > 8.f);
      if (grow) {
        x0 = fmaxf(x0, m0); x1 = fmaxf(x1, m1);
        a0 = ex2((m0 - x0) * SC); a1 = ex2((m1 - x1) * SC);
        m0 = x0; m1 = x1;
        l0 *= a0; l1 *= a1;
      }
      const float b0 = -m0 * SC, b1 = -m1 * SC;
      float t0 = 0.f, t1 = 0.f, t2 = 0.f, t3 = 0.f;
#pragma unroll
      for (int jj = 0; jj < 8; jj++) {
        s[4 * jj]     = ex2(fmaf(s[4 * jj], SC, b0));
        s[4 * jj + 1] = ex2(fmaf(s[4 * jj + 1], SC, b0));
        s[4 * jj + 2] = ex2(fmaf(s[4 * jj + 2], SC, b1));
        s[4 * jj + 3] = ex2(fmaf(s[4 * jj + 3], SC, b1));
        t0 += s[4 * jj]; t1 += s[4 * jj + 1]; t2 += s[4 * jj + 2]; t3 += s[4 * jj + 3];
      }
      l0 += t0 + t1; l1 += t2 + t3;
      return grow;
    };
    auto softmax_fast = [&](uint32_t (&pp)[16], auto first, auto hook) -> bool {
      const float b0 = -m0 * SC, b1 = -m1 * SC;
      float t0 = 0.f, t1 = 0.f, t2 = 0.f, t3 = 0.f;
#pragma unroll
      for (int jj = 0; jj < 8; jj++) {
        const float e0 = ex2(fmaf(s[4 * jj], SC, b0)), e1 = ex2(fmaf(s[4 * jj + 1], SC, b0));
        const float e2 = ex2(fmaf(s[4 * jj + 2], SC, b1)), e3 = ex2(fmaf(s[4 * jj + 3], SC, b1));
        hook(jj, e0);
        pp[2 * jj] = pack_bf16(e0, e1); pp[2 * jj + 1] = pack_bf16(e2, e3);
        if (jj == 0) { t0 = e0; t1 = e1; t2 = e2; t3 = e3; } else { t0 += e0; t1 += e1; t2 += e2; t3 += e3; }
      }
      t0 += t1; t2 += t3;
      bool redo = __any_sync(0xffffffffu, !(t0 + t2 <= 16777216.f));
      if (decltype(first)::value) {
        uint32_t u0 = __ballot_sync(0xffffffffu, t0 >= 1.52587890625e-05f), u1 = __ballot_sync(0xffffffffu, t2 >= 1.52587890625e-05f);
        u0 |= u0 >> 1; u1 |= u1 >> 1;
        redo |= (((u0 | (u0 >> 2)) & (u1 | (u1 >> 2))) & 0x11111111u) != 0x11111111u;
      }
      if (!redo) { l0 += t0; l1 += t2; }
      return redo;
    };
    auto rescale = [&]() {
#pragma unroll
      for (int i = 0; i < 32; i++) { acc[4 * i] *= a0; acc[4 * i + 1] *= a0; acc[4 * i + 2] *= a1; acc[4 * i + 3] *= a1; }
    };
    auto to_p = [&](uint32_t (&pp)[16]) {
#pragma unroll
      for (int i = 0; i < 16; i++) pp[i] = pack_bf16(s[2 * i], s[2 * i + 1]);
    };
    auto q_free = [&]() { if (lane == 0) mbar_arrive(bar_addr(sb, B_QFREE + w)); };

    const int n = 2 * q_tile(h, j, which) + 1 + (w ^ which);
    uint32_t ks = take(rdy0);
    TS(9 + 5 * which);
    prep_qk(sb + ks * SLOT);
    turn_begin();
    TS(20 + 10 * which);
    wg_fence();
    issue_qk();
    wg_commit();
    turn_end();
    if (which == 1) give(take(rdy1));
    TS(22 + 10 * which);
    wg_wait<0>();
    TS(21 + 10 * which);
    reg_fence(s);
    give(ks);
    if (which == 0 && n == 1) q_free();
    if (which == 1 || n == 1) mask_diag();
    {
      const uint4* dst = at<uint4>(g_qc, (uint32_t)((h * 8 + j) * 2 + w) * 32768 + (fresh_tid() & 127) * 16);
      const bool redo = softmax_fast(pa, Int<1>(), [&](int jj, float e) {
        if (jj == PEEK_JJ) peek2();
        const int i = CTX_SPLIT + jj;
        if (i < 16)
          asm volatile("{\n.reg .pred p, q;\nsetp.ne.b32 q, %6, 0;\nsetp.geu.and.f32 p, %5, 0fBF800000, q;\n@p st.global.v4.u32 [%0], {%1, %2, %3, %4};\n}"
                       :: "l"(dst + i * 128), "r"(pk[4 * (i & 15)]), "r"(pk[4 * (i & 15) + 1]), "r"(pk[4 * (i & 15) + 2]), "r"(pk[4 * (i & 15) + 3]), "f"(e), "r"(which) : "memory");
      });
      if (redo) {
        m0 = -INFINITY; m1 = -INFINITY;
        softmax();
        to_p(pa);
      }
    }
    if (which == 1) warp_arrive(bar_addr(sb, B_ST_CTX + w), lane);
    TS(10 + 5 * which);
#pragma unroll 1
    for (int jj = 1; jj < n; jj++) {
      ks = take(rdy0);
      const uint32_t vs = take(rdy1);
      prep_qk(sb + ks * SLOT);
      prep_pv(sb + vs * SLOT);
      TSC(23 + 10 * which, jj == 1);
      turn_begin();
      TSC(24 + 10 * which, jj == 1);
      TSC(26 + 10 * which, jj == n - 1);
      wg_fence();
      issue_qk();
      wg_commit();
      issue_pv(jj > 1);
      wg_commit();
      turn_end();
      wg_wait<1>();
      TSC(25 + 10 * which, jj == 1);
      reg_fence(s);
      give(ks);
      if (jj == n - 1 && which == 0) { q_free(); mask_diag(); }
      if (PF_CTX && which == 1 && jj == max(n - PF_CTX, 1)) {
        const uint8_t* src = at<const uint8_t>(g_qc, (uint32_t)(((h ^ 8) * 8 + j) * 2 + (w ^ 1)) * 32768 + (fresh_tid() & 127) * 128);
        asm volatile("prefetch.global.L2 [%0];" :: "l"(src));
        asm volatile("prefetch.global.L2 [%0];" :: "l"(src + 16384));
      }
      if (softmax_fast(pb, Int<0>(), [](int, float) {})) {
        wg_wait<0>();
        reg_fence(acc);
        if (softmax()) rescale();
        to_p(pb);
      }
      peek2();
      wg_wait<0>();
      reg_fence(acc);
      reg_fence(pa);
      give(vs);
#pragma unroll
      for (int i = 0; i < 16; i++) pa[i] = pb[i] | (vs >> 8);
    }
    TS(11 + 5 * which);
    if (which == 0) { give(take(rdy0)); rdy0 = rdy1; }
    {
      const uint32_t vs = take(rdy0);
      prep_pv(sb + vs * SLOT);
      TS(27 + 10 * which);
      turn_begin();
      TS(28 + 10 * which);
      wg_fence();
      issue_pv(n > 1);
      wg_commit();
      turn_end();
      l0 += __shfl_xor_sync(0xffffffffu, l0, 1); l1 += __shfl_xor_sync(0xffffffffu, l1, 1);
      l0 += __shfl_xor_sync(0xffffffffu, l0, 2); l1 += __shfl_xor_sync(0xffffffffu, l1, 2);
      asm("rcp.approx.ftz.f32 %0, %0;" : "+f"(l0));
      asm("rcp.approx.ftz.f32 %0, %0;" : "+f"(l1));
      peek2();
      if (which == 0) mbar_wait(bar_addr(sb, B_QFULL + w), 0);
      wg_wait<0>();
      reg_fence(acc);
      reg_fence(pa);
      give(vs);
    }
    TS(12 + 5 * which);
    {
      const uint4* dst = at<uint4>(g_qc, (uint32_t)((h * 8 + j) * 2 + w) * 32768 + (fresh_tid() & 127) * 16);
#pragma unroll
      for (int i = 0; i < 16; i++) {
        const int c = (i & 1) ? (i >> 1) + 8 : i >> 1;
        pk[4 * c]     = pack_bf16(acc[8 * c] * l0, acc[8 * c + 1] * l0);
        pk[4 * c + 1] = pack_bf16(acc[8 * c + 2] * l1, acc[8 * c + 3] * l1);
        pk[4 * c + 2] = pack_bf16(acc[8 * c + 4] * l0, acc[8 * c + 5] * l0);
        pk[4 * c + 3] = pack_bf16(acc[8 * c + 6] * l1, acc[8 * c + 7] * l1);
        if (c < CTX_SPLIT)
          asm volatile("{\n.reg .pred p;\nsetp.eq.b32 p, %5, 0;\n@p st.global.v4.u32 [%0], {%1, %2, %3, %4};\n}"
                       :: "l"(dst + c * 128), "r"(pk[4 * c]), "r"(pk[4 * c + 1]), "r"(pk[4 * c + 2]), "r"(pk[4 * c + 3]), "r"(which) : "memory");
      }
    }
    TS(13 + 5 * which);
  }

  {
    float oa[32], ob[32];
#pragma unroll
    for (int i = 0; i < 32; i++) { oa[i] = 0.f; ob[i] = 0.f; }
    uint32_t pk2[64];
#pragma unroll
    for (int i = 0; i < 64; i++) pk2[i] = 0;
    auto stage = [&](float (&o)[32], int ch) {
      reg_fence(o);
      uint32_t q[16];
#pragma unroll
      for (int i = 0; i < 16; i++) q[i] = pack_bf16(o[2 * i], o[2 * i + 1]);
      if (ch >= 4) mbar_wait(bar_addr(sb, B_S2_EMPTY + w * 4 + (ch & 3)), 0);
      store_block(qreg + (ch & 3) * 8192, lane_base16(), q);
    };
    auto hand_over = [&](int ch) {
      fence_async_smem();
      warp_arrive(bar_addr(sb, B_S2_FULL + w * 4 + (ch & 3)), lane);
    };
    uint32_t prev = 0;
    auto half = [&](int f, float (&o)[32], uint32_t (&a)[64], int accumulate) {
      const uint32_t sl = take(rdy0);
      const uint64_t d = desc_mn(sb + sl * SLOT);
      turn_begin();
      TS(40 + f);
      wg_fence();
#pragma unroll
      for (int kk = 0; kk < 16; kk++) {
        wgmma_rs_n64_tb(o, a[4 * kk], a[4 * kk + 1], a[4 * kk + 2], a[4 * kk + 3], desc_add(d, kk * 2048), accumulate | kk);
        if (kk == ARRIVE_KK && (f < 13 || w == 0)) turn_end();
      }
      wg_commit();
      if (f < 13) rdy0 = mbar_test(bar_addr(sb, B_FULL + r.slot), r.phase);
      wg_wait<1>();
      if (f >= 1 && f <= 9) give(prev);
      prev = sl;
    };
    auto load_ctx = [&](auto h0) {
      constexpr int I0 = decltype(h0)::value ? CTX_LD : 0, NL = decltype(h0)::value ? 16 - CTX_LD : CTX_LD;
      const uint4* src = at<const uint4>(g_qc, (uint32_t)(((h ^ 8) * 8 + j) * 2 + (w ^ 1)) * 32768 + (fresh_tid() & 127) * 16);
#pragma unroll
      for (int i = I0; i < I0 + NL; i++) { const uint4 v = __ldcg(src + i * 128); pk2[4 * i] = v.x; pk2[4 * i + 1] = v.y; pk2[4 * i + 2] = v.z; pk2[4 * i + 3] = v.w; }
    };
#pragma unroll 1
    for (int i = 0; i < 3; i++) {
      half(4 * i, oa, pk, 0);
      if (i == 0) { mbar_wait(bar_addr(sb, B_CTXOK + w), 0); load_ctx(Int<0>()); }
      else { hand_over(2 * i - 2); stage(ob, 2 * i - 1); }
      half(4 * i + 1, ob, pk, 0);
      if (i == 0) load_ctx(Int<1>()); else hand_over(2 * i - 1);
      half(4 * i + 2, oa, pk2, 1);
      half(4 * i + 3, ob, pk2, 1);
      stage(oa, 2 * i);
    }
    half(12, oa, pk, 0);
    hand_over(4);
    stage(ob, 5);
    half(13, oa, pk2, 1);
    hand_over(5);
    wg_wait<0>();
    reg_fence(pk);
    reg_fence(pk2);
    stage(oa, 6);
    hand_over(6);
  }
  TS(19);
  TDUMP();
}

namespace ssm {
constexpr int NCH = DA / NCONV;
constexpr int NS = 8, NP = 6;
constexpr uint32_t X0 = 384;
constexpr uint32_t HO = X0 + 4096;
constexpr uint32_t HE = HO + HO_STRIDE + 64;
constexpr uint32_t SSLOT = HE + 4096 + 64;
constexpr uint32_t PART = 264 * 16;
constexpr uint32_t OFF_P = NS * SSLOT, OFF_D = OFF_P + NP * 4 * PART, END = OFF_D + NCH * 4;
static_assert(SSLOT % 128 == 0 && HO % 128 == 0 && END <= BARS, "smem");
enum : uint32_t { B_FULL = 0, B_EMPTY = NS, B_PFULL = 2 * NS, B_PEMPTY = 2 * NS + NP };
__device__ __forceinline__ int channel(int cidx, int i) { return (i >> 4) * 64 + cidx * 16 + (i & 15); }

__device__ __forceinline__ void producer(const Params& p, uint32_t sb, int cidx, unsigned epoch) {
#pragma unroll 1
  for (int i = 0; i < NCH; i++) {
    const int s = i % NS, ch = channel(cidx, i);
    const uint32_t full = bar_addr(sb, B_FULL + s), dst = sb + s * SSLOT;
    mbar_wait(bar_addr(sb, B_EMPTY + s), ((i / NS) & 1) ^ 1);
    mbar_expect_tx(full, 4096 + 4128 + 4096);
    bulk_ld(dst + HE, at<uint8_t>(p.a_ssmk, ch * 4096), 4096, full);
    if ((i & 15) == 0) { flag_wait(flag_at(g_flags.x_ready, i >> 4), NMAIN, epoch); fence_async_all(); }
    bulk_ld(dst + HO, at<uint8_t>(g_ho, ch * HO_STRIDE), 4128, full);
    bulk_ld(dst + X0, at<uint8_t>(g_xs, ch * 4096), 4096, full);
  }
}

__device__ __forceinline__ void reducer(uint32_t sb, int cidx, int rw) {
  uint32_t n = 0;
#pragma unroll 1
  for (int i = rw; i < NCH; i += 3, n++) {
    const uint32_t b = rw + 3 * (n & 1), pb = sb + OFF_P + b * 4 * PART;
    uint8_t* dst = at<uint8_t>(g_xs, channel(cidx, i) * 4096);
    mbar_wait(bar_addr(sb, B_PFULL + b), (n >> 1) & 1);
    asm volatile("cp.async.bulk.global.shared::cta.bulk_group [%0], [%1], 4096;" :: "l"(dst), "r"(pb + 3 * PART) : "memory");
    bulk_commit();
    bulk_wait_all();
#pragma unroll
    for (int k = 2; k >= 0; k--)
      asm volatile("cp.reduce.async.bulk.global.shared::cta.bulk_group.add.noftz.bf16 [%0], [%1], 4096;" :: "l"(dst), "r"(pb + k * PART) : "memory");
    bulk_commit();
    bulk_wait_read();
    mbar_arrive(bar_addr(sb, B_PEMPTY + b));
    if (((i + 3) >> 4) != (i >> 4)) {
      bulk_wait_all();
      fence_async_all();
      flag_signal(flag_at(g_flags.z_ready, i >> 4));
    }
  }
}

__device__ __forceinline__ void mma_warpgroup(uint32_t sb, int w) {
  const int lane = threadIdx.x & 31, g = lane >> 2, c = lane & 3, wq = (threadIdx.x >> 5) & 3;
  const uint32_t aoff = ((g & 1) ? HO + 30 : HE) + (16 * wq - g + 2 * c) * 2;
  const uint32_t poff = OFF_P + wq * PART + (2 * wq + lane) * 16;
  const uint32_t dmask = (wq == 0 && c == (g >> 1)) ? ((g & 1) ? 0xffff0000u : 0xffffu) : 0u;
  float acc[8][16];
  uint32_t fa[16][4];
#pragma unroll
  for (int e = 0; e < 8; e++)
#pragma unroll
    for (int i = 0; i < 16; i++) acc[e][i] = 0.f;
  auto load_a = [&](int m, uint32_t ad) {
    fa[m][0] = lds4(ad + m * 256 + 16); fa[m][1] = lds4(ad + m * 256 + 144); fa[m][2] = lds4(ad + m * 256); fa[m][3] = lds4(ad + m * 256 + 128);
  };
  if (w == 1) named_arrive(PP_BAR, 256);
  mbar_wait(bar_addr(sb, B_FULL + w), 0);
#pragma unroll
  for (int m = 0; m < 16; m++) load_a(m, sb + w * SSLOT + aoff);
  uint32_t dd = lds4(sb + OFF_D + w * 4);
  if (threadIdx.x == 128) { GT(12); PT(10); }
  uint32_t pb = w, pphase = 1;
#pragma unroll 1
  for (int i = w; i < NCH; i += 2) {
    fa[0][2] = badd(fa[0][2], dd & dmask);
    const uint64_t db = (uint64_t)((((sb + (i % NS) * SSLOT + X0 - 16) & 0x3FFFF) >> 4) | (1u << 16)) | ((uint64_t)8 << 32);
    named_sync(PP_BAR + w, 256);
    wg_fence();
#pragma unroll
    for (int r = 0; r < 16; r++) {
      auto mm = [&](int e, int m) { wgmma_rs_n32(acc[e], fa[m][0], fa[m][1], fa[m][2], fa[m][3], db + (int64_t)(32 * e - 16 * m), m != 0); };
      mm(7, r);
      if (r < 14) mm(6, r); else mm(0, r - 14);
      if (r < 12) mm(5, r); else mm(1, r - 12);
      if (r < 10) mm(4, r); else mm(2, r - 10);
      if ((r & 1) == 0) mm(3, r >> 1);
      if (r == CONV_ARRIVE && (i + 1 < NCH)) named_arrive(PP_BAR + (w ^ 1), 256);
    }
    wg_commit();
    const int nx = i + 2 < NCH ? i + 2 : i;
    mbar_wait(bar_addr(sb, B_FULL + nx % NS), (nx / NS) & 1);
    mbar_wait(bar_addr(sb, B_PEMPTY + pb), pphase);
    const uint32_t ad = sb + (nx % NS) * SSLOT + aoff, pa = sb + pb * 4 * PART + poff;
    wg_wait<0>();
#pragma unroll
    for (int e = 0; e < 8; e++) reg_fence(acc[e]);
#pragma unroll
    for (int m = 0; m < 16; m++) reg_fence(fa[m]);
    if (lane == 0) mbar_arrive(bar_addr(sb, B_EMPTY + i % NS));
#pragma unroll
    for (int e = 0; e < 8; e++) {
      if (e < CONV_EARLY) load_a(e, ad);
      uint32_t u[4];
#pragma unroll
      for (int j = 0; j < 4; j++) {
        const int T = 4 * e + j, U = T - 1;
        float lo = acc[e][4 * j], hi = acc[e][4 * j + 1];
        if (T > 0) { lo += acc[U >> 2][4 * (U & 3) + 2]; hi += acc[U >> 2][4 * (U & 3) + 3]; }
        u[j] = pack_bf16(lo, hi);
      }
      asm volatile("stmatrix.sync.aligned.m8n8.x4.trans.shared.b16 [%0], {%1, %2, %3, %4};" :: "r"(pa + e * 512), "r"(u[0]), "r"(u[1]), "r"(u[2]), "r"(u[3]) : "memory");
    }
    dd = lds4(sb + OFF_D + nx * 4);
#pragma unroll
    for (int m = CONV_EARLY; m < CONV_FENCE; m++) load_a(m, ad);
    fence_async_smem();
    warp_arrive(bar_addr(sb, B_PFULL + pb), lane);
#pragma unroll
    for (int m = CONV_FENCE; m < 16; m++) load_a(m, ad);
    pb += 2;
    if (pb >= NP) { pb -= NP; pphase ^= 1; }
  }
  if (threadIdx.x == 128) { PT(9); GT(13); }
}

__device__ __forceinline__ void init(const Params& p, uint32_t sb, int cidx) {
  const uint32_t t = threadIdx.x;
  if (t < NCH) {
    const uint32_t d = (uint32_t)__ldg(reinterpret_cast<const unsigned short*>(p.a_D + channel(cidx, t))) * 0x10001u;
    asm volatile("st.shared.u32 [%0], %1;" :: "r"(sb + OFF_D + t * 4), "r"(d) : "memory");
  }
#pragma unroll 1
  for (uint32_t u = t; u < NS * 32; u += 128) {
    const uint32_t r = u & 31;
    if (r < 28) sts16(sb + (u >> 5) * SSLOT + (r < 24 ? r * 16 : HE - 64 + (r - 24) * 16), 0, 0, 0, 0);
    if (u < NP * 32) sts16(sb + OFF_P + (u >> 3) * PART + (u & 7) * 16, 0, 0, 0, 0);
  }
  if (t == 0) {
    for (int i = 0; i < NS; i++) { mbar_init(bar_addr(sb, B_FULL + i), 1); mbar_init(bar_addr(sb, B_EMPTY + i), 4); }
    for (int i = 0; i < NP; i++) { mbar_init(bar_addr(sb, B_PFULL + i), 4); mbar_init(bar_addr(sb, B_PEMPTY + i), 1); }
  }
  fence_async_smem();
}

__device__ __forceinline__ void side_prepare(const Params& p, int cta, int rd) {
  const int lane = threadIdx.x & 31, t0 = 16 * cta + 8 * (lane & 1);
  if (EXP_SIDE & 16) { if (lane == 0) flag_signal_after_bulk(flag_at(g_flags.x_ready, rd)); return; }
#pragma unroll 1
  for (int ch = 64 * rd + (lane & ~1); ch < 64 * rd + 64; ch += 32) {
    const uint4 sv = __ldg(at<const uint4>(p.a_shift, ch * 8));
    const uint32_t* kp = at<const uint32_t>(p.a_k, (t0 * DA + ch) * 2);
    const uint32_t* vp = at<const uint32_t>(p.a_v, (t0 * DA + ch) * 2);
    uint32_t k0 = 0, k1 = 0, k2 = 0, kk[8], x[8];
    if (t0 > 0) { k0 = __ldg(kp - 3 * (DA / 2)); k1 = __ldg(kp - 2 * (DA / 2)); k2 = __ldg(kp - DA / 2); }
#pragma unroll
    for (int i = 0; i < 8; i++) { kk[i] = __ldg(kp + i * (DA / 2)); x[i] = __ldg(vp + i * (DA / 2)); }
    const uint32_t sh0 = __byte_perm(sv.x, sv.z, 0x5410), sh1 = __byte_perm(sv.x, sv.z, 0x7632);
    const uint32_t sh2 = __byte_perm(sv.y, sv.w, 0x5410), sh3 = __byte_perm(sv.y, sv.w, 0x7632);
#pragma unroll
    for (int i = 0; i < 8; i++) {
      uint32_t ks = bmul(k0, sh3);
      ks = badd(ks, bmul(k1, sh2)); ks = badd(ks, bmul(k2, sh1)); ks = badd(ks, bmul(kk[i], sh0));
      x[i] = bmul(ks, x[i]);
      k0 = k1; k1 = k2; k2 = kk[i];
    }
    uint4* dst = at<uint4>(g_xs, ch * 4096 + t0 * 2);
    if ((EXP_SIDE & 4) && (x[0] ^ x[1] ^ x[2] ^ x[3] ^ x[4] ^ x[5] ^ x[6] ^ x[7]) != 0x12345) continue;
    dst[0]   = make_uint4(__byte_perm(x[7], x[6], 0x5410), __byte_perm(x[5], x[4], 0x5410), __byte_perm(x[3], x[2], 0x5410), __byte_perm(x[1], x[0], 0x5410));
    dst[256] = make_uint4(__byte_perm(x[7], x[6], 0x7632), __byte_perm(x[5], x[4], 0x7632), __byte_perm(x[3], x[2], 0x7632), __byte_perm(x[1], x[0], 0x7632));
  }
  if (!(EXP_SIDE & 8)) {
    const int hc = 64 * rd + (cta >> 1), r0 = (cta & 1) * 128 + lane;
    const uint4* src = at<const uint4>(p.a_ssmk, hc * 4096 + r0 * 16);
    uint4* dst = at<uint4>(g_ho, hc * HO_STRIDE + r0 * 16);
    uint4 w[4];
    uint32_t nx[4];
#pragma unroll
    for (int i = 0; i < 4; i++) { w[i] = __ldg(src + 32 * i); nx[i] = r0 + 32 * i < 255 ? __ldg(reinterpret_cast<const uint32_t*>(src + 32 * i + 1)) : 0u; }
#pragma unroll
    for (int i = 0; i < 4; i++)
      dst[32 * i + 2] = make_uint4(__byte_perm(w[i].x, w[i].y, 0x5432), __byte_perm(w[i].y, w[i].z, 0x5432), __byte_perm(w[i].z, w[i].w, 0x5432), __byte_perm(w[i].w, nx[i], 0x5432));
    const uint32_t h0 = __shfl_sync(0xffffffffu, w[0].x, 0);
    if (r0 < 2) dst[0] = make_uint4(0, 0, 0, r0 ? h0 << 16 : 0u);
  }
  __syncwarp();
  if (lane == 0) { if (EXP_SIDE & 2) flag_signal_after_bulk(flag_at(g_flags.x_ready, rd)); else flag_signal(flag_at(g_flags.x_ready, rd)); }
}
__device__ __forceinline__ void side_finish(const Params& p, int cta, int rd) {
  const int lane = threadIdx.x & 31, t0 = 16 * cta + 8 * (lane & 1);
#pragma unroll 1
  for (int ch = 64 * rd + (lane & ~1); ch < 64 * rd + 64; ch += 32) {
    const uint4* src = at<const uint4>(g_xs, ch * 4096 + t0 * 2);
    const uint32_t* qp = at<const uint32_t>(p.a_q, (t0 * DA + ch) * 2);
    uint32_t* op = at<uint32_t>(p.out, (t0 * OUTW + ch) * 2);
    const uint4 z0 = __ldcg(src), z1 = __ldcg(src + 256);
    uint32_t q[8];
#pragma unroll
    for (int i = 0; i < 8; i++) q[i] = __ldg(qp + i * (DA / 2));
    const uint32_t a[4] = {z0.w, z0.z, z0.y, z0.x}, b[4] = {z1.w, z1.z, z1.y, z1.x};
#pragma unroll
    for (int i = 0; i < 4; i++) {
      op[(2 * i) * (OUTW / 2)]     = bmul(q[2 * i], __byte_perm(a[i], b[i], 0x7632));
      op[(2 * i + 1) * (OUTW / 2)] = bmul(q[2 * i + 1], __byte_perm(a[i], b[i], 0x5410));
    }
  }
}
__device__ __forceinline__ void clear_rows(const Params& p, int qt, int part) {
  const int lane = threadIdx.x & 31;
  if (lane < 28) {
    uint4* z = at<uint4>(p.out, ((qt * 128 + part * 16) * OUTW + DA) * 2 + lane * 16);
#pragma unroll
    for (int i = 0; i < 32; i++) z[(i >> 1) * (OUTW / 8) + (i & 1) * 28] = make_uint4(0, 0, 0, 0);
  }
  __syncwarp();
  if (lane == 0) flag_signal(flag_at(g_flags.zero_ready, qt));
}
__device__ __forceinline__ void side_work(const Params& p, int cta, int qt, unsigned epoch) {
#pragma unroll 1
  for (int rd = -SIDE_AHEAD; rd < 7; rd++) {
    if (rd >= 0) {
      if ((threadIdx.x & 31) == 0) flag_wait_slow(flag_at(g_flags.z_ready, rd), 3 * NCONV, epoch);
      __syncwarp();
    }
    if (rd + SIDE_AHEAD < 7) side_prepare(p, cta, rd + SIDE_AHEAD);
    if (rd >= 0 && !(EXP_SIDE & 1)) side_finish(p, cta, rd);
    if (rd == ZERO_RD) clear_rows(p, qt, (cta >> 3) & 7);
  }
}
}

__global__ void __cluster_dims__(2, 1, 1) __launch_bounds__(NTHREADS, 1)
concat_heads__ssm_conv_h3__compressed_kv_cla__prompt_kernel(const __grid_constant__ Params p) {
  extern __shared__ uint8_t smem_raw[];
  const uint32_t sb = (smem_u32(smem_raw) + 1023) & ~1023u;
  const int warp = __shfl_sync(0xffffffffu, threadIdx.x >> 5, 0);
  const int wg = warp >> 2;
  const int cta = blockIdx.x;
  const bool attn = cta < NMAIN;
  int h, u;
  {
    const int c = cta >> 1;
    if (c < 4) { h = 9; u = c; }
    else if (c < 36) { h = (c - 4) & 7; u = (c - 4) >> 3; }
    else { const int i = (c - 36) % 7; h = i == 0 ? 8 : 9 + i; u = (c - 36) / 7; }
  }
  const int j = 2 * u + (cta & 1);
  const int lane = threadIdx.x & 31;
  if (wg != 0) {
    if (attn) {
      if (threadIdx.x == NTHREADS - 32) {
        if (PF_MAPS & 2) prefetch_map(QFIRST ? &p.wq : &p.wuk);
        for (int i = 0; i < NSLOT; i++) mbar_init(bar_addr(sb, B_FULL + i), 1);
        asm volatile("fence.mbarrier_init.release.cluster;" ::: "memory");
      }
      __syncwarp();
      cluster_arrive();
      if (wg == 2) named_arrive(PP_BAR, 256);
      if (threadIdx.x == NTHREADS - 32) {
        for (int k = 0; k < EARLY_LD; k++) {
          const uint32_t full = bar_addr(sb, B_FULL + k);
          mbar_expect_tx(full, 49152);
          if (QFIRST) {
            tma_ld2(sb + QREG + k * 16384, &p.x, full, k * 64, q_tile(h, j, 1) * 128);
            load_tile4(sb + k * SLOT, &p.wq, full, k * 64, att_head(h, 1) * 4, j & 1, false);
          } else {
            tma_ld2(sb + QREG + k * 16384, &p.ckv, full, k * 64, p1_rows(h, j, 0) * 128);
            load_tile4(sb + k * SLOT, &p.wuk, full, k * 64, p1_head(h, 0) * 4, j & 1, false);
          }
        }
      }
      __syncwarp();
    }
    asm volatile("setmaxnreg.inc.sync.aligned.u32 232;");
    if (!attn) {
      if (p.out != nullptr) { named_sync(0, NTHREADS); ssm::mma_warpgroup(sb, wg - 1); }
      return;
    }
    if (p.out != nullptr) consumer_main(p, sb, h, j, wg - 1, warp & 3);
  } else {
    asm volatile("setmaxnreg.dec.sync.aligned.u32 40;");
    if (!attn) {
      ssm::init(p, sb, cta - NMAIN);
      named_sync(0, NTHREADS);
      if (lane == 0) {
        if (warp == 0) { ssm::producer(p, sb, cta - NMAIN, load_epoch()); cta_done(32); }
        else ssm::reducer(sb, cta - NMAIN, warp - 1);
        if (warp == 1) GT(14);
      }
      return;
    }
    if (lane == 0) {
      if (warp == 1) {
        for (int i = 0; i < NSLOT; i++) mbar_init(bar_addr(sb, B_EMPTY + i), (UNICAST & 8) ? 8 : 16);
        for (int i = 0; i < 2; i++) {
          mbar_init(bar_addr(sb, B_QFREE + i), 4); mbar_init(bar_addr(sb, B_QFULL + i), 1);
          mbar_init(bar_addr(sb, B_KVOK + i), 1); mbar_init(bar_addr(sb, B_CTXOK + i), 1);
        }
      } else if (warp == 2) {
        for (int i = 0; i < 8; i++) { mbar_init(bar_addr(sb, B_S2_FULL + i), 4); mbar_init(bar_addr(sb, B_S2_EMPTY + i), 1); }
      } else if (warp == 0) {
        mbar_init(bar_addr(sb, B_DONE), 2);
        for (int i = 0; i < 2; i++) {
          mbar_init(bar_addr(sb, B_ST_KV + i), 4); mbar_init(bar_addr(sb, B_ST_KV + 2 + i), 4);
          mbar_init(bar_addr(sb, B_ST_Q + i), 4); mbar_init(bar_addr(sb, B_ST_CTX + i), 4);
        }
      }
      asm volatile("fence.mbarrier_init.release.cluster;" ::: "memory");
    }
    __syncwarp();
    cluster_arrive();
    cluster_wait();
    if (warp == 0) {
      if (lane == 0) producer_main(p, sb, h, j);
    } else if (warp < 3) {
      if (lane == 0) {
        if ((PF_MAPS & 1) && warp == 1) { __nanosleep(2000); prefetch_map(&p.wuv); prefetch_map(&p.x); prefetch_map(&p.wq); prefetch_map(&p.o); prefetch_map(&p.wo); }
        helper_main(p, sb, h, j, warp - 1);
        mbar_arrive(bar_addr(sb, B_DONE));
      }
    } else {
      ssm::side_work(p, h * 8 + j, q_tile(h, j, 1), load_epoch());
      if (lane == 0) { GT(57); mbar_wait(bar_addr(sb, B_DONE), 0); cta_done(1); }
    }
  }
}

typedef CUresult (*EncodeTiledFn)(CUtensorMap*, CUtensorMapDataType, cuuint32_t, void*, const cuuint64_t*, const cuuint64_t*,
                                  const cuuint32_t*, const cuuint32_t*, CUtensorMapInterleave, CUtensorMapSwizzle,
                                  CUtensorMapL2promotion, CUtensorMapFloatOOBfill);

void make_map(EncodeTiledFn enc, CUtensorMap* m, const void* ptr, int rank, const uint64_t* dims, const uint64_t* strides, const uint32_t* box) {
  cuuint64_t d[5], s[4]; cuuint32_t b[5], e[5] = {1, 1, 1, 1, 1};
  for (int i = 0; i < rank; i++) { d[i] = dims[i]; b[i] = box[i]; if (i) s[i - 1] = strides[i - 1]; }
  enc(m, CU_TENSOR_MAP_DATA_TYPE_BFLOAT16, rank, const_cast<void*>(ptr), d, s, b, e, CU_TENSOR_MAP_INTERLEAVE_NONE,
      CU_TENSOR_MAP_SWIZZLE_128B, CU_TENSOR_MAP_L2_PROMOTION_L2_256B, CU_TENSOR_MAP_FLOAT_OOB_FILL_NONE);
}
void map2(EncodeTiledFn enc, CUtensorMap* m, const void* ptr, uint64_t cols, uint64_t rows, uint32_t bc, uint32_t br) {
  const uint64_t dims[2] = {cols, rows}, st[1] = {cols * 2}; const uint32_t box[2] = {bc, br};
  make_map(enc, m, ptr, 2, dims, st, box);
}
void map3(EncodeTiledFn enc, CUtensorMap* m, const void* ptr, uint64_t rows, uint32_t nblk) {
  const uint64_t dims[3] = {64, rows, 64}, st[2] = {8192, 128}; const uint32_t box[3] = {64, 64, nblk};
  make_map(enc, m, ptr, 3, dims, st, box);
}

}

extern "C" void kernel_launch(void* const* d_in, const int* in_sizes, int n_in, void* d_out, int out_size) {
  (void)in_sizes; (void)n_in; (void)out_size;
  static EncodeTiledFn enc = nullptr;
  if (!enc) {
    void* fn = nullptr; cudaDriverEntryPointQueryResult qr;
    cudaGetDriverEntryPoint("cuTensorMapEncodeTiled", &fn, cudaEnableDefault, &qr);
    enc = (EncodeTiledFn)fn;
    cudaFuncSetAttribute(concat_heads__ssm_conv_h3__compressed_kv_cla__prompt_kernel, cudaFuncAttributeMaxDynamicSharedMemorySize, SMEM_BYTES);
  }
  Params p;
  p.a_q = (const bf16*)d_in[0]; p.a_k = (const bf16*)d_in[1]; p.a_v = (const bf16*)d_in[2];
  p.a_shift = (const bf16*)d_in[3]; p.a_ssmk = (const bf16*)d_in[4]; p.a_D = (const bf16*)d_in[5];
  p.out = (bf16*)d_out;
  map2(enc, &p.x, d_in[6], DM, SEQ, 64, 128);
  map2(enc, &p.ckv, d_in[7], DC, SEQ, 64, 128);
  map3(enc, &p.wq, d_in[8], DM, 2);
  map3(enc, &p.wuk, d_in[9], DC, 2);
  map3(enc, &p.wuv, d_in[10], DC, 2);
  {
    const uint64_t dims[5] = {DM, 2, 4, 4, NH * HD / 32}, st[4] = {DM * 2, 8 * DM * 2, 2 * DM * 2, 32 * DM * 2}; const uint32_t box[5] = {64, 2, 4, 4, 4};
    make_map(enc, &p.wo, d_in[11], 5, dims, st, box);
  }
  map2(enc, &p.o, d_out, OUTW, SEQ, 64, 64);
  concat_heads__ssm_conv_h3__compressed_kv_cla__prompt_kernel<<<NCTA, NTHREADS, SMEM_BYTES>>>(p);
}
```

```cpp
#include <cuda_runtime.h>
#include <cuda_bf16.h>
#include <cuda.h>
#include <stdint.h>

namespace {

typedef __nv_bfloat16 bf16;

constexpr int SEQ  = 2048;
constexpr int DA   = 448;
constexpr int NH   = 16;
constexpr int HD   = 256;
constexpr int DM   = 448;
constexpr int DC   = 1024;
constexpr int OUTW = DA + DM;
constexpr int NMAIN = 128;
constexpr int NCONV = 4;
constexpr int NCTA  = NMAIN + NCONV;
constexpr int LOG_DONE = 8;
constexpr int NTHREADS = 384;

__device__ __align__(1024) bf16 g_kv[2ull * SEQ * NH * HD];
__device__ __align__(1024) bf16 g_qc[(size_t)NMAIN * 128 * HD];
__device__ __align__(128) uint8_t g_xs[DA * SEQ * 2];
constexpr uint32_t HO_STRIDE = 4224;
__device__ __align__(128) uint8_t g_ho[DA * HO_STRIDE];
struct alignas(128) Flag { unsigned v; unsigned pad[31]; };
struct Flags {
  Flag kv_ready[NH * 2];
  Flag ctx_ready[NMAIN * 2];
  Flag x_ready[7];
  Flag z_ready[7];
  Flag zero_ready[16];
  alignas(128) unsigned long long done;
};
__device__ Flags g_flags;
#define TS(i)
#define TSC(i, cond)
#define TDUMP()
#define GT(i)
#define PT(i)
#define PCLK(var)
#define PACC(acc, t0)

struct alignas(64) Params {
  CUtensorMap ckv;
  CUtensorMap wuk;
  CUtensorMap wuv;
  CUtensorMap x;
  CUtensorMap wq;
  CUtensorMap o;
  CUtensorMap wo;
  const bf16 *a_q, *a_k, *a_v, *a_shift, *a_ssmk, *a_D;
  bf16* out;
};

constexpr uint32_t SLOT     = 32768;
constexpr int      NSLOT    = 5;
constexpr uint32_t QREG     = 163840;
constexpr uint32_t BARS     = 229376;
constexpr uint32_t SMEM_BYTES = BARS + 1024 + 1024;
enum : uint32_t {
  B_FULL = 0, B_EMPTY = 5, B_KVOK = 12, B_ST_Q = 14, B_ST_CTX = 16, B_DONE = 19, B_QFREE = 20, B_QFULL = 22,
  B_S2_FULL = 24, B_S2_EMPTY = 32, B_CTXOK = 40, B_PF = 42, B_ST_KV = 44
};
constexpr int P1_STEPS = 4 * 16 + 2 * 7, P1_XS = P1_STEPS - 2;

template <typename T> __device__ __forceinline__ T* at(const void* base, uint32_t off) {
  asm volatile("" : "+r"(off));
  return reinterpret_cast<T*>(const_cast<char*>(static_cast<const char*>(base)) + off);
}
__device__ __forceinline__ unsigned* flag_at(Flag* f, uint32_t i) { return at<unsigned>(f, i * (uint32_t)sizeof(Flag)); }
__device__ __forceinline__ uint32_t smem_u32(const void* p) { return (uint32_t)__cvta_generic_to_shared(p); }
__device__ __forceinline__ void mbar_init(uint32_t bar, uint32_t cnt) {
  asm volatile("mbarrier.init.shared::cta.b64 [%0], %1;" :: "r"(bar), "r"(cnt) : "memory");
}
__device__ __forceinline__ void mbar_expect_tx(uint32_t bar, uint32_t bytes) {
  asm volatile("mbarrier.arrive.expect_tx.shared::cta.b64 _, [%0], %1;" :: "r"(bar), "r"(bytes) : "memory");
}
__device__ __forceinline__ void mbar_arrive(uint32_t bar) {
  asm volatile("mbarrier.arrive.shared::cta.b64 _, [%0];" :: "r"(bar) : "memory");
}
__device__ __forceinline__ void mbar_arrive_n(uint32_t bar, uint32_t n) {
  asm volatile("mbarrier.arrive.shared::cta.b64 _, [%0], %1;" :: "r"(bar), "r"(n) : "memory");
}
__device__ __forceinline__ void mbar_arrive_remote(uint32_t bar, uint32_t cta) {
  asm volatile("{\n.reg .b32 ra;\nmapa.shared::cluster.u32 ra, %0, %1;\n"
               "mbarrier.arrive.shared::cluster.b64 _, [ra];\n}" :: "r"(bar), "r"(cta) : "memory");
}
__device__ __forceinline__ bool mbar_try(uint32_t bar, uint32_t parity) {
  uint32_t ok;
  asm volatile("{\n.reg .pred p;\nmbarrier.try_wait.parity.shared::cta.b64 p, [%1], %2;\nselp.u32 %0, 1, 0, p;\n}"
               : "=r"(ok) : "r"(bar), "r"(parity) : "memory");
  return ok;
}
__device__ __forceinline__ uint32_t mbar_test(uint32_t bar, uint32_t parity) {
  uint32_t ok;
  asm volatile("{\n.reg .pred p;\nmbarrier.test_wait.parity.shared::cta.b64 p, [%1], %2;\nselp.u32 %0, 1, 0, p;\n}"
               : "=r"(ok) : "r"(bar), "r"(parity) : "memory");
  return ok;
}
constexpr uint32_t SPIN_LIMIT = 1u << 24;
__device__ __forceinline__ void mbar_wait(uint32_t bar, uint32_t parity) {
  if (mbar_try(bar, parity)) return;
  uint32_t n = 0;
  while (!mbar_try(bar, parity)) { if (++n > SPIN_LIMIT) __trap(); }
}
__device__ __forceinline__ void mbar_wait_unless(uint32_t ready, uint32_t bar, uint32_t parity) {
  asm volatile("{\n.reg .pred p;\n.reg .b32 n;\nsetp.ne.u32 p, %0, 0;\nvote.sync.all.pred p, p, 0xffffffff;\n@p bra.uni WDONE;\nmov.u32 n, 0;\n"
               "WLOOP:\nmbarrier.try_wait.parity.shared::cta.b64 p, [%1], %2;\n@p bra.uni WDONE;\nadd.u32 n, n, 1;\nsetp.lt.u32 p, n, %3;\n@p bra.uni WLOOP;\ntrap;\nWDONE:\n}"
               :: "r"(ready), "r"(bar), "r"(parity), "n"(SPIN_LIMIT) : "memory");
}
__device__ __forceinline__ unsigned load_epoch() {
  unsigned long long d; asm volatile("ld.relaxed.gpu.global.u64 %0, [%1];" : "=l"(d) : "l"(&g_flags.done) : "memory");
  return (unsigned)(d >> LOG_DONE);
}
__device__ __forceinline__ void flag_wait(const unsigned* f, unsigned count, unsigned epoch) {
  const unsigned target = (epoch + 1) * count;
  uint32_t n = 0;
  while (true) {
    unsigned v;
    asm volatile("ld.acquire.gpu.global.u32 %0, [%1];" : "=r"(v) : "l"(f) : "memory");
    if ((int)(v - target) >= 0) break;
    if (++n > SPIN_LIMIT) __trap();
    __nanosleep(20);
  }
}
__device__ __forceinline__ void flag_wait_slow(const unsigned* f, unsigned count, unsigned epoch) {
  const unsigned target = (epoch + 1) * count;
  uint32_t n = 0;
  while (true) {
    unsigned v;
    asm volatile("ld.acquire.gpu.global.u32 %0, [%1];" : "=r"(v) : "l"(f) : "memory");
    if ((int)(v - target) >= 0) break;
    if (++n > SPIN_LIMIT / 16) __trap();
    __nanosleep(1000);
  }
}
__device__ __forceinline__ void cta_done(unsigned long long n) { asm volatile("red.relaxed.gpu.global.add.u64 [%0], %1;" :: "l"(&g_flags.done), "l"(n) : "memory"); }
__device__ __forceinline__ void flag_wait_fast(const unsigned* f, unsigned count, unsigned epoch) {
  const unsigned target = (epoch + 1) * count;
  uint32_t n = 0;
  while (true) {
    unsigned v;
    asm volatile("ld.acquire.gpu.global.u32 %0, [%1];" : "=r"(v) : "l"(f) : "memory");
    if ((int)(v - target) >= 0) break;
    if (++n > SPIN_LIMIT) __trap();
  }
}
__device__ __forceinline__ void fence_async_all() { asm volatile("fence.proxy.async.global;" ::: "memory"); }
__device__ __forceinline__ void flag_signal(unsigned* f) { asm volatile("red.release.gpu.global.add.u32 [%0], 1;" :: "l"(f) : "memory"); }
__device__ __forceinline__ void flag_signal_after_bulk(unsigned* f) {
  asm volatile("red.relaxed.gpu.global.add.u32 [%0], 1;" :: "l"(f) : "memory");
}
__device__ __forceinline__ void fence_async_smem() { asm volatile("fence.proxy.async.shared::cta;" ::: "memory"); }
#define HINTS 40
constexpr uint64_t POL_NORMAL = 0x1000000000000000ull, POL_FIRST = 0x12F0000000000000ull;
__device__ __forceinline__ constexpr uint64_t pol(bool first) { return first ? POL_FIRST : POL_NORMAL; }
__device__ __forceinline__ void tma_ld2(uint32_t dst, const CUtensorMap* m, uint32_t bar, int c0, int c1, uint64_t pl = POL_NORMAL) {
  asm volatile("cp.async.bulk.tensor.2d.shared::cluster.global.mbarrier::complete_tx::bytes.L2::cache_hint [%0], [%1, {%3, %4}], [%2], %5;"
               :: "r"(dst), "l"(m), "r"(bar), "r"(c0), "r"(c1), "l"(pl) : "memory");
}
__device__ __forceinline__ void tma_ld3(uint32_t dst, const CUtensorMap* m, uint32_t bar, int c0, int c1, int c2, uint64_t pl = POL_NORMAL) {
  asm volatile("cp.async.bulk.tensor.3d.shared::cluster.global.mbarrier::complete_tx::bytes.L2::cache_hint [%0], [%1, {%3, %4, %5}], [%2], %6;"
               :: "r"(dst), "l"(m), "r"(bar), "r"(c0), "r"(c1), "r"(c2), "l"(pl) : "memory");
}
__device__ __forceinline__ void tma_ld3_mc(uint32_t dst, const CUtensorMap* m, uint32_t bar, int c0, int c1, int c2, uint64_t pl = POL_NORMAL) {
  asm volatile("cp.async.bulk.tensor.3d.shared::cluster.global.mbarrier::complete_tx::bytes.multicast::cluster.L2::cache_hint [%0], [%1, {%3, %4, %5}], [%2], %6, %7;"
               :: "r"(dst), "l"(m), "r"(bar), "r"(c0), "r"(c1), "r"(c2), "h"((uint16_t)3), "l"(pl) : "memory");
}
__device__ __forceinline__ void bulk_ld(uint32_t dst, const void* src, uint32_t bytes, uint32_t bar) {
  asm volatile("cp.async.bulk.shared::cluster.global.mbarrier::complete_tx::bytes [%0], [%1], %2, [%3];"
               :: "r"(dst), "l"(src), "r"(bytes), "r"(bar) : "memory");
}
__device__ __forceinline__ void bulk_ld_p(uint32_t dst, const void* src, uint32_t bytes, uint32_t bar, uint64_t pl) {
  asm volatile("cp.async.bulk.shared::cluster.global.mbarrier::complete_tx::bytes.L2::cache_hint [%0], [%1], %2, [%3], %4;"
               :: "r"(dst), "l"(src), "r"(bytes), "r"(bar), "l"(pl) : "memory");
}
__device__ __forceinline__ void bulk_ld_mc(uint32_t dst, const void* src, uint32_t bytes, uint32_t bar, uint64_t pl) {
  asm volatile("cp.async.bulk.shared::cluster.global.mbarrier::complete_tx::bytes.multicast::cluster.L2::cache_hint [%0], [%1], %2, [%3], %4, %5;"
               :: "r"(dst), "l"(src), "r"(bytes), "r"(bar), "h"((uint16_t)3), "l"(pl) : "memory");
}
__device__ __forceinline__ void tma_st3(const CUtensorMap* m, uint32_t src, int c0, int c1, int c2) {
  asm volatile("cp.async.bulk.tensor.3d.global.shared::cta.bulk_group.L2::cache_hint [%0, {%2, %3, %4}], [%1], %5;"
               :: "l"(m), "r"(src), "r"(c0), "r"(c1), "r"(c2), "l"(pol(HINTS & 1024)) : "memory");
}
__device__ __forceinline__ void tma_ld2_mc(uint32_t dst, const CUtensorMap* m, uint32_t bar, int c0, int c1, uint64_t pl = POL_NORMAL) {
  asm volatile("cp.async.bulk.tensor.2d.shared::cluster.global.mbarrier::complete_tx::bytes.multicast::cluster.L2::cache_hint [%0], [%1, {%3, %4}], [%2], %5, %6;"
               :: "r"(dst), "l"(m), "r"(bar), "r"(c0), "r"(c1), "h"((uint16_t)3), "l"(pl) : "memory");
}
__device__ __forceinline__ void tma_ld5_mc(uint32_t dst, const CUtensorMap* m, uint32_t bar, int c0, int c4, uint64_t pl = POL_NORMAL) {
  asm volatile("cp.async.bulk.tensor.5d.shared::cluster.global.mbarrier::complete_tx::bytes.multicast::cluster.L2::cache_hint [%0], [%1, {%3, %7, %7, %7, %4}], [%2], %5, %6;"
               :: "r"(dst), "l"(m), "r"(bar), "r"(c0), "r"(c4), "h"((uint16_t)3), "l"(pl), "r"(0) : "memory");
}
__device__ __forceinline__ void tma_ld5(uint32_t dst, const CUtensorMap* m, uint32_t bar, int c0, int c4, uint64_t pl = POL_NORMAL) {
  asm volatile("cp.async.bulk.tensor.5d.shared::cluster.global.mbarrier::complete_tx::bytes.L2::cache_hint [%0], [%1, {%3, %6, %6, %6, %4}], [%2], %5;"
               :: "r"(dst), "l"(m), "r"(bar), "r"(c0), "r"(c4), "l"(pl), "r"(0) : "memory");
}
__device__ __forceinline__ void tma_st2(const CUtensorMap* m, uint32_t src, int c0, int c1) {
  asm volatile("cp.async.bulk.tensor.2d.global.shared::cta.bulk_group [%0, {%2, %3}], [%1];"
               :: "l"(m), "r"(src), "r"(c0), "r"(c1) : "memory");
}
__device__ __forceinline__ void tma_red2(const CUtensorMap* m, uint32_t src, int c0, int c1) {
  asm volatile("cp.reduce.async.bulk.tensor.2d.global.shared::cta.add.bulk_group [%0, {%2, %3}], [%1];"
               :: "l"(m), "r"(src), "r"(c0), "r"(c1) : "memory");
}
__device__ __forceinline__ void bulk_commit() { asm volatile("cp.async.bulk.commit_group;" ::: "memory"); }
__device__ __forceinline__ void bulk_wait_read() { asm volatile("cp.async.bulk.wait_group.read 0;" ::: "memory"); }
__device__ __forceinline__ void bulk_wait_all() { asm volatile("cp.async.bulk.wait_group 0;" ::: "memory"); }
__device__ __forceinline__ void prefetch_map(const CUtensorMap* m) { asm volatile("prefetch.tensormap [%0];" :: "l"(m) : "memory"); }
__device__ __forceinline__ void wg_fence() { asm volatile("wgmma.fence.sync.aligned;" ::: "memory"); }
__device__ __forceinline__ void wg_commit() { asm volatile("wgmma.commit_group.sync.aligned;" ::: "memory"); }
template <int N> __device__ __forceinline__ void wg_wait() { asm volatile("wgmma.wait_group.sync.aligned %0;" :: "n"(N) : "memory"); }
template <int N> __device__ __forceinline__ void reg_fence(float (&d)[N]) {
#pragma unroll
  for (int i = 0; i < N; i++) asm volatile("" : "+f"(d[i]) :: "memory");
}
template <int N> __device__ __forceinline__ void reg_fence(uint32_t (&d)[N]) {
#pragma unroll
  for (int i = 0; i < N; i++) asm volatile("" : "+r"(d[i]) :: "memory");
}
__device__ __forceinline__ uint32_t fresh_tid() { uint32_t t; asm volatile("mov.u32 %0, %%tid.x;" : "=r"(t)); return t; }
__device__ __forceinline__ uint32_t lane_base16() {
  const uint32_t t = fresh_tid(), lane = t & 31, wq = (t >> 5) & 3;
  return (16 * wq + (lane & 7) + 8 * ((lane >> 3) & 1)) * 128 + (((lane >> 4) ^ (lane & 7)) << 4);
}
__device__ __forceinline__ void cluster_arrive() { asm volatile("barrier.cluster.arrive.relaxed.aligned;" ::: "memory"); }
__device__ __forceinline__ void cluster_wait() { asm volatile("barrier.cluster.wait.acquire.aligned;" ::: "memory"); }
__device__ __forceinline__ void named_sync(int id, int n) { asm volatile("bar.sync %0, %1;" :: "r"(id), "r"(n) : "memory"); }
__device__ __forceinline__ void named_arrive(int id, int n) { asm volatile("bar.arrive %0, %1;" :: "r"(id), "r"(n) : "memory"); }
__device__ __forceinline__ uint32_t pack_bf16(float lo, float hi) {
  uint32_t r; asm("cvt.rn.bf16x2.f32 %0, %1, %2;" : "=r"(r) : "f"(hi), "f"(lo)); return r;
}
__device__ __forceinline__ float ex2(float x) { float y; asm("ex2.approx.ftz.f32 %0, %1;" : "=f"(y) : "f"(x)); return y; }
__device__ __forceinline__ void stsm4(uint32_t addr, uint32_t a, uint32_t b, uint32_t c, uint32_t d) {
  asm volatile("stmatrix.sync.aligned.m8n8.x4.shared.b16 [%0], {%1, %2, %3, %4};" :: "r"(addr), "r"(a), "r"(b), "r"(c), "r"(d) : "memory");
}
__device__ __forceinline__ uint64_t mk_desc(uint32_t addr, uint32_t lbo, uint32_t sbo) {
  return (uint64_t)(((addr & 0x3FFFF) >> 4) | ((lbo >> 4) << 16)) | ((uint64_t)((sbo >> 4) | (1u << 30)) << 32);
}
__device__ __forceinline__ uint64_t desc_k(uint32_t addr)  { return mk_desc(addr, 16, 1024); }
__device__ __forceinline__ uint64_t desc_mn(uint32_t addr) { return mk_desc(addr, 8192, 1024); }
__device__ __forceinline__ uint64_t desc_64(uint32_t addr) { return (uint64_t)(((addr & 0x3FFFF) >> 4) | ((4096u >> 4) << 16)) | ((uint64_t)((512u >> 4) | (2u << 30)) << 32); }
__device__ __forceinline__ uint64_t desc_add(uint64_t d, uint32_t bytes) { return d + (bytes >> 4); }

__device__ __forceinline__ void wgmma_ss_n256_tb(float (&d)[128], uint64_t da, uint64_t db, int sd) {
  asm volatile("{\n.reg .pred p;\nsetp.ne.b32 p, %130, 0;\n"
    "wgmma.mma_async.sync.aligned.m64n256k16.f32.bf16.bf16 "
    "{%0, %1, %2, %3, %4, %5, %6, %7, %8, %9, %10, %11, %12, %13, %14, %15, "
    "%16, %17, %18, %19, %20, %21, %22, %23, %24, %25, %26, %27, %28, %29, %30, %31, "
    "%32, %33, %34, %35, %36, %37, %38, %39, %40, %41, %42, %43, %44, %45, %46, %47, "
    "%48, %49, %50, %51, %52, %53, %54, %55, %56, %57, %58, %59, %60, %61, %62, %63, "
    "%64, %65, %66, %67, %68, %69, %70, %71, %72, %73, %74, %75, %76, %77, %78, %79, "
    "%80, %81, %82, %83, %84, %85, %86, %87, %88, %89, %90, %91, %92, %93, %94, %95, "
    "%96, %97, %98, %99, %100, %101, %102, %103, %104, %105, %106, %107, %108, %109, %110, %111, "
    "%112, %113, %114, %115, %116, %117, %118, %119, %120, %121, %122, %123, %124, %125, %126, %127}, "
    "%128, %129, p, 1, 1, 0, 1;\n}"
    : "+f"(d[0]), "+f"(d[1]), "+f"(d[2]), "+f"(d[3]), "+f"(d[4]), "+f"(d[5]), "+f"(d[6]), "+f"(d[7]),
      "+f"(d[8]), "+f"(d[9]), "+f"(d[10]), "+f"(d[11]), "+f"(d[12]), "+f"(d[13]), "+f"(d[14]), "+f"(d[15]),
      "+f"(d[16]), "+f"(d[17]), "+f"(d[18]), "+f"(d[19]), "+f"(d[20]), "+f"(d[21]), "+f"(d[22]), "+f"(d[23]),
      "+f"(d[24]), "+f"(d[25]), "+f"(d[26]), "+f"(d[27]), "+f"(d[28]), "+f"(d[29]), "+f"(d[30]), "+f"(d[31]),
      "+f"(d[32]), "+f"(d[33]), "+f"(d[34]), "+f"(d[35]), "+f"(d[36]), "+f"(d[37]), "+f"(d[38]), "+f"(d[39]),
      "+f"(d[40]), "+f"(d[41]), "+f"(d[42]), "+f"(d[43]), "+f"(d[44]), "+f"(d[45]), "+f"(d[46]), "+f"(d[47]),
      "+f"(d[48]), "+f"(d[49]), "+f"(d[50]), "+f"(d[51]), "+f"(d[52]), "+f"(d[53]), "+f"(d[54]), "+f"(d[55]),
      "+f"(d[56]), "+f"(d[57]), "+f"(d[58]), "+f"(d[59]), "+f"(d[60]), "+f"(d[61]), "+f"(d[62]), "+f"(d[63]),
      "+f"(d[64]), "+f"(d[65]), "+f"(d[66]), "+f"(d[67]), "+f"(d[68]), "+f"(d[69]), "+f"(d[70]), "+f"(d[71]),
      "+f"(d[72]), "+f"(d[73]), "+f"(d[74]), "+f"(d[75]), "+f"(d[76]), "+f"(d[77]), "+f"(d[78]), "+f"(d[79]),
      "+f"(d[80]), "+f"(d[81]), "+f"(d[82]), "+f"(d[83]), "+f"(d[84]), "+f"(d[85]), "+f"(d[86]), "+f"(d[87]),
      "+f"(d[88]), "+f"(d[89]), "+f"(d[90]), "+f"(d[91]), "+f"(d[92]), "+f"(d[93]), "+f"(d[94]), "+f"(d[95]),
      "+f"(d[96]), "+f"(d[97]), "+f"(d[98]), "+f"(d[99]), "+f"(d[100]), "+f"(d[101]), "+f"(d[102]), "+f"(d[103]),
      "+f"(d[104]), "+f"(d[105]), "+f"(d[106]), "+f"(d[107]), "+f"(d[108]), "+f"(d[109]), "+f"(d[110]), "+f"(d[111]),
      "+f"(d[112]), "+f"(d[113]), "+f"(d[114]), "+f"(d[115]), "+f"(d[116]), "+f"(d[117]), "+f"(d[118]), "+f"(d[119]),
      "+f"(d[120]), "+f"(d[121]), "+f"(d[122]), "+f"(d[123]), "+f"(d[124]), "+f"(d[125]), "+f"(d[126]), "+f"(d[127])
    : "l"(da), "l"(db), "r"(sd));
}
__device__ __forceinline__ void wgmma_ss_n64(float (&d)[32], uint64_t da, uint64_t db, int sd) {
  asm volatile("{\n.reg .pred p;\nsetp.ne.b32 p, %34, 0;\n"
    "wgmma.mma_async.sync.aligned.m64n64k16.f32.bf16.bf16 "
    "{%0, %1, %2, %3, %4, %5, %6, %7, %8, %9, %10, %11, %12, %13, %14, %15, "
    "%16, %17, %18, %19, %20, %21, %22, %23, %24, %25, %26, %27, %28, %29, %30, %31}, "
    "%32, %33, p, 1, 1, 0, 0;\n}"
    : "+f"(d[0]), "+f"(d[1]), "+f"(d[2]), "+f"(d[3]), "+f"(d[4]), "+f"(d[5]), "+f"(d[6]), "+f"(d[7]),
      "+f"(d[8]), "+f"(d[9]), "+f"(d[10]), "+f"(d[11]), "+f"(d[12]), "+f"(d[13]), "+f"(d[14]), "+f"(d[15]),
      "+f"(d[16]), "+f"(d[17]), "+f"(d[18]), "+f"(d[19]), "+f"(d[20]), "+f"(d[21]), "+f"(d[22]), "+f"(d[23]),
      "+f"(d[24]), "+f"(d[25]), "+f"(d[26]), "+f"(d[27]), "+f"(d[28]), "+f"(d[29]), "+f"(d[30]), "+f"(d[31])
    : "l"(da), "l"(db), "r"(sd));
}
__device__ __forceinline__ void wgmma_rs_n256_tb(float (&d)[128], uint32_t a0, uint32_t a1, uint32_t a2, uint32_t a3, uint64_t db, int sd) {
  asm volatile("{\n.reg .pred p;\nsetp.ne.b32 p, %133, 0;\n"
    "wgmma.mma_async.sync.aligned.m64n256k16.f32.bf16.bf16 "
    "{%0, %1, %2, %3, %4, %5, %6, %7, %8, %9, %10, %11, %12, %13, %14, %15, "
    "%16, %17, %18, %19, %20, %21, %22, %23, %24, %25, %26, %27, %28, %29, %30, %31, "
    "%32, %33, %34, %35, %36, %37, %38, %39, %40, %41, %42, %43, %44, %45, %46, %47, "
    "%48, %49, %50, %51, %52, %53, %54, %55, %56, %57, %58, %59, %60, %61, %62, %63, "
    "%64, %65, %66, %67, %68, %69, %70, %71, %72, %73, %74, %75, %76, %77, %78, %79, "
    "%80, %81, %82, %83, %84, %85, %86, %87, %88, %89, %90, %91, %92, %93, %94, %95, "
    "%96, %97, %98, %99, %100, %101, %102, %103, %104, %105, %106, %107, %108, %109, %110, %111, "
    "%112, %113, %114, %115, %116, %117, %118, %119, %120, %121, %122, %123, %124, %125, %126, %127}, "
    "{%128, %129, %130, %131}, %132, p, 1, 1, 1;\n}"
    : "+f"(d[0]), "+f"(d[1]), "+f"(d[2]), "+f"(d[3]), "+f"(d[4]), "+f"(d[5]), "+f"(d[6]), "+f"(d[7]),
      "+f"(d[8]), "+f"(d[9]), "+f"(d[10]), "+f"(d[11]), "+f"(d[12]), "+f"(d[13]), "+f"(d[14]), "+f"(d[15]),
      "+f"(d[16]), "+f"(d[17]), "+f"(d[18]), "+f"(d[19]), "+f"(d[20]), "+f"(d[21]), "+f"(d[22]), "+f"(d[23]),
      "+f"(d[24]), "+f"(d[25]), "+f"(d[26]), "+f"(d[27]), "+f"(d[28]), "+f"(d[29]), "+f"(d[30]), "+f"(d[31]),
      "+f"(d[32]), "+f"(d[33]), "+f"(d[34]), "+f"(d[35]), "+f"(d[36]), "+f"(d[37]), "+f"(d[38]), "+f"(d[39]),
      "+f"(d[40]), "+f"(d[41]), "+f"(d[42]), "+f"(d[43]), "+f"(d[44]), "+f"(d[45]), "+f"(d[46]), "+f"(d[47]),
      "+f"(d[48]), "+f"(d[49]), "+f"(d[50]), "+f"(d[51]), "+f"(d[52]), "+f"(d[53]), "+f"(d[54]), "+f"(d[55]),
      "+f"(d[56]), "+f"(d[57]), "+f"(d[58]), "+f"(d[59]), "+f"(d[60]), "+f"(d[61]), "+f"(d[62]), "+f"(d[63]),
      "+f"(d[64]), "+f"(d[65]), "+f"(d[66]), "+f"(d[67]), "+f"(d[68]), "+f"(d[69]), "+f"(d[70]), "+f"(d[71]),
      "+f"(d[72]), "+f"(d[73]), "+f"(d[74]), "+f"(d[75]), "+f"(d[76]), "+f"(d[77]), "+f"(d[78]), "+f"(d[79]),
      "+f"(d[80]), "+f"(d[81]), "+f"(d[82]), "+f"(d[83]), "+f"(d[84]), "+f"(d[85]), "+f"(d[86]), "+f"(d[87]),
      "+f"(d[88]), "+f"(d[89]), "+f"(d[90]), "+f"(d[91]), "+f"(d[92]), "+f"(d[93]), "+f"(d[94]), "+f"(d[95]),
      "+f"(d[96]), "+f"(d[97]), "+f"(d[98]), "+f"(d[99]), "+f"(d[100]), "+f"(d[101]), "+f"(d[102]), "+f"(d[103]),
      "+f"(d[104]), "+f"(d[105]), "+f"(d[106]), "+f"(d[107]), "+f"(d[108]), "+f"(d[109]), "+f"(d[110]), "+f"(d[111]),
      "+f"(d[112]), "+f"(d[113]), "+f"(d[114]), "+f"(d[115]), "+f"(d[116]), "+f"(d[117]), "+f"(d[118]), "+f"(d[119]),
      "+f"(d[120]), "+f"(d[121]), "+f"(d[122]), "+f"(d[123]), "+f"(d[124]), "+f"(d[125]), "+f"(d[126]), "+f"(d[127])
    : "r"(a0), "r"(a1), "r"(a2), "r"(a3), "l"(db), "r"(sd));
}
__device__ __forceinline__ void wgmma_rs_n64_tb(float (&d)[32], uint32_t a0, uint32_t a1, uint32_t a2, uint32_t a3, uint64_t db, int sd) {
  asm volatile("{\n.reg .pred p;\nsetp.ne.b32 p, %37, 0;\n"
    "wgmma.mma_async.sync.aligned.m64n64k16.f32.bf16.bf16 "
    "{%0, %1, %2, %3, %4, %5, %6, %7, %8, %9, %10, %11, %12, %13, %14, %15, "
    "%16, %17, %18, %19, %20, %21, %22, %23, %24, %25, %26, %27, %28, %29, %30, %31}, "
    "{%32, %33, %34, %35}, %36, p, 1, 1, 1;\n}"
    : "+f"(d[0]), "+f"(d[1]), "+f"(d[2]), "+f"(d[3]), "+f"(d[4]), "+f"(d[5]), "+f"(d[6]), "+f"(d[7]),
      "+f"(d[8]), "+f"(d[9]), "+f"(d[10]), "+f"(d[11]), "+f"(d[12]), "+f"(d[13]), "+f"(d[14]), "+f"(d[15]),
      "+f"(d[16]), "+f"(d[17]), "+f"(d[18]), "+f"(d[19]), "+f"(d[20]), "+f"(d[21]), "+f"(d[22]), "+f"(d[23]),
      "+f"(d[24]), "+f"(d[25]), "+f"(d[26]), "+f"(d[27]), "+f"(d[28]), "+f"(d[29]), "+f"(d[30]), "+f"(d[31])
    : "r"(a0), "r"(a1), "r"(a2), "r"(a3), "l"(db), "r"(sd));
}
__device__ __forceinline__ void wgmma_rs_n32(float (&d)[16], uint32_t a0, uint32_t a1, uint32_t a2, uint32_t a3, uint64_t db, int sd) {
  asm volatile("{\n.reg .pred p;\nsetp.ne.b32 p, %21, 0;\n"
    "wgmma.mma_async.sync.aligned.m64n32k16.f32.bf16.bf16 "
    "{%0, %1, %2, %3, %4, %5, %6, %7, %8, %9, %10, %11, %12, %13, %14, %15}, "
    "{%16, %17, %18, %19}, %20, p, 1, 1, 0;\n}"
    : "+f"(d[0]), "+f"(d[1]), "+f"(d[2]), "+f"(d[3]), "+f"(d[4]), "+f"(d[5]), "+f"(d[6]), "+f"(d[7]),
      "+f"(d[8]), "+f"(d[9]), "+f"(d[10]), "+f"(d[11]), "+f"(d[12]), "+f"(d[13]), "+f"(d[14]), "+f"(d[15])
    : "r"(a0), "r"(a1), "r"(a2), "r"(a3), "l"(db), "r"(sd));
}
__device__ __forceinline__ void wgmma_rs_n64(float (&d)[32], uint32_t a0, uint32_t a1, uint32_t a2, uint32_t a3, uint64_t db, int sd) {
  asm volatile("{\n.reg .pred p;\nsetp.ne.b32 p, %37, 0;\n"
    "wgmma.mma_async.sync.aligned.m64n64k16.f32.bf16.bf16 "
    "{%0, %1, %2, %3, %4, %5, %6, %7, %8, %9, %10, %11, %12, %13, %14, %15, "
    "%16, %17, %18, %19, %20, %21, %22, %23, %24, %25, %26, %27, %28, %29, %30, %31}, "
    "{%32, %33, %34, %35}, %36, p, 1, 1, 0;\n}"
    : "+f"(d[0]), "+f"(d[1]), "+f"(d[2]), "+f"(d[3]), "+f"(d[4]), "+f"(d[5]), "+f"(d[6]), "+f"(d[7]),
      "+f"(d[8]), "+f"(d[9]), "+f"(d[10]), "+f"(d[11]), "+f"(d[12]), "+f"(d[13]), "+f"(d[14]), "+f"(d[15]),
      "+f"(d[16]), "+f"(d[17]), "+f"(d[18]), "+f"(d[19]), "+f"(d[20]), "+f"(d[21]), "+f"(d[22]), "+f"(d[23]),
      "+f"(d[24]), "+f"(d[25]), "+f"(d[26]), "+f"(d[27]), "+f"(d[28]), "+f"(d[29]), "+f"(d[30]), "+f"(d[31])
    : "r"(a0), "r"(a1), "r"(a2), "r"(a3), "l"(db), "r"(sd));
}

__device__ __forceinline__ uint4 lds16(uint32_t a) {
  uint4 v; asm volatile("ld.shared.v4.u32 {%0, %1, %2, %3}, [%4];" : "=r"(v.x), "=r"(v.y), "=r"(v.z), "=r"(v.w) : "r"(a) : "memory"); return v;
}
__device__ __forceinline__ void sts16(uint32_t a, uint32_t x, uint32_t y, uint32_t z, uint32_t w) {
  asm volatile("st.shared.v4.u32 [%0], {%1, %2, %3, %4};" :: "r"(a), "r"(x), "r"(y), "r"(z), "r"(w) : "memory");
}
__device__ __forceinline__ uint32_t lds4(uint32_t a) { uint32_t v; asm volatile("ld.shared.u32 %0, [%1];" : "=r"(v) : "r"(a) : "memory"); return v; }
__device__ __forceinline__ uint32_t lds4v(uint32_t a) { uint32_t v; asm volatile("ld.volatile.shared.u32 %0, [%1];" : "=r"(v) : "r"(a) : "memory"); return v; }
__device__ __forceinline__ uint32_t bmul(uint32_t a, uint32_t b) { uint32_t r; asm("mul.rn.bf16x2 %0, %1, %2;" : "=r"(r) : "r"(a), "r"(b)); return r; }
__device__ __forceinline__ uint32_t badd(uint32_t a, uint32_t b) { uint32_t r; asm("add.rn.bf16x2 %0, %1, %2;" : "=r"(r) : "r"(a), "r"(b)); return r; }

__device__ __forceinline__ void ldsm4(uint32_t (&r)[4], uint32_t a) {
  asm volatile("ldmatrix.sync.aligned.m8n8.x4.shared.b16 {%0, %1, %2, %3}, [%4];" : "=r"(r[0]), "=r"(r[1]), "=r"(r[2]), "=r"(r[3]) : "r"(a) : "memory");
}
__device__ __forceinline__ uint32_t transpose8(uint32_t a) { uint32_t d; asm volatile("movmatrix.sync.aligned.m8n8.trans.b16 %0, %1;" : "=r"(d) : "r"(a)); return d; }

__device__ __forceinline__ void mma16816(float (&d)[4], const uint32_t (&a)[4], uint32_t b0, uint32_t b1) {
  asm volatile("mma.sync.aligned.m16n8k16.row.col.f32.bf16.bf16.f32 {%0, %1, %2, %3}, {%4, %5, %6, %7}, {%8, %9}, {%0, %1, %2, %3};"
               : "+f"(d[0]), "+f"(d[1]), "+f"(d[2]), "+f"(d[3]) : "r"(a[0]), "r"(a[1]), "r"(a[2]), "r"(a[3]), "r"(b0), "r"(b1));
}

#define EXP_SIDE 0
#define SIDE_AHEAD 3
#define ZERO_RD 4
#define CTX_SPLIT 8
#define CONV_EARLY 8
#define CONV_FENCE 12
#define CTX_LD 8
#define PEEK_JJ 7
#define PF_CTX 0
#define KV_ORDER 3
#define QFIRST 0
#define UNICAST 2
#define PF_MAPS 3
#define SINGLE0 2
#define LAST_DIRECT 1
#define HAND_NOW 1
#define CONV_ARRIVE 13
#define ARRIVE_KK 12
#define SIDE_DELAY_NS 4000
#define KVH(h) (h)
#define HEAD_MAP 2
#define EARLY_LD 1
constexpr int RED_BAR = 6;
constexpr int CV_BAR = 5;
constexpr int PP_BAR = 3;
template <int V> struct Int { static constexpr int value = V; };
struct Ring {
  uint32_t slot, phase;
  __device__ __forceinline__ void next() { if (++slot == NSLOT) { slot = 0; phase ^= 1; } }
};
__device__ __forceinline__ uint32_t bar_addr(uint32_t sb, uint32_t i) { return sb + BARS + 8 * i; }

__device__ __forceinline__ int q_tile(int h, int j, int which) { return ((h < 8) == (which == 0)) ? 15 - j : j; }

constexpr int T_QB = QFIRST ? 0 : 4, IT_KV = QFIRST ? 7 : 0, IT_QB = QFIRST ? 0 : 64;
constexpr int KV_ISV  = KV_ORDER == 0 ? 0xC : KV_ORDER == 1 ? 0xA : KV_ORDER == 2 ? 0x6 : KV_ORDER == 3 ? 0xA : 0xC;
constexpr int KV_PART = KV_ORDER == 0 ? 0xA : KV_ORDER == 1 ? 0xC : KV_ORDER == 2 ? 0xC : KV_ORDER == 3 ? 0x3 : KV_ORDER == 4 ? 0x5 : 0x9;
constexpr int LAST_PART = KV_PART >> 3;
constexpr int T_FIRST = (((KV_PART >> 2) & 1) != LAST_PART ? 3 : 2) + QFIRST;
constexpr int T_LAST = 4 + QFIRST;
__device__ __forceinline__ int p1_isv(int n) { return (KV_ISV >> n) & 1; }
__device__ __forceinline__ int att_head(int h, int which) { return (h & 7) + 8 * which; }
__device__ __forceinline__ int p1_head(int h, int n) { return (h & 7) + 8 * ((KV_PART >> n) & 1); }
__device__ __forceinline__ int p1_rows(int h, int j, int n) { return q_tile(h, j, 0); }
#define KV_FLAG(h) ((h) & 7)
#define KV_COUNT 32
#define F_PART1 (2 * own - 1)

__device__ __forceinline__ void load_tile4(uint32_t dst, const CUtensorMap* m, uint32_t full, int row, int blk0, int rank, bool shared, uint64_t pl = POL_NORMAL) {
  if (shared) {
    tma_ld3_mc(dst + rank * 16384, m, full, 0, row, blk0 + 2 * rank, pl);
  } else {
    tma_ld3(dst, m, full, 0, row, blk0, pl);
    tma_ld3(dst + 16384, m, full, 0, row, blk0 + 2, pl);
  }
}
__device__ __forceinline__ void producer_main(const Params& p, uint32_t sb, int h, int j) {
  const int rank = j & 1;
  Ring r{EARLY_LD, 0};
  auto wait_slot = [&]() { mbar_wait(bar_addr(sb, B_EMPTY + r.slot), r.phase ^ 1); };
  auto load_a = [&](int it, uint32_t dst, uint32_t full) {
    const unsigned u = it - IT_KV;
    if (u < 64) tma_ld2(dst, &p.ckv, full, (u & 15) * 64, p1_rows(h, j, u >> 4) * 128, pol((HINTS & 2) && u >= 48));
    else tma_ld2(dst, &p.x, full, (it < 71 ? it - IT_QB : it - 71) * 64, q_tile(h, j, it < 71) * 128, pol((HINTS & 64) && it >= 71));
  };
  uint32_t prev = 0;
#pragma unroll 1
  for (int it = EARLY_LD; it < P1_STEPS; it++) {
    wait_slot();
    if (it > EARLY_LD && it <= P1_XS) load_a(it - 1, sb + QREG + ((it - 1) & 3) * 16384, prev);
    const uint32_t full = bar_addr(sb, B_FULL + r.slot), dst = sb + r.slot * SLOT;
    mbar_expect_tx(full, it < P1_XS ? 49152 : 32768);
    const unsigned u = it - IT_KV;
    if (u < 64) load_tile4(dst, p1_isv(u >> 4) ? &p.wuv : &p.wuk, full, (u & 15) * 64, p1_head(h, u >> 4) * 4, rank, !(UNICAST & 2), pol(HINTS & 1));
    else load_tile4(dst, &p.wq, full, (it < 71 ? it - IT_QB : it - 71) * 64, att_head(h, it < 71) * 4, rank, !(UNICAST & 2), pol((HINTS & 4) && it >= 71));
    prev = full;
    r.next();
    if (it == P1_XS) {
      wait_slot();
      const uint32_t f2 = bar_addr(sb, B_FULL + r.slot);
      mbar_expect_tx(f2, 32768);
      load_a(P1_XS, sb + r.slot * SLOT, f2);
      load_a(P1_XS + 1, sb + r.slot * SLOT + 16384, f2);
      r.next();
    }
  }
  const int qa = q_tile(h, j, 0), na = 2 * qa + 2, own = 2 * (qa & ~1) + 2;
#pragma unroll 1
  for (int f = 0; f < 68; f++) {
    const bool isK = (f == 0) || ((f & 1) && f < 67);
    const int i = isK ? (f + 1) >> 1 : (f - 1) >> 1, which = i >= na;
    if (f == 0 || f == F_PART1) mbar_wait(bar_addr(sb, B_KVOK + (f & 1)), 0);
    wait_slot();
    const uint32_t full = bar_addr(sb, B_FULL + r.slot);
    mbar_expect_tx(full, 32768);
    const uint32_t src = (uint32_t)(((isK ? 0 : NH) + KVH(att_head(h, which))) * 32 + (which ? 33 - i : i)) * 32768;
    const uint64_t pl = pol(which ? (HINTS & 32) : (HINTS & 8));
    if (!(UNICAST & 1) && (i & ~1) != own) bulk_ld_mc(sb + r.slot * SLOT + rank * 16384, at<uint8_t>(g_kv, src + rank * 16384), 16384, full, pl);
    else bulk_ld_p(sb + r.slot * SLOT, at<uint8_t>(g_kv, src), 32768, full, pl);
    r.next();
  }
#pragma unroll 1
  for (int f = 0; f < 14; f++) {
    const int ch = f < 4 ? f & 1 : f >> 1, par = f < 4 ? f >> 1 : f & 1;
    wait_slot();
    const uint32_t full = bar_addr(sb, B_FULL + r.slot);
    mbar_expect_tx(full, 32768);
    if (UNICAST & 4) {
      tma_ld5(sb + r.slot * SLOT, &p.wo, full, ch * 64, (par ? att_head(h ^ 8, 0) : att_head(h, 1)) * 8, pol(HINTS & 16));
      tma_ld5(sb + r.slot * SLOT + 16384, &p.wo, full, ch * 64, (par ? att_head(h ^ 8, 0) : att_head(h, 1)) * 8 + 4, pol(HINTS & 16));
    } else {
      tma_ld5_mc(sb + r.slot * SLOT + rank * 16384, &p.wo, full, ch * 64, (par ? att_head(h ^ 8, 0) : att_head(h, 1)) * 8 + rank * 4, pol(HINTS & 16));
    }
    r.next();
  }
}

__device__ __forceinline__ void helper_main(const Params& p, uint32_t sb, int h, int j, int w) {
  const unsigned epoch = load_epoch();
  const int cta = h * 8 + j, qb = q_tile(h, j, 1);
  const uint32_t qreg = sb + QREG + w * 32768, qfull = bar_addr(sb, B_QFULL + w);
  auto acquire = [&]() {
    flag_wait(flag_at(g_flags.kv_ready, KV_FLAG(h) * 2 + w), KV_COUNT, epoch);
    fence_async_all();
    mbar_arrive(bar_addr(sb, B_KVOK + w));
  };
  if (QFIRST) mbar_wait(bar_addr(sb, B_ST_Q + w), 0);
  mbar_wait(bar_addr(sb, B_ST_KV + w), 0);
  flag_signal(flag_at(g_flags.kv_ready, KV_FLAG(h) * 2 + (LAST_PART ^ 1)));
  if (w != LAST_PART) acquire();
  mbar_wait(bar_addr(sb, B_ST_KV + 2 + w), 0);
  flag_signal(flag_at(g_flags.kv_ready, KV_FLAG(h) * 2 + LAST_PART));
  const bool late = false;
  if (w == LAST_PART && !late) acquire();
  if (!QFIRST) { mbar_wait(bar_addr(sb, B_ST_Q + w), 0); asm volatile("fence.release.gpu;" ::: "memory"); }
  fence_async_all();
  mbar_wait(bar_addr(sb, B_QFREE + w), 0);
  mbar_expect_tx(qfull, 32768);
  bulk_ld(qreg, at<uint8_t>(g_qc, (cta * 2 + w) * 32768), 32768, qfull);
  if (w == LAST_PART && late) acquire();
  auto publish = [&]() { mbar_wait(bar_addr(sb, B_ST_CTX + w), 0); flag_signal(flag_at(g_flags.ctx_ready, cta * 2 + w)); };
  if (qb >= 8) publish();
  flag_wait(flag_at(g_flags.ctx_ready, (cta ^ 64) * 2 + (w ^ 1)), 1, epoch);
  mbar_arrive(bar_addr(sb, B_CTXOK + w));
  mbar_arrive(bar_addr(sb, B_DONE));
  if (qb < 8) publish();
  flag_wait(flag_at(g_flags.zero_ready, qb), 8, epoch);
  fence_async_all();
#pragma unroll 1
  for (int ch = 0; ch < (LAST_DIRECT ? 6 : 7); ch++) {
    mbar_wait(bar_addr(sb, B_S2_FULL + w * 4 + (ch & 3)), ch >> 2);
    tma_red2(&p.o, qreg + (ch & 3) * 8192, DA + ch * 64, qb * 128 + (w ^ 1) * 64);
    bulk_commit();
    if (ch < 3) { bulk_wait_read(); mbar_arrive(bar_addr(sb, B_S2_EMPTY + w * 4 + ch)); }
  }
  bulk_wait_read();
  GT(48 + w);
}

__device__ __forceinline__ void store_block(uint32_t base, uint32_t lanebase, const uint32_t (&pk)[16]) {
#pragma unroll
  for (int J = 0; J < 8; J += 2) stsm4(base + (lanebase ^ (J << 4)), pk[2 * J], pk[2 * J + 1], pk[2 * J + 2], pk[2 * J + 3]);
}
__device__ __forceinline__ void pack_chunks(uint32_t (&pk)[64], const float (&acc)[128]) {
#pragma unroll
  for (int i = 0; i < 64; i++) { const int e = 16 * (i >> 3) + 4 * (i & 3) + 2 * ((i >> 2) & 1); pk[i] = pack_bf16(acc[e], acc[e + 1]); }
}
__device__ __forceinline__ uint32_t chunk_off() { const uint32_t t = fresh_tid(); return (t & 96) * 32 + (t & 28) * 16 + (((t ^ (t >> 3)) & 3) << 4); }
__device__ __forceinline__ void warp_arrive(uint32_t bar, int lane) { __syncwarp(); if (lane == 0) mbar_arrive(bar); }

__device__ __forceinline__ void consumer_main(const Params& p, uint32_t sb, int h, int j, int w, int wq) {
  const int lane = threadIdx.x & 31;
  const int rank = j & 1;

  auto turn_begin = [&]() { named_sync(PP_BAR + w, 256); };
  auto turn_end = [&]() { named_arrive(PP_BAR + (w ^ 1), 256); };
  Ring r{0, 0};
  auto take = [&](uint32_t ready = 0) { const uint32_t sl = r.slot; mbar_wait_unless(ready, bar_addr(sb, B_FULL + sl), r.phase); r.next(); return sl; };
  uint32_t rdy0 = 0, rdy1 = 0;
  auto peek2 = [&]() { Ring q = r; rdy0 = mbar_test(bar_addr(sb, B_FULL + q.slot), q.phase); q.next(); rdy1 = mbar_test(bar_addr(sb, B_FULL + q.slot), q.phase); };
  auto give = [&](uint32_t sl) {
    if (UNICAST & 8) { if (lane == 0) mbar_arrive(bar_addr(sb, B_EMPTY + sl)); }
    else if (lane < 2) mbar_arrive_remote(bar_addr(sb, B_EMPTY + sl), rank ^ lane);
  };
  float acc[128];
#pragma unroll
  for (int i = 0; i < 128; i++) acc[i] = 0.f;
  uint32_t pk[64];
#pragma unroll
  for (int i = 0; i < 64; i++) pk[i] = 0;
  reg_fence(acc);
  reg_fence(pk);
  cluster_wait();
  TS(0);
  const uint32_t qreg = sb + QREG + w * 32768;
  {
    uint32_t xs = 0;
    uint4* row = nullptr;
    int it = 0;
#pragma unroll 1
    for (int t = 0; t < 6; t++) {
      const bool isq = t == T_QB || t == 5;
      const uint32_t abase = sb + QREG + (w ^ (t == T_QB)) * 8192;
#pragma unroll 1
      for (int u = 0, end = it + (isq ? 7 : 16); it < end; u++) {
        const bool two = !(isq && u == 1) && it >= SINGLE0, last = it == P1_XS;
        const uint32_t w0 = take(rdy0);
        TSC(1, it == 0);
        if (last) { xs = take(rdy1); rdy1 = 0; }
        const uint32_t xb = sb + xs * SLOT + w * 8192;
        const uint64_t da = desc_k(last ? xb : abase + (it & 3) * 16384), db = desc_mn(sb + w0 * SLOT);
        turn_begin();
        wg_fence();
#pragma unroll
        for (int kk = 0; kk < 4; kk++) wgmma_ss_n256_tb(acc, desc_add(da, kk * 32), desc_add(db, kk * 2048), (u | kk) != 0);
        wg_commit();
        uint32_t w1 = w0;
        if (two) {
          w1 = take(rdy1);
          const uint64_t da1 = desc_k(last ? xb + 16384 : abase + ((it + 1) & 3) * 16384), db1 = desc_mn(sb + w1 * SLOT);
          wg_fence();
#pragma unroll
          for (int kk = 0; kk < 4; kk++) wgmma_ss_n256_tb(acc, desc_add(da1, kk * 32), desc_add(db1, kk * 2048), 1);
          wg_commit();
          turn_end();
          wg_wait<1>();
          give(w0);
        } else {
          turn_end();
        }
        if (t > 0) {
          uint32_t m = isq ? 0xC0380403u >> (8 * u) : 1u << u;
          asm volatile("" : "+r"(m));
#pragma unroll
          for (int i = 0; i < 16; i++)
            if (m & (1u << (i >> 1))) row[(i >> 1) * 256 + (i & 1) * 32] = make_uint4(pk[4 * i], pk[4 * i + 1], pk[4 * i + 2], pk[4 * i + 3]);
        }
        peek2();
        wg_wait<0>();
        give(w1);
        it += 1 + two;
      }
      reg_fence(acc);
      if (t == T_QB + 1 || t == T_FIRST || t == T_LAST)
        warp_arrive(bar_addr(sb, (t == T_QB + 1 ? B_ST_Q : t == T_LAST ? B_ST_KV + 2 : B_ST_KV) + w), lane);
      pack_chunks(pk, acc);
      const int n = t - QFIRST;
      row = at<uint4>(t != T_QB ? (const void*)g_kv : (const void*)g_qc, chunk_off() +
                      (t != T_QB ? (uint32_t)((p1_isv(n) * NH + KVH(p1_head(h, n))) * 32 + p1_rows(h, j, n) * 2 + w) : (uint32_t)((h * 8 + j) * 2 + w)) * 32768);
      TS(2 + t);
    }
    give(xs);
    const uint32_t qa = qreg + chunk_off();
#pragma unroll
    for (int i = 0; i < 16; i++) sts16(qa + (i >> 1) * 4096 + (i & 1) * 512, pk[4 * i], pk[4 * i + 1], pk[4 * i + 2], pk[4 * i + 3]);
    fence_async_smem();
  }
  TS(8);

  constexpr float SC = 0.0625f * 1.4426950408889634f;
#pragma unroll 1
  for (int which = 0; which < 2; which++) {
    float s[32];
#pragma unroll
    for (int i = 0; i < 32; i++) s[i] = 0.f;
    uint32_t pa[16], pb[16];
    float m0 = 0.f, m1 = 0.f, l0 = 0.f, l1 = 0.f;
    const uint64_t dq = desc_64(qreg);
    uint64_t dk = 0, dqq = 0, dv = 0;
    auto prep_qk = [&](uint32_t kaddr) { dk = desc_64(kaddr); dqq = dq + (kaddr >> 31); asm volatile("" : "+l"(dk), "+l"(dqq)); };
    auto prep_pv = [&](uint32_t vaddr) { dv = desc_64(vaddr); asm volatile("" : "+l"(dv)); };
    auto issue_qk = [&]() {
#pragma unroll
      for (int kk = 0; kk < 16; kk++)
        wgmma_ss_n64(s, desc_add(dqq, (kk >> 1) * 4096 + (kk & 1) * 32), desc_add(dk, (kk >> 1) * 4096 + (kk & 1) * 32), kk != 0);
    };
    auto issue_pv = [&](int accumulate) {
#pragma unroll
      for (int kk = 0; kk < 4; kk++)
        wgmma_rs_n256_tb(acc, pa[4 * kk], pa[4 * kk + 1], pa[4 * kk + 2], pa[4 * kk + 3], desc_add(dv, kk * 1024), accumulate | kk);
    };
    auto mask_diag = [&]() {
      const int d = 16 * wq + (lane >> 2) - 2 * (lane & 3);
#pragma unroll
      for (int jj = 0; jj < 8; jj++) {
        if (8 * jj > d)     { s[4 * jj] = -INFINITY;     if (jj < 7) s[4 * jj + 6] = -INFINITY; }
        if (8 * jj + 1 > d) { s[4 * jj + 1] = -INFINITY; if (jj < 7) s[4 * jj + 7] = -INFINITY; }
      }
    };
    float a0, a1;
    auto softmax = [&]() -> bool {
      float x0 = fmaxf(s[0], s[1]), x1 = fmaxf(s[2], s[3]);
#pragma unroll
      for (int jj = 1; jj < 8; jj++) {
        x0 = fmaxf(x0, fmaxf(s[4 * jj], s[4 * jj + 1]));
        x1 = fmaxf(x1, fmaxf(s[4 * jj + 2], s[4 * jj + 3]));
      }
      x0 = fmaxf(x0, __shfl_xor_sync(0xffffffffu, x0, 1));
      x1 = fmaxf(x1, __shfl_xor_sync(0xffffffffu, x1, 1));
      x0 = fmaxf(x0, __shfl_xor_sync(0xffffffffu, x0, 2));
      x1 = fmaxf(x1, __shfl_xor_sync(0xffffffffu, x1, 2));
      const bool grow = __any_sync(0xffffffffu, fmaxf(x0 - m0, x1 - m1) * SC > 8.f);
      if (grow) {
        x0 = fmaxf(x0, m0); x1 = fmaxf(x1, m1);
        a0 = ex2((m0 - x0) * SC); a1 = ex2((m1 - x1) * SC);
        m0 = x0; m1 = x1;
        l0 *= a0; l1 *= a1;
      }
      const float b0 = -m0 * SC, b1 = -m1 * SC;
      float t0 = 0.f, t1 = 0.f, t2 = 0.f, t3 = 0.f;
#pragma unroll
      for (int jj = 0; jj < 8; jj++) {
        s[4 * jj]     = ex2(fmaf(s[4 * jj], SC, b0));
        s[4 * jj + 1] = ex2(fmaf(s[4 * jj + 1], SC, b0));
        s[4 * jj + 2] = ex2(fmaf(s[4 * jj + 2], SC, b1));
        s[4 * jj + 3] = ex2(fmaf(s[4 * jj + 3], SC, b1));
        t0 += s[4 * jj]; t1 += s[4 * jj + 1]; t2 += s[4 * jj + 2]; t3 += s[4 * jj + 3];
      }
      l0 += t0 + t1; l1 += t2 + t3;
      return grow;
    };
    auto softmax_fast = [&](uint32_t (&pp)[16], auto first, auto hook) -> bool {
      const float b0 = -m0 * SC, b1 = -m1 * SC;
      float t0 = 0.f, t1 = 0.f, t2 = 0.f, t3 = 0.f;
#pragma unroll
      for (int jj = 0; jj < 8; jj++) {
        const float e0 = ex2(fmaf(s[4 * jj], SC, b0)), e1 = ex2(fmaf(s[4 * jj + 1], SC, b0));
        const float e2 = ex2(fmaf(s[4 * jj + 2], SC, b1)), e3 = ex2(fmaf(s[4 * jj + 3], SC, b1));
        hook(jj, e0);
        pp[2 * jj] = pack_bf16(e0, e1); pp[2 * jj + 1] = pack_bf16(e2, e3);
        if (jj == 0) { t0 = e0; t1 = e1; t2 = e2; t3 = e3; } else { t0 += e0; t1 += e1; t2 += e2; t3 += e3; }
      }
      t0 += t1; t2 += t3;
      bool redo = __any_sync(0xffffffffu, !(t0 + t2 <= 16777216.f));
      if (decltype(first)::value) {
        uint32_t u0 = __ballot_sync(0xffffffffu, t0 >= 1.52587890625e-05f), u1 = __ballot_sync(0xffffffffu, t2 >= 1.52587890625e-05f);
        u0 |= u0 >> 1; u1 |= u1 >> 1;
        redo |= (((u0 | (u0 >> 2)) & (u1 | (u1 >> 2))) & 0x11111111u) != 0x11111111u;
      }
      if (!redo) { l0 += t0; l1 += t2; }
      return redo;
    };
    auto rescale = [&]() {
#pragma unroll
      for (int i = 0; i < 32; i++) { acc[4 * i] *= a0; acc[4 * i + 1] *= a0; acc[4 * i + 2] *= a1; acc[4 * i + 3] *= a1; }
    };
    auto to_p = [&](uint32_t (&pp)[16]) {
#pragma unroll
      for (int i = 0; i < 16; i++) pp[i] = pack_bf16(s[2 * i], s[2 * i + 1]);
    };
    auto q_free = [&]() { if (lane == 0) mbar_arrive(bar_addr(sb, B_QFREE + w)); };

    const int n = 2 * q_tile(h, j, which) + 1 + (w ^ which);
    uint32_t ks = take(rdy0);
    TS(9 + 5 * which);
    prep_qk(sb + ks * SLOT);
    turn_begin();
    TS(20 + 10 * which);
    wg_fence();
    issue_qk();
    wg_commit();
    turn_end();
    if (which == 1) give(take(rdy1));
    TS(22 + 10 * which);
    wg_wait<0>();
    TS(21 + 10 * which);
    reg_fence(s);
    give(ks);
    if (which == 0 && n == 1) q_free();
    if (which == 1 || n == 1) mask_diag();
    {
      const uint4* dst = at<uint4>(g_qc, (uint32_t)((h * 8 + j) * 2 + w) * 32768 + (fresh_tid() & 127) * 16);
      const bool redo = softmax_fast(pa, Int<1>(), [&](int jj, float e) {
        if (jj == PEEK_JJ) peek2();
        const int i = CTX_SPLIT + jj;
        if (i < 16)
          asm volatile("{\n.reg .pred p, q;\nsetp.ne.b32 q, %6, 0;\nsetp.geu.and.f32 p, %5, 0fBF800000, q;\n@p st.global.v4.u32 [%0], {%1, %2, %3, %4};\n}"
                       :: "l"(dst + i * 128), "r"(pk[4 * (i & 15)]), "r"(pk[4 * (i & 15) + 1]), "r"(pk[4 * (i & 15) + 2]), "r"(pk[4 * (i & 15) + 3]), "f"(e), "r"(which) : "memory");
      });
      if (redo) {
        m0 = -INFINITY; m1 = -INFINITY;
        softmax();
        to_p(pa);
      }
    }
    if (which == 1) warp_arrive(bar_addr(sb, B_ST_CTX + w), lane);
    TS(10 + 5 * which);
#pragma unroll 1
    for (int jj = 1; jj < n; jj++) {
      ks = take(rdy0);
      const uint32_t vs = take(rdy1);
      prep_qk(sb + ks * SLOT);
      prep_pv(sb + vs * SLOT);
      TSC(23 + 10 * which, jj == 1);
      turn_begin();
      TSC(24 + 10 * which, jj == 1);
      TSC(26 + 10 * which, jj == n - 1);
      wg_fence();
      issue_qk();
      wg_commit();
      issue_pv(jj > 1);
      wg_commit();
      turn_end();
      wg_wait<1>();
      TSC(25 + 10 * which, jj == 1);
      reg_fence(s);
      give(ks);
      if (jj == n - 1 && which == 0) { q_free(); mask_diag(); }
      if (PF_CTX && which == 1 && jj == max(n - PF_CTX, 1)) {
        const uint8_t* src = at<const uint8_t>(g_qc, (uint32_t)(((h ^ 8) * 8 + j) * 2 + (w ^ 1)) * 32768 + (fresh_tid() & 127) * 128);
        asm volatile("prefetch.global.L2 [%0];" :: "l"(src));
        asm volatile("prefetch.global.L2 [%0];" :: "l"(src + 16384));
      }
      if (softmax_fast(pb, Int<0>(), [](int, float) {})) {
        wg_wait<0>();
        reg_fence(acc);
        if (softmax()) rescale();
        to_p(pb);
      }
      peek2();
      wg_wait<0>();
      reg_fence(acc);
      reg_fence(pa);
      give(vs);
#pragma unroll
      for (int i = 0; i < 16; i++) pa[i] = pb[i] | (vs >> 8);
    }
    TS(11 + 5 * which);
    if (which == 0) { give(take(rdy0)); rdy0 = rdy1; }
    {
      const uint32_t vs = take(rdy0);
      prep_pv(sb + vs * SLOT);
      TS(27 + 10 * which);
      turn_begin();
      TS(28 + 10 * which);
      wg_fence();
      issue_pv(n > 1);
      wg_commit();
      turn_end();
      l0 += __shfl_xor_sync(0xffffffffu, l0, 1); l1 += __shfl_xor_sync(0xffffffffu, l1, 1);
      l0 += __shfl_xor_sync(0xffffffffu, l0, 2); l1 += __shfl_xor_sync(0xffffffffu, l1, 2);
      asm("rcp.approx.ftz.f32 %0, %0;" : "+f"(l0));
      asm("rcp.approx.ftz.f32 %0, %0;" : "+f"(l1));
      peek2();
      if (which == 0) mbar_wait(bar_addr(sb, B_QFULL + w), 0);
      wg_wait<0>();
      reg_fence(acc);
      reg_fence(pa);
      give(vs);
    }
    TS(12 + 5 * which);
    {
      const uint4* dst = at<uint4>(g_qc, (uint32_t)((h * 8 + j) * 2 + w) * 32768 + (fresh_tid() & 127) * 16);
#pragma unroll
      for (int i = 0; i < 16; i++) {
        const int c = (i & 1) ? (i >> 1) + 8 : i >> 1;
        pk[4 * c]     = pack_bf16(acc[8 * c] * l0, acc[8 * c + 1] * l0);
        pk[4 * c + 1] = pack_bf16(acc[8 * c + 2] * l1, acc[8 * c + 3] * l1);
        pk[4 * c + 2] = pack_bf16(acc[8 * c + 4] * l0, acc[8 * c + 5] * l0);
        pk[4 * c + 3] = pack_bf16(acc[8 * c + 6] * l1, acc[8 * c + 7] * l1);
        if (c < CTX_SPLIT)
          asm volatile("{\n.reg .pred p;\nsetp.eq.b32 p, %5, 0;\n@p st.global.v4.u32 [%0], {%1, %2, %3, %4};\n}"
                       :: "l"(dst + c * 128), "r"(pk[4 * c]), "r"(pk[4 * c + 1]), "r"(pk[4 * c + 2]), "r"(pk[4 * c + 3]), "r"(which) : "memory");
      }
    }
    TS(13 + 5 * which);
  }

  {
    float oa[32], ob[32];
#pragma unroll
    for (int i = 0; i < 32; i++) { oa[i] = 0.f; ob[i] = 0.f; }
    uint32_t pk2[64];
    auto stage = [&](float (&o)[32], int ch) {
      reg_fence(o);
      uint32_t q[16];
#pragma unroll
      for (int i = 0; i < 16; i++) q[i] = pack_bf16(o[2 * i], o[2 * i + 1]);
      if (ch >= 4) mbar_wait(bar_addr(sb, B_S2_EMPTY + w * 4 + (ch & 3)), 0);
      store_block(qreg + (ch & 3) * 8192, lane_base16(), q);
    };
    auto hand_over = [&](int ch) {
      fence_async_smem();
      warp_arrive(bar_addr(sb, B_S2_FULL + w * 4 + (ch & 3)), lane);
    };
    uint32_t prev = 0;
    auto half = [&](int f, float (&o)[32], uint32_t (&a)[64], int accumulate) {
      const uint32_t sl = take(rdy0);
      const uint64_t d = desc_mn(sb + sl * SLOT);
      turn_begin();
      TS(40 + f);
      wg_fence();
#pragma unroll
      for (int kk = 0; kk < 16; kk++) {
        wgmma_rs_n64_tb(o, a[4 * kk], a[4 * kk + 1], a[4 * kk + 2], a[4 * kk + 3], desc_add(d, kk * 2048), accumulate | kk);
        if (kk == ARRIVE_KK && (f < 13 || w == 0)) turn_end();
      }
      wg_commit();
      if (f < 13) rdy0 = mbar_test(bar_addr(sb, B_FULL + r.slot), r.phase);
      wg_wait<1>();
      if (f >= 1 && f <= 9) give(prev);
      prev = sl;
    };
    auto load_ctx = [&](auto h0) {
      constexpr int I0 = decltype(h0)::value ? CTX_LD : 0, NL = decltype(h0)::value ? 16 - CTX_LD : CTX_LD;
      const uint4* src = at<const uint4>(g_qc, (uint32_t)(((h ^ 8) * 8 + j) * 2 + (w ^ 1)) * 32768 + (fresh_tid() & 127) * 16);
#pragma unroll
      for (int i = I0; i < I0 + NL; i++) { const uint4 v = __ldcg(src + i * 128); pk2[4 * i] = v.x; pk2[4 * i + 1] = v.y; pk2[4 * i + 2] = v.z; pk2[4 * i + 3] = v.w; }
    };
    half(0, oa, pk, 0);
    mbar_wait(bar_addr(sb, B_CTXOK + w), 0);
    load_ctx(Int<0>());
    half(1, ob, pk, 0);
    load_ctx(Int<1>());
    half(2, oa, pk2, 1);
#pragma unroll 1
    for (int i = 0; i < 3; i++) {
      half(4 * i + 3, ob, pk2, 1);
      if (i == 0) stage(oa, 0); else if (!HAND_NOW) hand_over(2 * i);
      half(4 * i + 4, oa, pk, 0);
      if (i == 0) hand_over(0);
      stage(ob, 2 * i + 1);
      if (HAND_NOW) hand_over(2 * i + 1);
      half(4 * i + 5, oa, pk2, 1);
      if (!HAND_NOW) hand_over(2 * i + 1);
      if (i == 2) break;
      half(4 * i + 6, ob, pk, 0);
      stage(oa, 2 * i + 2);
      if (HAND_NOW) hand_over(2 * i + 2);
    }
    wg_wait<0>();
    reg_fence(pk);
    reg_fence(pk2);
    stage(oa, 6);
    fence_async_smem();
    named_sync(1 + w, 128);
    if (wq == 0 && lane == 0) {
      tma_red2(&p.o, qreg + 2 * 8192, DA + 6 * 64, q_tile(h, j, 1) * 128 + (w ^ 1) * 64);
      bulk_commit();
      bulk_wait_read();
    }
  }
  TS(19);
  TDUMP();
}

namespace ssm {
constexpr int NCH = DA / NCONV;
constexpr int NS = 8, NP = 6;
constexpr uint32_t X0 = 384;
constexpr uint32_t HO = X0 + 4096;
constexpr uint32_t HE = HO + HO_STRIDE + 64;
constexpr uint32_t SSLOT = HE + 4096 + 64;
constexpr uint32_t PART = 264 * 16;
constexpr uint32_t OFF_P = NS * SSLOT, OFF_D = OFF_P + NP * 4 * PART, END = OFF_D + NCH * 4;
static_assert(SSLOT % 128 == 0 && HO % 128 == 0 && END <= BARS, "smem");
enum : uint32_t { B_FULL = 0, B_EMPTY = NS, B_PFULL = 2 * NS, B_PEMPTY = 2 * NS + NP };
__device__ __forceinline__ int channel(int cidx, int i) { return (i >> 4) * 64 + cidx * 16 + (i & 15); }

__device__ __forceinline__ void producer(const Params& p, uint32_t sb, int cidx, unsigned epoch) {
#pragma unroll 1
  for (int i = 0; i < NCH; i++) {
    const int s = i % NS, ch = channel(cidx, i);
    const uint32_t full = bar_addr(sb, B_FULL + s), dst = sb + s * SSLOT;
    mbar_wait(bar_addr(sb, B_EMPTY + s), ((i / NS) & 1) ^ 1);
    mbar_expect_tx(full, 4096 + 4128 + 4096);
    bulk_ld(dst + HE, at<uint8_t>(p.a_ssmk, ch * 4096), 4096, full);
    if ((i & 15) == 0) { flag_wait(flag_at(g_flags.x_ready, i >> 4), NMAIN, epoch); fence_async_all(); }
    bulk_ld(dst + HO, at<uint8_t>(g_ho, ch * HO_STRIDE), 4128, full);
    bulk_ld(dst + X0, at<uint8_t>(g_xs, ch * 4096), 4096, full);
  }
}

__device__ __forceinline__ void reducer(uint32_t sb, int cidx, int rw) {
  uint32_t n = 0;
#pragma unroll 1
  for (int i = rw; i < NCH; i += 3, n++) {
    const uint32_t b = rw + 3 * (n & 1), pb = sb + OFF_P + b * 4 * PART;
    uint8_t* dst = at<uint8_t>(g_xs, channel(cidx, i) * 4096);
    mbar_wait(bar_addr(sb, B_PFULL + b), (n >> 1) & 1);
    asm volatile("cp.async.bulk.global.shared::cta.bulk_group [%0], [%1], 4096;" :: "l"(dst), "r"(pb + 3 * PART) : "memory");
    bulk_commit();
    bulk_wait_all();
#pragma unroll
    for (int k = 2; k >= 0; k--)
      asm volatile("cp.reduce.async.bulk.global.shared::cta.bulk_group.add.noftz.bf16 [%0], [%1], 4096;" :: "l"(dst), "r"(pb + k * PART) : "memory");
    bulk_commit();
    bulk_wait_read();
    mbar_arrive(bar_addr(sb, B_PEMPTY + b));
    if (((i + 3) >> 4) != (i >> 4)) {
      bulk_wait_all();
      fence_async_all();
      flag_signal(flag_at(g_flags.z_ready, i >> 4));
    }
  }
}

__device__ __forceinline__ void mma_warpgroup(uint32_t sb, int w) {
  const int lane = threadIdx.x & 31, g = lane >> 2, c = lane & 3, wq = (threadIdx.x >> 5) & 3;
  const uint32_t aoff = ((g & 1) ? HO + 30 : HE) + (16 * wq - g + 2 * c) * 2;
  const uint32_t poff = OFF_P + wq * PART + (2 * wq + lane) * 16;
  const uint32_t dmask = (wq == 0 && c == (g >> 1)) ? ((g & 1) ? 0xffff0000u : 0xffffu) : 0u;
  float acc[8][16];
  uint32_t fa[16][4];
#pragma unroll
  for (int e = 0; e < 8; e++)
#pragma unroll
    for (int i = 0; i < 16; i++) acc[e][i] = 0.f;
  auto load_a = [&](int m, uint32_t ad) {
    fa[m][0] = lds4(ad + m * 256 + 16); fa[m][1] = lds4(ad + m * 256 + 144); fa[m][2] = lds4(ad + m * 256); fa[m][3] = lds4(ad + m * 256 + 128);
  };
  if (w == 1) named_arrive(PP_BAR, 256);
  mbar_wait(bar_addr(sb, B_FULL + w), 0);
#pragma unroll
  for (int m = 0; m < 16; m++) load_a(m, sb + w * SSLOT + aoff);
  uint32_t dd = lds4(sb + OFF_D + w * 4);
  if (threadIdx.x == 128) { GT(12); PT(10); }
  uint32_t pb = w, pphase = 1;
#pragma unroll 1
  for (int i = w; i < NCH; i += 2) {
    fa[0][2] = badd(fa[0][2], dd & dmask);
    const uint64_t db = (uint64_t)((((sb + (i % NS) * SSLOT + X0 - 16) & 0x3FFFF) >> 4) | (1u << 16)) | ((uint64_t)8 << 32);
    named_sync(PP_BAR + w, 256);
    wg_fence();
#pragma unroll
    for (int r = 0; r < 16; r++) {
      auto mm = [&](int e, int m) { wgmma_rs_n32(acc[e], fa[m][0], fa[m][1], fa[m][2], fa[m][3], db + (int64_t)(32 * e - 16 * m), m != 0); };
      mm(7, r);
      if (r < 14) mm(6, r); else mm(0, r - 14);
      if (r < 12) mm(5, r); else mm(1, r - 12);
      if (r < 10) mm(4, r); else mm(2, r - 10);
      if ((r & 1) == 0) mm(3, r >> 1);
      if (r == CONV_ARRIVE && (i + 1 < NCH)) named_arrive(PP_BAR + (w ^ 1), 256);
    }
    wg_commit();
    const int nx = i + 2 < NCH ? i + 2 : i;
    mbar_wait(bar_addr(sb, B_FULL + nx % NS), (nx / NS) & 1);
    mbar_wait(bar_addr(sb, B_PEMPTY + pb), pphase);
    const uint32_t ad = sb + (nx % NS) * SSLOT + aoff, pa = sb + pb * 4 * PART + poff;
    wg_wait<0>();
#pragma unroll
    for (int e = 0; e < 8; e++) reg_fence(acc[e]);
#pragma unroll
    for (int m = 0; m < 16; m++) reg_fence(fa[m]);
    if (lane == 0) mbar_arrive(bar_addr(sb, B_EMPTY + i % NS));
#pragma unroll
    for (int e = 0; e < 8; e++) {
      if (e < CONV_EARLY) load_a(e, ad);
      uint32_t u[4];
#pragma unroll
      for (int j = 0; j < 4; j++) {
        const int T = 4 * e + j, U = T - 1;
        float lo = acc[e][4 * j], hi = acc[e][4 * j + 1];
        if (T > 0) { lo += acc[U >> 2][4 * (U & 3) + 2]; hi += acc[U >> 2][4 * (U & 3) + 3]; }
        u[j] = pack_bf16(lo, hi);
      }
      asm volatile("stmatrix.sync.aligned.m8n8.x4.trans.shared.b16 [%0], {%1, %2, %3, %4};" :: "r"(pa + e * 512), "r"(u[0]), "r"(u[1]), "r"(u[2]), "r"(u[3]) : "memory");
    }
    dd = lds4(sb + OFF_D + nx * 4);
#pragma unroll
    for (int m = CONV_EARLY; m < CONV_FENCE; m++) load_a(m, ad);
    fence_async_smem();
    warp_arrive(bar_addr(sb, B_PFULL + pb), lane);
#pragma unroll
    for (int m = CONV_FENCE; m < 16; m++) load_a(m, ad);
    pb += 2;
    if (pb >= NP) { pb -= NP; pphase ^= 1; }
  }
  if (threadIdx.x == 128) { PT(9); GT(13); }
}

__device__ __forceinline__ void init(const Params& p, uint32_t sb, int cidx) {
  const uint32_t t = threadIdx.x;
  if (t < NCH) {
    const uint32_t d = (uint32_t)__ldg(reinterpret_cast<const unsigned short*>(p.a_D + channel(cidx, t))) * 0x10001u;
    asm volatile("st.shared.u32 [%0], %1;" :: "r"(sb + OFF_D + t * 4), "r"(d) : "memory");
  }
#pragma unroll 1
  for (uint32_t u = t; u < NS * 32; u += 128) {
    const uint32_t r = u & 31;
    if (r < 28) sts16(sb + (u >> 5) * SSLOT + (r < 24 ? r * 16 : HE - 64 + (r - 24) * 16), 0, 0, 0, 0);
    if (u < NP * 32) sts16(sb + OFF_P + (u >> 3) * PART + (u & 7) * 16, 0, 0, 0, 0);
  }
  if (t == 0) {
    for (int i = 0; i < NS; i++) { mbar_init(bar_addr(sb, B_FULL + i), 1); mbar_init(bar_addr(sb, B_EMPTY + i), 4); }
    for (int i = 0; i < NP; i++) { mbar_init(bar_addr(sb, B_PFULL + i), 4); mbar_init(bar_addr(sb, B_PEMPTY + i), 1); }
  }
  fence_async_smem();
}

__device__ __forceinline__ void side_prepare(const Params& p, int cta, int rd) {
  const int lane = threadIdx.x & 31, t0 = 16 * cta + 8 * (lane & 1);
  if (EXP_SIDE & 16) { if (lane == 0) flag_signal_after_bulk(flag_at(g_flags.x_ready, rd)); return; }
#pragma unroll 1
  for (int ch = 64 * rd + (lane & ~1); ch < 64 * rd + 64; ch += 32) {
    const uint4 sv = __ldg(at<const uint4>(p.a_shift, ch * 8));
    const uint32_t* kp = at<const uint32_t>(p.a_k, (t0 * DA + ch) * 2);
    const uint32_t* vp = at<const uint32_t>(p.a_v, (t0 * DA + ch) * 2);
    uint32_t k0 = 0, k1 = 0, k2 = 0, kk[8], x[8];
    if (t0 > 0) { k0 = __ldg(kp - 3 * (DA / 2)); k1 = __ldg(kp - 2 * (DA / 2)); k2 = __ldg(kp - DA / 2); }
#pragma unroll
    for (int i = 0; i < 8; i++) { kk[i] = __ldg(kp + i * (DA / 2)); x[i] = __ldg(vp + i * (DA / 2)); }
    const uint32_t sh0 = __byte_perm(sv.x, sv.z, 0x5410), sh1 = __byte_perm(sv.x, sv.z, 0x7632);
    const uint32_t sh2 = __byte_perm(sv.y, sv.w, 0x5410), sh3 = __byte_perm(sv.y, sv.w, 0x7632);
#pragma unroll
    for (int i = 0; i < 8; i++) {
      uint32_t ks = bmul(k0, sh3);
      ks = badd(ks, bmul(k1, sh2)); ks = badd(ks, bmul(k2, sh1)); ks = badd(ks, bmul(kk[i], sh0));
      x[i] = bmul(ks, x[i]);
      k0 = k1; k1 = k2; k2 = kk[i];
    }
    uint4* dst = at<uint4>(g_xs, ch * 4096 + t0 * 2);
    if ((EXP_SIDE & 4) && (x[0] ^ x[1] ^ x[2] ^ x[3] ^ x[4] ^ x[5] ^ x[6] ^ x[7]) != 0x12345) continue;
    dst[0]   = make_uint4(__byte_perm(x[7], x[6], 0x5410), __byte_perm(x[5], x[4], 0x5410), __byte_perm(x[3], x[2], 0x5410), __byte_perm(x[1], x[0], 0x5410));
    dst[256] = make_uint4(__byte_perm(x[7], x[6], 0x7632), __byte_perm(x[5], x[4], 0x7632), __byte_perm(x[3], x[2], 0x7632), __byte_perm(x[1], x[0], 0x7632));
  }
  if (!(EXP_SIDE & 8)) {
    const int hc = 64 * rd + (cta >> 1), r0 = (cta & 1) * 128 + lane;
    const uint4* src = at<const uint4>(p.a_ssmk, hc * 4096 + r0 * 16);
    uint4* dst = at<uint4>(g_ho, hc * HO_STRIDE + r0 * 16);
    uint4 w[4];
    uint32_t nx[4];
#pragma unroll
    for (int i = 0; i < 4; i++) { w[i] = __ldg(src + 32 * i); nx[i] = r0 + 32 * i < 255 ? __ldg(reinterpret_cast<const uint32_t*>(src + 32 * i + 1)) : 0u; }
#pragma unroll
    for (int i = 0; i < 4; i++)
      dst[32 * i + 2] = make_uint4(__byte_perm(w[i].x, w[i].y, 0x5432), __byte_perm(w[i].y, w[i].z, 0x5432), __byte_perm(w[i].z, w[i].w, 0x5432), __byte_perm(w[i].w, nx[i], 0x5432));
    const uint32_t h0 = __shfl_sync(0xffffffffu, w[0].x, 0);
    if (r0 < 2) dst[0] = make_uint4(0, 0, 0, r0 ? h0 << 16 : 0u);
  }
  __syncwarp();
  if (lane == 0) { if (EXP_SIDE & 2) flag_signal_after_bulk(flag_at(g_flags.x_ready, rd)); else flag_signal(flag_at(g_flags.x_ready, rd)); }
}
__device__ __forceinline__ void side_finish(const Params& p, int cta, int rd) {
  const int lane = threadIdx.x & 31, t0 = 16 * cta + 8 * (lane & 1);
#pragma unroll 1
  for (int ch = 64 * rd + (lane & ~1); ch < 64 * rd + 64; ch += 32) {
    const uint4* src = at<const uint4>(g_xs, ch * 4096 + t0 * 2);
    const uint32_t* qp = at<const uint32_t>(p.a_q, (t0 * DA + ch) * 2);
    uint32_t* op = at<uint32_t>(p.out, (t0 * OUTW + ch) * 2);
    const uint4 z0 = __ldcg(src), z1 = __ldcg(src + 256);
    uint32_t q[8];
#pragma unroll
    for (int i = 0; i < 8; i++) q[i] = __ldg(qp + i * (DA / 2));
    const uint32_t a[4] = {z0.w, z0.z, z0.y, z0.x}, b[4] = {z1.w, z1.z, z1.y, z1.x};
#pragma unroll
    for (int i = 0; i < 4; i++) {
      op[(2 * i) * (OUTW / 2)]     = bmul(q[2 * i], __byte_perm(a[i], b[i], 0x7632));
      op[(2 * i + 1) * (OUTW / 2)] = bmul(q[2 * i + 1], __byte_perm(a[i], b[i], 0x5410));
    }
  }
}
__device__ __forceinline__ void clear_rows(const Params& p, int qt, int part) {
  const int lane = threadIdx.x & 31;
  if (lane < 28) {
    uint4* z = at<uint4>(p.out, ((qt * 128 + part * 16) * OUTW + DA) * 2 + lane * 16);
#pragma unroll
    for (int i = 0; i < 32; i++) z[(i >> 1) * (OUTW / 8) + (i & 1) * 28] = make_uint4(0, 0, 0, 0);
  }
  __syncwarp();
  if (lane == 0) flag_signal(flag_at(g_flags.zero_ready, qt));
}
__device__ __forceinline__ void side_work(const Params& p, int cta, int qt, unsigned epoch) {
#pragma unroll 1
  for (int rd = -SIDE_AHEAD; rd < 7; rd++) {
    if (rd >= 0) {
      if ((threadIdx.x & 31) == 0) flag_wait_slow(flag_at(g_flags.z_ready, rd), 3 * NCONV, epoch);
      __syncwarp();
    }
    if (rd + SIDE_AHEAD < 7) side_prepare(p, cta, rd + SIDE_AHEAD);
    if (rd >= 0 && !(EXP_SIDE & 1)) side_finish(p, cta, rd);
    if (rd == ZERO_RD) clear_rows(p, qt, (cta >> 3) & 7);
  }
}
}

__global__ void __cluster_dims__(2, 1, 1) __launch_bounds__(NTHREADS, 1)
concat_heads__ssm_conv_h3__compressed_kv_cla__prompt_kernel(const __grid_constant__ Params p) {
  extern __shared__ uint8_t smem_raw[];
  const uint32_t sb = (smem_u32(smem_raw) + 1023) & ~1023u;
  const int warp = __shfl_sync(0xffffffffu, threadIdx.x >> 5, 0);
  const int wg = warp >> 2;
  const int cta = blockIdx.x;
  const bool attn = cta < NMAIN;
  int h, u;
  {
    const int c = cta >> 1;
    if (c < 4) { h = 9; u = c; }
    else if (c < 36) { h = (c - 4) & 7; u = (c - 4) >> 3; }
    else { const int i = (c - 36) % 7; h = i == 0 ? 8 : 9 + i; u = (c - 36) / 7; }
  }
  const int j = 2 * u + (cta & 1);
  const int lane = threadIdx.x & 31;
  if (wg != 0) {
    if (attn) {
      if (threadIdx.x == NTHREADS - 32) {
        if (PF_MAPS & 2) prefetch_map(QFIRST ? &p.wq : &p.wuk);
        for (int i = 0; i < NSLOT; i++) mbar_init(bar_addr(sb, B_FULL + i), 1);
        asm volatile("fence.mbarrier_init.release.cluster;" ::: "memory");
      }
      __syncwarp();
      cluster_arrive();
      if (wg == 2) named_arrive(PP_BAR, 256);
      if (threadIdx.x == NTHREADS - 32) {
        for (int k = 0; k < EARLY_LD; k++) {
          const uint32_t full = bar_addr(sb, B_FULL + k);
          mbar_expect_tx(full, 49152);
          if (QFIRST) {
            tma_ld2(sb + QREG + k * 16384, &p.x, full, k * 64, q_tile(h, j, 1) * 128);
            load_tile4(sb + k * SLOT, &p.wq, full, k * 64, att_head(h, 1) * 4, j & 1, false);
          } else {
            tma_ld2(sb + QREG + k * 16384, &p.ckv, full, k * 64, p1_rows(h, j, 0) * 128);
            load_tile4(sb + k * SLOT, &p.wuk, full, k * 64, p1_head(h, 0) * 4, j & 1, false);
          }
        }
      }
      __syncwarp();
    }
    asm volatile("setmaxnreg.inc.sync.aligned.u32 232;");
    if (!attn) {
      if (p.out != nullptr) { named_sync(0, NTHREADS); ssm::mma_warpgroup(sb, wg - 1); }
      return;
    }
    if (p.out != nullptr) consumer_main(p, sb, h, j, wg - 1, warp & 3);
  } else {
    asm volatile("setmaxnreg.dec.sync.aligned.u32 40;");
    if (!attn) {
      ssm::init(p, sb, cta - NMAIN);
      named_sync(0, NTHREADS);
      if (lane == 0) {
        if (warp == 0) { ssm::producer(p, sb, cta - NMAIN, load_epoch()); cta_done(32); }
        else ssm::reducer(sb, cta - NMAIN, warp - 1);
        if (warp == 1) GT(14);
      }
      return;
    }
    if (lane == 0) {
      if (warp == 1) {
        for (int i = 0; i < NSLOT; i++) mbar_init(bar_addr(sb, B_EMPTY + i), (UNICAST & 8) ? 8 : 16);
        for (int i = 0; i < 2; i++) {
          mbar_init(bar_addr(sb, B_QFREE + i), 4); mbar_init(bar_addr(sb, B_QFULL + i), 1);
          mbar_init(bar_addr(sb, B_KVOK + i), 1); mbar_init(bar_addr(sb, B_CTXOK + i), 1);
        }
      } else if (warp == 2) {
        for (int i = 0; i < 8; i++) { mbar_init(bar_addr(sb, B_S2_FULL + i), 4); mbar_init(bar_addr(sb, B_S2_EMPTY + i), 1); }
      } else if (warp == 0) {
        mbar_init(bar_addr(sb, B_DONE), 2);
        for (int i = 0; i < 2; i++) {
          mbar_init(bar_addr(sb, B_ST_KV + i), 4); mbar_init(bar_addr(sb, B_ST_KV + 2 + i), 4);
          mbar_init(bar_addr(sb, B_ST_Q + i), 4); mbar_init(bar_addr(sb, B_ST_CTX + i), 4);
        }
      }
      asm volatile("fence.mbarrier_init.release.cluster;" ::: "memory");
    }
    __syncwarp();
    cluster_arrive();
    cluster_wait();
    if (warp == 0) {
      if (lane == 0) producer_main(p, sb, h, j);
    } else if (warp < 3) {
      if (lane == 0) {
        if ((PF_MAPS & 1) && warp == 1) { __nanosleep(2000); prefetch_map(&p.wuv); prefetch_map(&p.x); prefetch_map(&p.wq); prefetch_map(&p.o); prefetch_map(&p.wo); }
        helper_main(p, sb, h, j, warp - 1);
      }
    } else {
      ssm::side_work(p, h * 8 + j, q_tile(h, j, 1), load_epoch());
      if (lane == 0) { GT(57); mbar_wait(bar_addr(sb, B_DONE), 0); cta_done(1); }
    }
  }
}

typedef CUresult (*EncodeTiledFn)(CUtensorMap*, CUtensorMapDataType, cuuint32_t, void*, const cuuint64_t*, const cuuint64_t*,
                                  const cuuint32_t*, const cuuint32_t*, CUtensorMapInterleave, CUtensorMapSwizzle,
                                  CUtensorMapL2promotion, CUtensorMapFloatOOBfill);

void make_map(EncodeTiledFn enc, CUtensorMap* m, const void* ptr, int rank, const uint64_t* dims, const uint64_t* strides, const uint32_t* box) {
  cuuint64_t d[5], s[4]; cuuint32_t b[5], e[5] = {1, 1, 1, 1, 1};
  for (int i = 0; i < rank; i++) { d[i] = dims[i]; b[i] = box[i]; if (i) s[i - 1] = strides[i - 1]; }
  enc(m, CU_TENSOR_MAP_DATA_TYPE_BFLOAT16, rank, const_cast<void*>(ptr), d, s, b, e, CU_TENSOR_MAP_INTERLEAVE_NONE,
      CU_TENSOR_MAP_SWIZZLE_128B, CU_TENSOR_MAP_L2_PROMOTION_L2_256B, CU_TENSOR_MAP_FLOAT_OOB_FILL_NONE);
}
void map2(EncodeTiledFn enc, CUtensorMap* m, const void* ptr, uint64_t cols, uint64_t rows, uint32_t bc, uint32_t br) {
  const uint64_t dims[2] = {cols, rows}, st[1] = {cols * 2}; const uint32_t box[2] = {bc, br};
  make_map(enc, m, ptr, 2, dims, st, box);
}
void map3(EncodeTiledFn enc, CUtensorMap* m, const void* ptr, uint64_t rows, uint32_t nblk) {
  const uint64_t dims[3] = {64, rows, 64}, st[2] = {8192, 128}; const uint32_t box[3] = {64, 64, nblk};
  make_map(enc, m, ptr, 3, dims, st, box);
}

}

extern "C" void kernel_launch(void* const* d_in, const int* in_sizes, int n_in, void* d_out, int out_size) {
  (void)in_sizes; (void)n_in; (void)out_size;
  static EncodeTiledFn enc = nullptr;
  if (!enc) {
    void* fn = nullptr; cudaDriverEntryPointQueryResult qr;
    cudaGetDriverEntryPoint("cuTensorMapEncodeTiled", &fn, cudaEnableDefault, &qr);
    enc = (EncodeTiledFn)fn;
    cudaFuncSetAttribute(concat_heads__ssm_conv_h3__compressed_kv_cla__prompt_kernel, cudaFuncAttributeMaxDynamicSharedMemorySize, SMEM_BYTES);
  }
  Params p;
  p.a_q = (const bf16*)d_in[0]; p.a_k = (const bf16*)d_in[1]; p.a_v = (const bf16*)d_in[2];
  p.a_shift = (const bf16*)d_in[3]; p.a_ssmk = (const bf16*)d_in[4]; p.a_D = (const bf16*)d_in[5];
  p.out = (bf16*)d_out;
  map2(enc, &p.x, d_in[6], DM, SEQ, 64, 128);
  map2(enc, &p.ckv, d_in[7], DC, SEQ, 64, 128);
  map3(enc, &p.wq, d_in[8], DM, 2);
  map3(enc, &p.wuk, d_in[9], DC, 2);
  map3(enc, &p.wuv, d_in[10], DC, 2);
  {
    const uint64_t dims[5] = {DM, 2, 4, 4, NH * HD / 32}, st[4] = {DM * 2, 8 * DM * 2, 2 * DM * 2, 32 * DM * 2}; const uint32_t box[5] = {64, 2, 4, 4, 4};
    make_map(enc, &p.wo, d_in[11], 5, dims, st, box);
  }
  map2(enc, &p.o, d_out, OUTW, SEQ, 64, 64);
  concat_heads__ssm_conv_h3__compressed_kv_cla__prompt_kernel<<<NCTA, NTHREADS, SMEM_BYTES>>>(p);
}
```

```cpp
#include <cuda_runtime.h>
#include <cuda_bf16.h>
#include <cuda.h>
#include <stdint.h>

namespace {

typedef __nv_bfloat16 bf16;

constexpr int SEQ  = 2048;
constexpr int DA   = 448;
constexpr int NH   = 16;
constexpr int HD   = 256;
constexpr int DM   = 448;
constexpr int DC   = 1024;
constexpr int OUTW = DA + DM;
constexpr int NMAIN = 128;
constexpr int NCONV = 4;
constexpr int NCTA  = NMAIN + NCONV;
constexpr int LOG_DONE = 8;
constexpr int NTHREADS = 384;

__device__ __align__(1024) bf16 g_kv[2ull * SEQ * NH * HD];
__device__ __align__(1024) bf16 g_qc[(size_t)NMAIN * 128 * HD];
__device__ __align__(128) uint8_t g_xs[DA * SEQ * 2];
constexpr uint32_t HO_STRIDE = 4224;
__device__ __align__(128) uint8_t g_ho[DA * HO_STRIDE];
struct alignas(128) Flag { unsigned v; unsigned pad[31]; };
struct Flags {
  Flag kv_ready[NH * 2];
  Flag ctx_ready[NMAIN * 2];
  Flag x_ready[7];
  Flag z_ready[7];
  Flag zero_ready[16];
  alignas(128) unsigned long long done;
};
__device__ Flags g_flags;
#define TS(i)
#define TSC(i, cond)
#define TDUMP()
#define GT(i)
#define PT(i)
#define PCLK(var)
#define PACC(acc, t0)

struct alignas(64) Params {
  CUtensorMap ckv;
  CUtensorMap wuk;
  CUtensorMap wuv;
  CUtensorMap x;
  CUtensorMap wq;
  CUtensorMap o;
  CUtensorMap wo;
  const bf16 *a_q, *a_k, *a_v, *a_shift, *a_ssmk, *a_D;
  bf16* out;
};

constexpr uint32_t SLOT     = 32768;
constexpr int      NSLOT    = 5;
constexpr uint32_t QREG     = 163840;
constexpr uint32_t BARS     = 229376;
constexpr uint32_t SMEM_BYTES = BARS + 1024 + 1024;
enum : uint32_t {
  B_FULL = 0, B_EMPTY = 5, B_KVOK = 12, B_ST_Q = 14, B_ST_CTX = 16, B_DONE = 19, B_QFREE = 20, B_QFULL = 22,
  B_S2_FULL = 24, B_S2_EMPTY = 32, B_CTXOK = 40, B_PF = 42, B_ST_KV = 44
};
constexpr int P1_STEPS = 4 * 16 + 2 * 7, P1_XS = P1_STEPS - 2;

template <typename T> __device__ __forceinline__ T* at(const void* base, uint32_t off) {
  asm volatile("" : "+r"(off));
  return reinterpret_cast<T*>(const_cast<char*>(static_cast<const char*>(base)) + off);
}
__device__ __forceinline__ unsigned* flag_at(Flag* f, uint32_t i) { return at<unsigned>(f, i * (uint32_t)sizeof(Flag)); }
__device__ __forceinline__ uint32_t smem_u32(const void* p) { return (uint32_t)__cvta_generic_to_shared(p); }
__device__ __forceinline__ void mbar_init(uint32_t bar, uint32_t cnt) {
  asm volatile("mbarrier.init.shared::cta.b64 [%0], %1;" :: "r"(bar), "r"(cnt) : "memory");
}
__device__ __forceinline__ void mbar_expect_tx(uint32_t bar, uint32_t bytes) {
  asm volatile("mbarrier.arrive.expect_tx.shared::cta.b64 _, [%0], %1;" :: "r"(bar), "r"(bytes) : "memory");
}
__device__ __forceinline__ void mbar_arrive(uint32_t bar) {
  asm volatile("mbarrier.arrive.shared::cta.b64 _, [%0];" :: "r"(bar) : "memory");
}
__device__ __forceinline__ void mbar_arrive_n(uint32_t bar, uint32_t n) {
  asm volatile("mbarrier.arrive.shared::cta.b64 _, [%0], %1;" :: "r"(bar), "r"(n) : "memory");
}
__device__ __forceinline__ void mbar_arrive_remote(uint32_t bar, uint32_t cta) {
  asm volatile("{\n.reg .b32 ra;\nmapa.shared::cluster.u32 ra, %0, %1;\n"
               "mbarrier.arrive.shared::cluster.b64 _, [ra];\n}" :: "r"(bar), "r"(cta) : "memory");
}
__device__ __forceinline__ bool mbar_try(uint32_t bar, uint32_t parity) {
  uint32_t ok;
  asm volatile("{\n.reg .pred p;\nmbarrier.try_wait.parity.shared::cta.b64 p, [%1], %2;\nselp.u32 %0, 1, 0, p;\n}"
               : "=r"(ok) : "r"(bar), "r"(parity) : "memory");
  return ok;
}
__device__ __forceinline__ uint32_t mbar_test(uint32_t bar, uint32_t parity) {
  uint32_t ok;
  asm volatile("{\n.reg .pred p;\nmbarrier.test_wait.parity.shared::cta.b64 p, [%1], %2;\nselp.u32 %0, 1, 0, p;\n}"
               : "=r"(ok) : "r"(bar), "r"(parity) : "memory");
  return ok;
}
constexpr uint32_t SPIN_LIMIT = 1u << 24;
__device__ __forceinline__ void mbar_wait(uint32_t bar, uint32_t parity) {
  if (mbar_try(bar, parity)) return;
  uint32_t n = 0;
  while (!mbar_try(bar, parity)) { if (++n > SPIN_LIMIT) __trap(); }
}
__device__ __forceinline__ void mbar_wait_unless(uint32_t ready, uint32_t bar, uint32_t parity) {
  asm volatile("{\n.reg .pred p;\n.reg .b32 n;\nsetp.ne.u32 p, %0, 0;\nvote.sync.all.pred p, p, 0xffffffff;\n@p bra.uni WDONE;\nmov.u32 n, 0;\n"
               "WLOOP:\nmbarrier.try_wait.parity.shared::cta.b64 p, [%1], %2;\n@p bra.uni WDONE;\nadd.u32 n, n, 1;\nsetp.lt.u32 p, n, %3;\n@p bra.uni WLOOP;\ntrap;\nWDONE:\n}"
               :: "r"(ready), "r"(bar), "r"(parity), "n"(SPIN_LIMIT) : "memory");
}
__device__ __forceinline__ unsigned load_epoch() {
  unsigned long long d; asm volatile("ld.relaxed.gpu.global.u64 %0, [%1];" : "=l"(d) : "l"(&g_flags.done) : "memory");
  return (unsigned)(d >> LOG_DONE);
}
__device__ __forceinline__ void flag_wait(const unsigned* f, unsigned count, unsigned epoch) {
  const unsigned target = (epoch + 1) * count;
  uint32_t n = 0;
  while (true) {
    unsigned v;
    asm volatile("ld.acquire.gpu.global.u32 %0, [%1];" : "=r"(v) : "l"(f) : "memory");
    if ((int)(v - target) >= 0) break;
    if (++n > SPIN_LIMIT) __trap();
    __nanosleep(20);
  }
}
__device__ __forceinline__ void flag_wait_slow(const unsigned* f, unsigned count, unsigned epoch) {
  const unsigned target = (epoch + 1) * count;
  uint32_t n = 0;
  while (true) {
    unsigned v;
    asm volatile("ld.acquire.gpu.global.u32 %0, [%1];" : "=r"(v) : "l"(f) : "memory");
    if ((int)(v - target) >= 0) break;
    if (++n > SPIN_LIMIT / 16) __trap();
    __nanosleep(1000);
  }
}
__device__ __forceinline__ void cta_done(unsigned long long n) { asm volatile("red.relaxed.gpu.global.add.u64 [%0], %1;" :: "l"(&g_flags.done), "l"(n) : "memory"); }
__device__ __forceinline__ void flag_wait_fast(const unsigned* f, unsigned count, unsigned epoch) {
  const unsigned target = (epoch + 1) * count;
  uint32_t n = 0;
  while (true) {
    unsigned v;
    asm volatile("ld.acquire.gpu.global.u32 %0, [%1];" : "=r"(v) : "l"(f) : "memory");
    if ((int)(v - target) >= 0) break;
    if (++n > SPIN_LIMIT) __trap();
  }
}
__device__ __forceinline__ void fence_async_all() { asm volatile("fence.proxy.async.global;" ::: "memory"); }
__device__ __forceinline__ void flag_signal(unsigned* f) { asm volatile("red.release.gpu.global.add.u32 [%0], 1;" :: "l"(f) : "memory"); }
__device__ __forceinline__ void flag_signal_after_bulk(unsigned* f) {
  asm volatile("red.relaxed.gpu.global.add.u32 [%0], 1;" :: "l"(f) : "memory");
}
__device__ __forceinline__ void fence_async_smem() { asm volatile("fence.proxy.async.shared::cta;" ::: "memory"); }
#define HINTS 40
constexpr uint64_t POL_NORMAL = 0x1000000000000000ull, POL_FIRST = 0x12F0000000000000ull;
__device__ __forceinline__ constexpr uint64_t pol(bool first) { return first ? POL_FIRST : POL_NORMAL; }
__device__ __forceinline__ void tma_ld2(uint32_t dst, const CUtensorMap* m, uint32_t bar, int c0, int c1, uint64_t pl = POL_NORMAL) {
  asm volatile("cp.async.bulk.tensor.2d.shared::cluster.global.mbarrier::complete_tx::bytes.L2::cache_hint [%0], [%1, {%3, %4}], [%2], %5;"
               :: "r"(dst), "l"(m), "r"(bar), "r"(c0), "r"(c1), "l"(pl) : "memory");
}
__device__ __forceinline__ void tma_ld3(uint32_t dst, const CUtensorMap* m, uint32_t bar, int c0, int c1, int c2, uint64_t pl = POL_NORMAL) {
  asm volatile("cp.async.bulk.tensor.3d.shared::cluster.global.mbarrier::complete_tx::bytes.L2::cache_hint [%0], [%1, {%3, %4, %5}], [%2], %6;"
               :: "r"(dst), "l"(m), "r"(bar), "r"(c0), "r"(c1), "r"(c2), "l"(pl) : "memory");
}
__device__ __forceinline__ void tma_ld3_mc(uint32_t dst, const CUtensorMap* m, uint32_t bar, int c0, int c1, int c2, uint64_t pl = POL_NORMAL) {
  asm volatile("cp.async.bulk.tensor.3d.shared::cluster.global.mbarrier::complete_tx::bytes.multicast::cluster.L2::cache_hint [%0], [%1, {%3, %4, %5}], [%2], %6, %7;"
               :: "r"(dst), "l"(m), "r"(bar), "r"(c0), "r"(c1), "r"(c2), "h"((uint16_t)3), "l"(pl) : "memory");
}
__device__ __forceinline__ void bulk_ld(uint32_t dst, const void* src, uint32_t bytes, uint32_t bar) {
  asm volatile("cp.async.bulk.shared::cluster.global.mbarrier::complete_tx::bytes [%0], [%1], %2, [%3];"
               :: "r"(dst), "l"(src), "r"(bytes), "r"(bar) : "memory");
}
__device__ __forceinline__ void bulk_ld_p(uint32_t dst, const void* src, uint32_t bytes, uint32_t bar, uint64_t pl) {
  asm volatile("cp.async.bulk.shared::cluster.global.mbarrier::complete_tx::bytes.L2::cache_hint [%0], [%1], %2, [%3], %4;"
               :: "r"(dst), "l"(src), "r"(bytes), "r"(bar), "l"(pl) : "memory");
}
__device__ __forceinline__ void bulk_ld_mc(uint32_t dst, const void* src, uint32_t bytes, uint32_t bar, uint64_t pl) {
  asm volatile("cp.async.bulk.shared::cluster.global.mbarrier::complete_tx::bytes.multicast::cluster.L2::cache_hint [%0], [%1], %2, [%3], %4, %5;"
               :: "r"(dst), "l"(src), "r"(bytes), "r"(bar), "h"((uint16_t)3), "l"(pl) : "memory");
}
__device__ __forceinline__ void tma_st3(const CUtensorMap* m, uint32_t src, int c0, int c1, int c2) {
  asm volatile("cp.async.bulk.tensor.3d.global.shared::cta.bulk_group.L2::cache_hint [%0, {%2, %3, %4}], [%1], %5;"
               :: "l"(m), "r"(src), "r"(c0), "r"(c1), "r"(c2), "l"(pol(HINTS & 1024)) : "memory");
}
__device__ __forceinline__ void tma_ld2_mc(uint32_t dst, const CUtensorMap* m, uint32_t bar, int c0, int c1, uint64_t pl = POL_NORMAL) {
  asm volatile("cp.async.bulk.tensor.2d.shared::cluster.global.mbarrier::complete_tx::bytes.multicast::cluster.L2::cache_hint [%0], [%1, {%3, %4}], [%2], %5, %6;"
               :: "r"(dst), "l"(m), "r"(bar), "r"(c0), "r"(c1), "h"((uint16_t)3), "l"(pl) : "memory");
}
__device__ __forceinline__ void tma_ld5_mc(uint32_t dst, const CUtensorMap* m, uint32_t bar, int c0, int c4, uint64_t pl = POL_NORMAL) {
  asm volatile("cp.async.bulk.tensor.5d.shared::cluster.global.mbarrier::complete_tx::bytes.multicast::cluster.L2::cache_hint [%0], [%1, {%3, %7, %7, %7, %4}], [%2], %5, %6;"
               :: "r"(dst), "l"(m), "r"(bar), "r"(c0), "r"(c4), "h"((uint16_t)3), "l"(pl), "r"(0) : "memory");
}
__device__ __forceinline__ void tma_ld5(uint32_t dst, const CUtensorMap* m, uint32_t bar, int c0, int c4, uint64_t pl = POL_NORMAL) {
  asm volatile("cp.async.bulk.tensor.5d.shared::cluster.global.mbarrier::complete_tx::bytes.L2::cache_hint [%0], [%1, {%3, %6, %6, %6, %4}], [%2], %5;"
               :: "r"(dst), "l"(m), "r"(bar), "r"(c0), "r"(c4), "l"(pl), "r"(0) : "memory");
}
__device__ __forceinline__ void tma_st2(const CUtensorMap* m, uint32_t src, int c0, int c1) {
  asm volatile("cp.async.bulk.tensor.2d.global.shared::cta.bulk_group [%0, {%2, %3}], [%1];"
               :: "l"(m), "r"(src), "r"(c0), "r"(c1) : "memory");
}
__device__ __forceinline__ void tma_red2(const CUtensorMap* m, uint32_t src, int c0, int c1) {
  asm volatile("cp.reduce.async.bulk.tensor.2d.global.shared::cta.add.bulk_group [%0, {%2, %3}], [%1];"
               :: "l"(m), "r"(src), "r"(c0), "r"(c1) : "memory");
}
__device__ __forceinline__ void bulk_commit() { asm volatile("cp.async.bulk.commit_group;" ::: "memory"); }
__device__ __forceinline__ void bulk_wait_read() { asm volatile("cp.async.bulk.wait_group.read 0;" ::: "memory"); }
__device__ __forceinline__ void bulk_wait_all() { asm volatile("cp.async.bulk.wait_group 0;" ::: "memory"); }
__device__ __forceinline__ void prefetch_map(const CUtensorMap* m) { asm volatile("prefetch.tensormap [%0];" :: "l"(m) : "memory"); }
__device__ __forceinline__ void wg_fence() { asm volatile("wgmma.fence.sync.aligned;" ::: "memory"); }
__device__ __forceinline__ void wg_commit() { asm volatile("wgmma.commit_group.sync.aligned;" ::: "memory"); }
template <int N> __device__ __forceinline__ void wg_wait() { asm volatile("wgmma.wait_group.sync.aligned %0;" :: "n"(N) : "memory"); }
template <int N> __device__ __forceinline__ void reg_fence(float (&d)[N]) {
#pragma unroll
  for (int i = 0; i < N; i++) asm volatile("" : "+f"(d[i]) :: "memory");
}
template <int N> __device__ __forceinline__ void reg_fence(uint32_t (&d)[N]) {
#pragma unroll
  for (int i = 0; i < N; i++) asm volatile("" : "+r"(d[i]) :: "memory");
}
__device__ __forceinline__ uint32_t fresh_tid() { uint32_t t; asm volatile("mov.u32 %0, %%tid.x;" : "=r"(t)); return t; }
__device__ __forceinline__ uint32_t lane_base16() {
  const uint32_t t = fresh_tid(), lane = t & 31, wq = (t >> 5) & 3;
  return (16 * wq + (lane & 7) + 8 * ((lane >> 3) & 1)) * 128 + (((lane >> 4) ^ (lane & 7)) << 4);
}
__device__ __forceinline__ void cluster_arrive() { asm volatile("barrier.cluster.arrive.relaxed.aligned;" ::: "memory"); }
__device__ __forceinline__ void cluster_wait() { asm volatile("barrier.cluster.wait.acquire.aligned;" ::: "memory"); }
__device__ __forceinline__ void named_sync(int id, int n) { asm volatile("bar.sync %0, %1;" :: "r"(id), "r"(n) : "memory"); }
__device__ __forceinline__ void named_arrive(int id, int n) { asm volatile("bar.arrive %0, %1;" :: "r"(id), "r"(n) : "memory"); }
__device__ __forceinline__ uint32_t pack_bf16(float lo, float hi) {
  uint32_t r; asm("cvt.rn.bf16x2.f32 %0, %1, %2;" : "=r"(r) : "f"(hi), "f"(lo)); return r;
}
__device__ __forceinline__ float ex2(float x) { float y; asm("ex2.approx.ftz.f32 %0, %1;" : "=f"(y) : "f"(x)); return y; }
__device__ __forceinline__ void stsm4(uint32_t addr, uint32_t a, uint32_t b, uint32_t c, uint32_t d) {
  asm volatile("stmatrix.sync.aligned.m8n8.x4.shared.b16 [%0], {%1, %2, %3, %4};" :: "r"(addr), "r"(a), "r"(b), "r"(c), "r"(d) : "memory");
}
__device__ __forceinline__ uint64_t mk_desc(uint32_t addr, uint32_t lbo, uint32_t sbo) {
  return (uint64_t)(((addr & 0x3FFFF) >> 4) | ((lbo >> 4) << 16)) | ((uint64_t)((sbo >> 4) | (1u << 30)) << 32);
}
__device__ __forceinline__ uint64_t desc_k(uint32_t addr)  { return mk_desc(addr, 16, 1024); }
__device__ __forceinline__ uint64_t desc_mn(uint32_t addr) { return mk_desc(addr, 8192, 1024); }
__device__ __forceinline__ uint64_t desc_64(uint32_t addr) { return (uint64_t)(((addr & 0x3FFFF) >> 4) | ((4096u >> 4) << 16)) | ((uint64_t)((512u >> 4) | (2u << 30)) << 32); }
__device__ __forceinline__ uint64_t desc_add(uint64_t d, uint32_t bytes) { return d + (bytes >> 4); }

__device__ __forceinline__ void wgmma_ss_n256_tb(float (&d)[128], uint64_t da, uint64_t db, int sd) {
  asm volatile("{\n.reg .pred p;\nsetp.ne.b32 p, %130, 0;\n"
    "wgmma.mma_async.sync.aligned.m64n256k16.f32.bf16.bf16 "
    "{%0, %1, %2, %3, %4, %5, %6, %7, %8, %9, %10, %11, %12, %13, %14, %15, "
    "%16, %17, %18, %19, %20, %21, %22, %23, %24, %25, %26, %27, %28, %29, %30, %31, "
    "%32, %33, %34, %35, %36, %37, %38, %39, %40, %41, %42, %43, %44, %45, %46, %47, "
    "%48, %49, %50, %51, %52, %53, %54, %55, %56, %57, %58, %59, %60, %61, %62, %63, "
    "%64, %65, %66, %67, %68, %69, %70, %71, %72, %73, %74, %75, %76, %77, %78, %79, "
    "%80, %81, %82, %83, %84, %85, %86, %87, %88, %89, %90, %91, %92, %93, %94, %95, "
    "%96, %97, %98, %99, %100, %101, %102, %103, %104, %105, %106, %107, %108, %109, %110, %111, "
    "%112, %113, %114, %115, %116, %117, %118, %119, %120, %121, %122, %123, %124, %125, %126, %127}, "
    "%128, %129, p, 1, 1, 0, 1;\n}"
    : "+f"(d[0]), "+f"(d[1]), "+f"(d[2]), "+f"(d[3]), "+f"(d[4]), "+f"(d[5]), "+f"(d[6]), "+f"(d[7]),
      "+f"(d[8]), "+f"(d[9]), "+f"(d[10]), "+f"(d[11]), "+f"(d[12]), "+f"(d[13]), "+f"(d[14]), "+f"(d[15]),
      "+f"(d[16]), "+f"(d[17]), "+f"(d[18]), "+f"(d[19]), "+f"(d[20]), "+f"(d[21]), "+f"(d[22]), "+f"(d[23]),
      "+f"(d[24]), "+f"(d[25]), "+f"(d[26]), "+f"(d[27]), "+f"(d[28]), "+f"(d[29]), "+f"(d[30]), "+f"(d[31]),
      "+f"(d[32]), "+f"(d[33]), "+f"(d[34]), "+f"(d[35]), "+f"(d[36]), "+f"(d[37]), "+f"(d[38]), "+f"(d[39]),
      "+f"(d[40]), "+f"(d[41]), "+f"(d[42]), "+f"(d[43]), "+f"(d[44]), "+f"(d[45]), "+f"(d[46]), "+f"(d[47]),
      "+f"(d[48]), "+f"(d[49]), "+f"(d[50]), "+f"(d[51]), "+f"(d[52]), "+f"(d[53]), "+f"(d[54]), "+f"(d[55]),
      "+f"(d[56]), "+f"(d[57]), "+f"(d[58]), "+f"(d[59]), "+f"(d[60]), "+f"(d[61]), "+f"(d[62]), "+f"(d[63]),
      "+f"(d[64]), "+f"(d[65]), "+f"(d[66]), "+f"(d[67]), "+f"(d[68]), "+f"(d[69]), "+f"(d[70]), "+f"(d[71]),
      "+f"(d[72]), "+f"(d[73]), "+f"(d[74]), "+f"(d[75]), "+f"(d[76]), "+f"(d[77]), "+f"(d[78]), "+f"(d[79]),
      "+f"(d[80]), "+f"(d[81]), "+f"(d[82]), "+f"(d[83]), "+f"(d[84]), "+f"(d[85]), "+f"(d[86]), "+f"(d[87]),
      "+f"(d[88]), "+f"(d[89]), "+f"(d[90]), "+f"(d[91]), "+f"(d[92]), "+f"(d[93]), "+f"(d[94]), "+f"(d[95]),
      "+f"(d[96]), "+f"(d[97]), "+f"(d[98]), "+f"(d[99]), "+f"(d[100]), "+f"(d[101]), "+f"(d[102]), "+f"(d[103]),
      "+f"(d[104]), "+f"(d[105]), "+f"(d[106]), "+f"(d[107]), "+f"(d[108]), "+f"(d[109]), "+f"(d[110]), "+f"(d[111]),
      "+f"(d[112]), "+f"(d[113]), "+f"(d[114]), "+f"(d[115]), "+f"(d[116]), "+f"(d[117]), "+f"(d[118]), "+f"(d[119]),
      "+f"(d[120]), "+f"(d[121]), "+f"(d[122]), "+f"(d[123]), "+f"(d[124]), "+f"(d[125]), "+f"(d[126]), "+f"(d[127])
    : "l"(da), "l"(db), "r"(sd));
}
__device__ __forceinline__ void wgmma_ss_n64(float (&d)[32], uint64_t da, uint64_t db, int sd) {
  asm volatile("{\n.reg .pred p;\nsetp.ne.b32 p, %34, 0;\n"
    "wgmma.mma_async.sync.aligned.m64n64k16.f32.bf16.bf16 "
    "{%0, %1, %2, %3, %4, %5, %6, %7, %8, %9, %10, %11, %12, %13, %14, %15, "
    "%16, %17, %18, %19, %20, %21, %22, %23, %24, %25, %26, %27, %28, %29, %30, %31}, "
    "%32, %33, p, 1, 1, 0, 0;\n}"
    : "+f"(d[0]), "+f"(d[1]), "+f"(d[2]), "+f"(d[3]), "+f"(d[4]), "+f"(d[5]), "+f"(d[6]), "+f"(d[7]),
      "+f"(d[8]), "+f"(d[9]), "+f"(d[10]), "+f"(d[11]), "+f"(d[12]), "+f"(d[13]), "+f"(d[14]), "+f"(d[15]),
      "+f"(d[16]), "+f"(d[17]), "+f"(d[18]), "+f"(d[19]), "+f"(d[20]), "+f"(d[21]), "+f"(d[22]), "+f"(d[23]),
      "+f"(d[24]), "+f"(d[25]), "+f"(d[26]), "+f"(d[27]), "+f"(d[28]), "+f"(d[29]), "+f"(d[30]), "+f"(d[31])
    : "l"(da), "l"(db), "r"(sd));
}
__device__ __forceinline__ void wgmma_rs_n256_tb(float (&d)[128], uint32_t a0, uint32_t a1, uint32_t a2, uint32_t a3, uint64_t db, int sd) {
  asm volatile("{\n.reg .pred p;\nsetp.ne.b32 p, %133, 0;\n"
    "wgmma.mma_async.sync.aligned.m64n256k16.f32.bf16.bf16 "
    "{%0, %1, %2, %3, %4, %5, %6, %7, %8, %9, %10, %11, %12, %13, %14, %15, "
    "%16, %17, %18, %19, %20, %21, %22, %23, %24, %25, %26, %27, %28, %29, %30, %31, "
    "%32, %33, %34, %35, %36, %37, %38, %39, %40, %41, %42, %43, %44, %45, %46, %47, "
    "%48, %49, %50, %51, %52, %53, %54, %55, %56, %57, %58, %59, %60, %61, %62, %63, "
    "%64, %65, %66, %67, %68, %69, %70, %71, %72, %73, %74, %75, %76, %77, %78, %79, "
    "%80, %81, %82, %83, %84, %85, %86, %87, %88, %89, %90, %91, %92, %93, %94, %95, "
    "%96, %97, %98, %99, %100, %101, %102, %103, %104, %105, %106, %107, %108, %109, %110, %111, "
    "%112, %113, %114, %115, %116, %117, %118, %119, %120, %121, %122, %123, %124, %125, %126, %127}, "
    "{%128, %129, %130, %131}, %132, p, 1, 1, 1;\n}"
    : "+f"(d[0]), "+f"(d[1]), "+f"(d[2]), "+f"(d[3]), "+f"(d[4]), "+f"(d[5]), "+f"(d[6]), "+f"(d[7]),
      "+f"(d[8]), "+f"(d[9]), "+f"(d[10]), "+f"(d[11]), "+f"(d[12]), "+f"(d[13]), "+f"(d[14]), "+f"(d[15]),
      "+f"(d[16]), "+f"(d[17]), "+f"(d[18]), "+f"(d[19]), "+f"(d[20]), "+f"(d[21]), "+f"(d[22]), "+f"(d[23]),
      "+f"(d[24]), "+f"(d[25]), "+f"(d[26]), "+f"(d[27]), "+f"(d[28]), "+f"(d[29]), "+f"(d[30]), "+f"(d[31]),
      "+f"(d[32]), "+f"(d[33]), "+f"(d[34]), "+f"(d[35]), "+f"(d[36]), "+f"(d[37]), "+f"(d[38]), "+f"(d[39]),
      "+f"(d[40]), "+f"(d[41]), "+f"(d[42]), "+f"(d[43]), "+f"(d[44]), "+f"(d[45]), "+f"(d[46]), "+f"(d[47]),
      "+f"(d[48]), "+f"(d[49]), "+f"(d[50]), "+f"(d[51]), "+f"(d[52]), "+f"(d[53]), "+f"(d[54]), "+f"(d[55]),
      "+f"(d[56]), "+f"(d[57]), "+f"(d[58]), "+f"(d[59]), "+f"(d[60]), "+f"(d[61]), "+f"(d[62]), "+f"(d[63]),
      "+f"(d[64]), "+f"(d[65]), "+f"(d[66]), "+f"(d[67]), "+f"(d[68]), "+f"(d[69]), "+f"(d[70]), "+f"(d[71]),
      "+f"(d[72]), "+f"(d[73]), "+f"(d[74]), "+f"(d[75]), "+f"(d[76]), "+f"(d[77]), "+f"(d[78]), "+f"(d[79]),
      "+f"(d[80]), "+f"(d[81]), "+f"(d[82]), "+f"(d[83]), "+f"(d[84]), "+f"(d[85]), "+f"(d[86]), "+f"(d[87]),
      "+f"(d[88]), "+f"(d[89]), "+f"(d[90]), "+f"(d[91]), "+f"(d[92]), "+f"(d[93]), "+f"(d[94]), "+f"(d[95]),
      "+f"(d[96]), "+f"(d[97]), "+f"(d[98]), "+f"(d[99]), "+f"(d[100]), "+f"(d[101]), "+f"(d[102]), "+f"(d[103]),
      "+f"(d[104]), "+f"(d[105]), "+f"(d[106]), "+f"(d[107]), "+f"(d[108]), "+f"(d[109]), "+f"(d[110]), "+f"(d[111]),
      "+f"(d[112]), "+f"(d[113]), "+f"(d[114]), "+f"(d[115]), "+f"(d[116]), "+f"(d[117]), "+f"(d[118]), "+f"(d[119]),
      "+f"(d[120]), "+f"(d[121]), "+f"(d[122]), "+f"(d[123]), "+f"(d[124]), "+f"(d[125]), "+f"(d[126]), "+f"(d[127])
    : "r"(a0), "r"(a1), "r"(a2), "r"(a3), "l"(db), "r"(sd));
}
__device__ __forceinline__ void wgmma_rs_n64_tb(float (&d)[32], uint32_t a0, uint32_t a1, uint32_t a2, uint32_t a3, uint64_t db, int sd) {
  asm volatile("{\n.reg .pred p;\nsetp.ne.b32 p, %37, 0;\n"
    "wgmma.mma_async.sync.aligned.m64n64k16.f32.bf16.bf16 "
    "{%0, %1, %2, %3, %4, %5, %6, %7, %8, %9, %10, %11, %12, %13, %14, %15, "
    "%16, %17, %18, %19, %20, %21, %22, %23, %24, %25, %26, %27, %28, %29, %30, %31}, "
    "{%32, %33, %34, %35}, %36, p, 1, 1, 1;\n}"
    : "+f"(d[0]), "+f"(d[1]), "+f"(d[2]), "+f"(d[3]), "+f"(d[4]), "+f"(d[5]), "+f"(d[6]), "+f"(d[7]),
      "+f"(d[8]), "+f"(d[9]), "+f"(d[10]), "+f"(d[11]), "+f"(d[12]), "+f"(d[13]), "+f"(d[14]), "+f"(d[15]),
      "+f"(d[16]), "+f"(d[17]), "+f"(d[18]), "+f"(d[19]), "+f"(d[20]), "+f"(d[21]), "+f"(d[22]), "+f"(d[23]),
      "+f"(d[24]), "+f"(d[25]), "+f"(d[26]), "+f"(d[27]), "+f"(d[28]), "+f"(d[29]), "+f"(d[30]), "+f"(d[31])
    : "r"(a0), "r"(a1), "r"(a2), "r"(a3), "l"(db), "r"(sd));
}
__device__ __forceinline__ void wgmma_rs_n32(float (&d)[16], uint32_t a0, uint32_t a1, uint32_t a2, uint32_t a3, uint64_t db, int sd) {
  asm volatile("{\n.reg .pred p;\nsetp.ne.b32 p, %21, 0;\n"
    "wgmma.mma_async.sync.aligned.m64n32k16.f32.bf16.bf16 "
    "{%0, %1, %2, %3, %4, %5, %6, %7, %8, %9, %10, %11, %12, %13, %14, %15}, "
    "{%16, %17, %18, %19}, %20, p, 1, 1, 0;\n}"
    : "+f"(d[0]), "+f"(d[1]), "+f"(d[2]), "+f"(d[3]), "+f"(d[4]), "+f"(d[5]), "+f"(d[6]), "+f"(d[7]),
      "+f"(d[8]), "+f"(d[9]), "+f"(d[10]), "+f"(d[11]), "+f"(d[12]), "+f"(d[13]), "+f"(d[14]), "+f"(d[15])
    : "r"(a0), "r"(a1), "r"(a2), "r"(a3), "l"(db), "r"(sd));
}
__device__ __forceinline__ void wgmma_rs_n64(float (&d)[32], uint32_t a0, uint32_t a1, uint32_t a2, uint32_t a3, uint64_t db, int sd) {
  asm volatile("{\n.reg .pred p;\nsetp.ne.b32 p, %37, 0;\n"
    "wgmma.mma_async.sync.aligned.m64n64k16.f32.bf16.bf16 "
    "{%0, %1, %2, %3, %4, %5, %6, %7, %8, %9, %10, %11, %12, %13, %14, %15, "
    "%16, %17, %18, %19, %20, %21, %22, %23, %24, %25, %26, %27, %28, %29, %30, %31}, "
    "{%32, %33, %34, %35}, %36, p, 1, 1, 0;\n}"
    : "+f"(d[0]), "+f"(d[1]), "+f"(d[2]), "+f"(d[3]), "+f"(d[4]), "+f"(d[5]), "+f"(d[6]), "+f"(d[7]),
      "+f"(d[8]), "+f"(d[9]), "+f"(d[10]), "+f"(d[11]), "+f"(d[12]), "+f"(d[13]), "+f"(d[14]), "+f"(d[15]),
      "+f"(d[16]), "+f"(d[17]), "+f"(d[18]), "+f"(d[19]), "+f"(d[20]), "+f"(d[21]), "+f"(d[22]), "+f"(d[23]),
      "+f"(d[24]), "+f"(d[25]), "+f"(d[26]), "+f"(d[27]), "+f"(d[28]), "+f"(d[29]), "+f"(d[30]), "+f"(d[31])
    : "r"(a0), "r"(a1), "r"(a2), "r"(a3), "l"(db), "r"(sd));
}

__device__ __forceinline__ uint4 lds16(uint32_t a) {
  uint4 v; asm volatile("ld.shared.v4.u32 {%0, %1, %2, %3}, [%4];" : "=r"(v.x), "=r"(v.y), "=r"(v.z), "=r"(v.w) : "r"(a) : "memory"); return v;
}
__device__ __forceinline__ void sts16(uint32_t a, uint32_t x, uint32_t y, uint32_t z, uint32_t w) {
  asm volatile("st.shared.v4.u32 [%0], {%1, %2, %3, %4};" :: "r"(a), "r"(x), "r"(y), "r"(z), "r"(w) : "memory");
}
__device__ __forceinline__ uint32_t lds4(uint32_t a) { uint32_t v; asm volatile("ld.shared.u32 %0, [%1];" : "=r"(v) : "r"(a) : "memory"); return v; }
__device__ __forceinline__ uint32_t lds4v(uint32_t a) { uint32_t v; asm volatile("ld.volatile.shared.u32 %0, [%1];" : "=r"(v) : "r"(a) : "memory"); return v; }
__device__ __forceinline__ uint32_t bmul(uint32_t a, uint32_t b) { uint32_t r; asm("mul.rn.bf16x2 %0, %1, %2;" : "=r"(r) : "r"(a), "r"(b)); return r; }
__device__ __forceinline__ uint32_t badd(uint32_t a, uint32_t b) { uint32_t r; asm("add.rn.bf16x2 %0, %1, %2;" : "=r"(r) : "r"(a), "r"(b)); return r; }

__device__ __forceinline__ void ldsm4(uint32_t (&r)[4], uint32_t a) {
  asm volatile("ldmatrix.sync.aligned.m8n8.x4.shared.b16 {%0, %1, %2, %3}, [%4];" : "=r"(r[0]), "=r"(r[1]), "=r"(r[2]), "=r"(r[3]) : "r"(a) : "memory");
}
__device__ __forceinline__ uint32_t transpose8(uint32_t a) { uint32_t d; asm volatile("movmatrix.sync.aligned.m8n8.trans.b16 %0, %1;" : "=r"(d) : "r"(a)); return d; }

__device__ __forceinline__ void mma16816(float (&d)[4], const uint32_t (&a)[4], uint32_t b0, uint32_t b1) {
  asm volatile("mma.sync.aligned.m16n8k16.row.col.f32.bf16.bf16.f32 {%0, %1, %2, %3}, {%4, %5, %6, %7}, {%8, %9}, {%0, %1, %2, %3};"
               : "+f"(d[0]), "+f"(d[1]), "+f"(d[2]), "+f"(d[3]) : "r"(a[0]), "r"(a[1]), "r"(a[2]), "r"(a[3]), "r"(b0), "r"(b1));
}

#define EXP_SIDE 0
#define SIDE_AHEAD 3
#define ZERO_RD 4
#define CTX_SPLIT 8
#define CONV_EARLY 8
#define CONV_FENCE 12
#define CTX_LD 8
#define PEEK_JJ 7
#define PF_CTX 0
#define KV_ORDER 3
#define QFIRST 0
#define UNICAST 2
#define PF_MAPS 3
#define SINGLE0 2
#define LAST_DIRECT 1
#define HAND_NOW 1
#define GRID1 0
#define GRID2 0
#define GRID3 0
#define GRID_W 64
#define XMAP 2
#define XB 1
#define CONV_ARRIVE 13
#define ARRIVE_KK 12
#define SIDE_DELAY_NS 4000
#define KVH(h) (h)
#define HEAD_MAP 2
#define EARLY_LD 1
constexpr int RED_BAR = 6;
constexpr int CV_BAR = 5;
constexpr int PP_BAR = 3;
template <int V> struct Int { static constexpr int value = V; };
struct Ring {
  uint32_t slot, phase;
  __device__ __forceinline__ void next() { if (++slot == NSLOT) { slot = 0; phase ^= 1; } }
};
__device__ __forceinline__ uint32_t bar_addr(uint32_t sb, uint32_t i) { return sb + BARS + 8 * i; }

__device__ __forceinline__ int q_tile(int h, int j, int which) { return ((h < 8) == (which == 0)) ? 15 - j : j; }

constexpr int T_QB = QFIRST ? 0 : 4, IT_KV = QFIRST ? 7 : 0, IT_QB = QFIRST ? 0 : 64;
constexpr int KV_ISV  = KV_ORDER == 0 ? 0xC : KV_ORDER == 1 ? 0xA : KV_ORDER == 2 ? 0x6 : KV_ORDER == 3 ? 0xA : 0xC;
constexpr int KV_PART = KV_ORDER == 0 ? 0xA : KV_ORDER == 1 ? 0xC : KV_ORDER == 2 ? 0xC : KV_ORDER == 3 ? 0x3 : KV_ORDER == 4 ? 0x5 : 0x9;
constexpr int LAST_PART = KV_PART >> 3;
constexpr int T_FIRST = (((KV_PART >> 2) & 1) != LAST_PART ? 3 : 2) + QFIRST;
constexpr int T_LAST = 4 + QFIRST;
__device__ __forceinline__ int p1_isv(int j, int n) { return XMAP == 1 ? j & 1 : XMAP == 3 ? (j ^ n) & 1 : (KV_ISV >> n) & 1; }
__device__ __forceinline__ int att_head(int h, int which) { return (h & 7) + 8 * which; }
__device__ __forceinline__ int p1_pos(int h) { return HEAD_MAP == 2 ? (h < 9 ? h & 7 : h == 9 ? 7 : h - 9) : h & 7; }
__device__ __forceinline__ int p1_group(int h, int j) {
  return XMAP == 4 ? (j & 1) + 2 * (p1_pos(h) & 1) + 4 * (h >> 3) : XMAP == 2 ? (h & 7 & ~XB) | ((j & 1) * XB) : h & 7;
}
__device__ __forceinline__ int p1_head(int h, int j, int n) { return p1_group(h, j) + 8 * ((KV_PART >> n) & 1); }
__device__ __forceinline__ int p1_rows(int h, int j, int n) { return XMAP == 4 ? 4 * (p1_pos(h) >> 1) + (j >> 1) : XMAP == 0 ? q_tile(h, j, 0) : (q_tile(h, j, 0) & ~1) | (XMAP == 2 ? (h & XB) != 0 : n & 1); }
#define KV_FLAG(h) ((h) & 7)
#define KV_COUNT 32
#define F_PART1 (2 * own - 1)

__device__ __forceinline__ void load_tile4(uint32_t dst, const CUtensorMap* m, uint32_t full, int row, int blk0, int rank, bool shared, uint64_t pl = POL_NORMAL) {
  if (shared) {
    tma_ld3_mc(dst + rank * 16384, m, full, 0, row, blk0 + 2 * rank, pl);
  } else {
    tma_ld3(dst, m, full, 0, row, blk0, pl);
    tma_ld3(dst + 16384, m, full, 0, row, blk0 + 2, pl);
  }
}
__device__ __forceinline__ void producer_main(const Params& p, uint32_t sb, int h, int j) {
  const int rank = j & 1;
  Ring r{EARLY_LD, 0};
  auto wait_slot = [&](uint32_t period) {
    mbar_wait(bar_addr(sb, B_EMPTY + r.slot), r.phase ^ 1);
    if (period) { while (((uint32_t)clock() & (period - 1)) >= GRID_W) {} }
  };
  auto load_a = [&](int it, uint32_t dst, uint32_t full) {
    const unsigned u = it - IT_KV;
    if (u < 64) tma_ld2(dst, &p.ckv, full, (u & 15) * 64, p1_rows(h, j, u >> 4) * 128, pol((HINTS & 2) && u >= 48));
    else tma_ld2(dst, &p.x, full, (it < 71 ? it - IT_QB : it - 71) * 64, q_tile(h, j, it < 71) * 128, pol((HINTS & 64) && it >= 71));
  };
  uint32_t prev = 0;
#pragma unroll 1
  for (int it = EARLY_LD; it < P1_STEPS; it++) {
    wait_slot(it >= NSLOT ? GRID1 : 0);
    if (it > EARLY_LD && it <= P1_XS) load_a(it - 1, sb + QREG + ((it - 1) & 3) * 16384, prev);
    const uint32_t full = bar_addr(sb, B_FULL + r.slot), dst = sb + r.slot * SLOT;
    mbar_expect_tx(full, it < P1_XS ? 49152 : 32768);
    const unsigned u = it - IT_KV;
    if (u < 64) load_tile4(dst, p1_isv(j, u >> 4) ? &p.wuv : &p.wuk, full, (u & 15) * 64, p1_head(h, j, u >> 4) * 4, rank, !(UNICAST & 2), pol(HINTS & 1));
    else load_tile4(dst, &p.wq, full, (it < 71 ? it - IT_QB : it - 71) * 64, att_head(h, it < 71) * 4, rank, !(UNICAST & 2), pol((HINTS & 4) && it >= 71));
    prev = full;
    r.next();
    if (it == P1_XS) {
      wait_slot(0);
      const uint32_t f2 = bar_addr(sb, B_FULL + r.slot);
      mbar_expect_tx(f2, 32768);
      load_a(P1_XS, sb + r.slot * SLOT, f2);
      load_a(P1_XS + 1, sb + r.slot * SLOT + 16384, f2);
      r.next();
    }
  }
  const int qa = q_tile(h, j, 0), na = 2 * qa + 2, own = 2 * (qa & ~1) + 2;
#pragma unroll 1
  for (int f = 0; f < 68; f++) {
    const bool isK = (f == 0) || ((f & 1) && f < 67);
    const int i = isK ? (f + 1) >> 1 : (f - 1) >> 1, which = i >= na;
    if (f == 0 || f == F_PART1) mbar_wait(bar_addr(sb, B_KVOK + (f & 1)), 0);
    wait_slot(GRID2);
    const uint32_t full = bar_addr(sb, B_FULL + r.slot);
    mbar_expect_tx(full, 32768);
    const uint32_t src = (uint32_t)(((isK ? 0 : NH) + KVH(att_head(h, which))) * 32 + (which ? 33 - i : i)) * 32768;
    const uint64_t pl = pol(which ? (HINTS & 32) : (HINTS & 8));
    if (!(UNICAST & 1) && (i & ~1) != own) bulk_ld_mc(sb + r.slot * SLOT + rank * 16384, at<uint8_t>(g_kv, src + rank * 16384), 16384, full, pl);
    else bulk_ld_p(sb + r.slot * SLOT, at<uint8_t>(g_kv, src), 32768, full, pl);
    r.next();
  }
#pragma unroll 1
  for (int f = 0; f < 14; f++) {
    const int ch = f < 4 ? f & 1 : f >> 1, par = f < 4 ? f >> 1 : f & 1;
    wait_slot(GRID3);
    const uint32_t full = bar_addr(sb, B_FULL + r.slot);
    mbar_expect_tx(full, 32768);
    if (UNICAST & 4) {
      tma_ld5(sb + r.slot * SLOT, &p.wo, full, ch * 64, (par ? att_head(h ^ 8, 0) : att_head(h, 1)) * 8, pol(HINTS & 16));
      tma_ld5(sb + r.slot * SLOT + 16384, &p.wo, full, ch * 64, (par ? att_head(h ^ 8, 0) : att_head(h, 1)) * 8 + 4, pol(HINTS & 16));
    } else {
      tma_ld5_mc(sb + r.slot * SLOT + rank * 16384, &p.wo, full, ch * 64, (par ? att_head(h ^ 8, 0) : att_head(h, 1)) * 8 + rank * 4, pol(HINTS & 16));
    }
    r.next();
  }
}

__device__ __forceinline__ void helper_main(const Params& p, uint32_t sb, int h, int j, int w) {
  const unsigned epoch = load_epoch();
  const int cta = h * 8 + j, qb = q_tile(h, j, 1);
  const uint32_t qreg = sb + QREG + w * 32768, qfull = bar_addr(sb, B_QFULL + w);
  auto acquire = [&]() {
    flag_wait(flag_at(g_flags.kv_ready, KV_FLAG(h) * 2 + w), KV_COUNT, epoch);
    fence_async_all();
    mbar_arrive(bar_addr(sb, B_KVOK + w));
  };
  if (QFIRST) mbar_wait(bar_addr(sb, B_ST_Q + w), 0);
  mbar_wait(bar_addr(sb, B_ST_KV + w), 0);
  flag_signal(flag_at(g_flags.kv_ready, p1_group(h, j) * 2 + (LAST_PART ^ 1)));
  if (w != LAST_PART) acquire();
  mbar_wait(bar_addr(sb, B_ST_KV + 2 + w), 0);
  flag_signal(flag_at(g_flags.kv_ready, p1_group(h, j) * 2 + LAST_PART));
  const bool late = false;
  if (w == LAST_PART && !late) acquire();
  if (!QFIRST) { mbar_wait(bar_addr(sb, B_ST_Q + w), 0); asm volatile("fence.release.gpu;" ::: "memory"); }
  fence_async_all();
  mbar_wait(bar_addr(sb, B_QFREE + w), 0);
  mbar_expect_tx(qfull, 32768);
  bulk_ld(qreg, at<uint8_t>(g_qc, (cta * 2 + w) * 32768), 32768, qfull);
  if (w == LAST_PART && late) acquire();
  auto publish = [&]() { mbar_wait(bar_addr(sb, B_ST_CTX + w), 0); flag_signal(flag_at(g_flags.ctx_ready, cta * 2 + w)); };
  if (qb >= 8) publish();
  flag_wait(flag_at(g_flags.ctx_ready, (cta ^ 64) * 2 + (w ^ 1)), 1, epoch);
  mbar_arrive(bar_addr(sb, B_CTXOK + w));
  mbar_arrive(bar_addr(sb, B_DONE));
  if (qb < 8) publish();
  flag_wait(flag_at(g_flags.zero_ready, qb), 8, epoch);
  fence_async_all();
#pragma unroll 1
  for (int ch = 0; ch < (LAST_DIRECT ? 6 : 7); ch++) {
    mbar_wait(bar_addr(sb, B_S2_FULL + w * 4 + (ch & 3)), ch >> 2);
    tma_red2(&p.o, qreg + (ch & 3) * 8192, DA + ch * 64, qb * 128 + (w ^ 1) * 64);
    bulk_commit();
    if (ch < 3) { bulk_wait_read(); mbar_arrive(bar_addr(sb, B_S2_EMPTY + w * 4 + ch)); }
  }
  bulk_wait_read();
  GT(48 + w);
}

__device__ __forceinline__ void store_block(uint32_t base, uint32_t lanebase, const uint32_t (&pk)[16]) {
#pragma unroll
  for (int J = 0; J < 8; J += 2) stsm4(base + (lanebase ^ (J << 4)), pk[2 * J], pk[2 * J + 1], pk[2 * J + 2], pk[2 * J + 3]);
}
__device__ __forceinline__ void pack_chunks(uint32_t (&pk)[64], const float (&acc)[128]) {
#pragma unroll
  for (int i = 0; i < 64; i++) { const int e = 16 * (i >> 3) + 4 * (i & 3) + 2 * ((i >> 2) & 1); pk[i] = pack_bf16(acc[e], acc[e + 1]); }
}
__device__ __forceinline__ uint32_t chunk_off() { const uint32_t t = fresh_tid(); return (t & 96) * 32 + (t & 28) * 16 + (((t ^ (t >> 3)) & 3) << 4); }
__device__ __forceinline__ void warp_arrive(uint32_t bar, int lane) { __syncwarp(); if (lane == 0) mbar_arrive(bar); }

__device__ __forceinline__ void consumer_main(const Params& p, uint32_t sb, int h, int j, int w, int wq) {
  const int lane = threadIdx.x & 31;
  const int rank = j & 1;

  auto turn_begin = [&]() { named_sync(PP_BAR + w, 256); };
  auto turn_end = [&]() { named_arrive(PP_BAR + (w ^ 1), 256); };
  Ring r{0, 0};
  auto take = [&](uint32_t ready = 0) { const uint32_t sl = r.slot; mbar_wait_unless(ready, bar_addr(sb, B_FULL + sl), r.phase); r.next(); return sl; };
  uint32_t rdy0 = 0, rdy1 = 0;
  auto peek2 = [&]() { Ring q = r; rdy0 = mbar_test(bar_addr(sb, B_FULL + q.slot), q.phase); q.next(); rdy1 = mbar_test(bar_addr(sb, B_FULL + q.slot), q.phase); };
  auto give = [&](uint32_t sl) {
    if (UNICAST & 8) { if (lane == 0) mbar_arrive(bar_addr(sb, B_EMPTY + sl)); }
    else if (lane < 2) mbar_arrive_remote(bar_addr(sb, B_EMPTY + sl), rank ^ lane);
  };
  float acc[128];
#pragma unroll
  for (int i = 0; i < 128; i++) acc[i] = 0.f;
  uint32_t pk[64];
#pragma unroll
  for (int i = 0; i < 64; i++) pk[i] = 0;
  reg_fence(acc);
  reg_fence(pk);
  cluster_wait();
  TS(0);
  const uint32_t qreg = sb + QREG + w * 32768;
  {
    uint32_t xs = 0;
    uint4* row = nullptr;
    int it = 0;
#pragma unroll 1
    for (int t = 0; t < 6; t++) {
      const bool isq = t == T_QB || t == 5;
      const uint32_t abase = sb + QREG + (w ^ (t == T_QB)) * 8192;
#pragma unroll 1
      for (int u = 0, end = it + (isq ? 7 : 16); it < end; u++) {
        const bool two = !(isq && u == 1) && it >= SINGLE0, last = it == P1_XS;
        const uint32_t w0 = take(rdy0);
        TSC(1, it == 0);
        if (last) { xs = take(rdy1); rdy1 = 0; }
        const uint32_t xb = sb + xs * SLOT + w * 8192;
        const uint64_t da = desc_k(last ? xb : abase + (it & 3) * 16384), db = desc_mn(sb + w0 * SLOT);
        turn_begin();
        wg_fence();
#pragma unroll
        for (int kk = 0; kk < 4; kk++) wgmma_ss_n256_tb(acc, desc_add(da, kk * 32), desc_add(db, kk * 2048), (u | kk) != 0);
        wg_commit();
        uint32_t w1 = w0;
        if (two) {
          w1 = take(rdy1);
          const uint64_t da1 = desc_k(last ? xb + 16384 : abase + ((it + 1) & 3) * 16384), db1 = desc_mn(sb + w1 * SLOT);
          wg_fence();
#pragma unroll
          for (int kk = 0; kk < 4; kk++) wgmma_ss_n256_tb(acc, desc_add(da1, kk * 32), desc_add(db1, kk * 2048), 1);
          wg_commit();
          turn_end();
          wg_wait<1>();
          give(w0);
        } else {
          turn_end();
        }
        if (t > 0) {
          uint32_t m = isq ? 0xC0380403u >> (8 * u) : 1u << u;
          asm volatile("" : "+r"(m));
#pragma unroll
          for (int i = 0; i < 16; i++)
            if (m & (1u << (i >> 1))) row[(i >> 1) * 256 + (i & 1) * 32] = make_uint4(pk[4 * i], pk[4 * i + 1], pk[4 * i + 2], pk[4 * i + 3]);
        }
        peek2();
        wg_wait<0>();
        give(w1);
        it += 1 + two;
      }
      reg_fence(acc);
      if (t == T_QB + 1 || t == T_FIRST || t == T_LAST)
        warp_arrive(bar_addr(sb, (t == T_QB + 1 ? B_ST_Q : t == T_LAST ? B_ST_KV + 2 : B_ST_KV) + w), lane);
      pack_chunks(pk, acc);
      const int n = t - QFIRST;
      row = at<uint4>(t != T_QB ? (const void*)g_kv : (const void*)g_qc, chunk_off() +
                      (t != T_QB ? (uint32_t)((p1_isv(j, n) * NH + KVH(p1_head(h, j, n))) * 32 + p1_rows(h, j, n) * 2 + w) : (uint32_t)((h * 8 + j) * 2 + w)) * 32768);
      TS(2 + t);
    }
    give(xs);
    const uint32_t qa = qreg + chunk_off();
#pragma unroll
    for (int i = 0; i < 16; i++) sts16(qa + (i >> 1) * 4096 + (i & 1) * 512, pk[4 * i], pk[4 * i + 1], pk[4 * i + 2], pk[4 * i + 3]);
    fence_async_smem();
  }
  TS(8);

  constexpr float SC = 0.0625f * 1.4426950408889634f;
#pragma unroll 1
  for (int which = 0; which < 2; which++) {
    float s[32];
#pragma unroll
    for (int i = 0; i < 32; i++) s[i] = 0.f;
    uint32_t pa[16], pb[16];
    float m0 = 0.f, m1 = 0.f, l0 = 0.f, l1 = 0.f;
    const uint64_t dq = desc_64(qreg);
    uint64_t dk = 0, dqq = 0, dv = 0;
    auto prep_qk = [&](uint32_t kaddr) { dk = desc_64(kaddr); dqq = dq + (kaddr >> 31); asm volatile("" : "+l"(dk), "+l"(dqq)); };
    auto prep_pv = [&](uint32_t vaddr) { dv = desc_64(vaddr); asm volatile("" : "+l"(dv)); };
    auto issue_qk = [&]() {
#pragma unroll
      for (int kk = 0; kk < 16; kk++)
        wgmma_ss_n64(s, desc_add(dqq, (kk >> 1) * 4096 + (kk & 1) * 32), desc_add(dk, (kk >> 1) * 4096 + (kk & 1) * 32), kk != 0);
    };
    auto issue_pv = [&](int accumulate) {
#pragma unroll
      for (int kk = 0; kk < 4; kk++)
        wgmma_rs_n256_tb(acc, pa[4 * kk], pa[4 * kk + 1], pa[4 * kk + 2], pa[4 * kk + 3], desc_add(dv, kk * 1024), accumulate | kk);
    };
    auto mask_diag = [&]() {
      const int d = 16 * wq + (lane >> 2) - 2 * (lane & 3);
#pragma unroll
      for (int jj = 0; jj < 8; jj++) {
        if (8 * jj > d)     { s[4 * jj] = -INFINITY;     if (jj < 7) s[4 * jj + 6] = -INFINITY; }
        if (8 * jj + 1 > d) { s[4 * jj + 1] = -INFINITY; if (jj < 7) s[4 * jj + 7] = -INFINITY; }
      }
    };
    float a0, a1;
    auto softmax = [&]() -> bool {
      float x0 = fmaxf(s[0], s[1]), x1 = fmaxf(s[2], s[3]);
#pragma unroll
      for (int jj = 1; jj < 8; jj++) {
        x0 = fmaxf(x0, fmaxf(s[4 * jj], s[4 * jj + 1]));
        x1 = fmaxf(x1, fmaxf(s[4 * jj + 2], s[4 * jj + 3]));
      }
      x0 = fmaxf(x0, __shfl_xor_sync(0xffffffffu, x0, 1));
      x1 = fmaxf(x1, __shfl_xor_sync(0xffffffffu, x1, 1));
      x0 = fmaxf(x0, __shfl_xor_sync(0xffffffffu, x0, 2));
      x1 = fmaxf(x1, __shfl_xor_sync(0xffffffffu, x1, 2));
      const bool grow = __any_sync(0xffffffffu, fmaxf(x0 - m0, x1 - m1) * SC > 8.f);
      if (grow) {
        x0 = fmaxf(x0, m0); x1 = fmaxf(x1, m1);
        a0 = ex2((m0 - x0) * SC); a1 = ex2((m1 - x1) * SC);
        m0 = x0; m1 = x1;
        l0 *= a0; l1 *= a1;
      }
      const float b0 = -m0 * SC, b1 = -m1 * SC;
      float t0 = 0.f, t1 = 0.f, t2 = 0.f, t3 = 0.f;
#pragma unroll
      for (int jj = 0; jj < 8; jj++) {
        s[4 * jj]     = ex2(fmaf(s[4 * jj], SC, b0));
        s[4 * jj + 1] = ex2(fmaf(s[4 * jj + 1], SC, b0));
        s[4 * jj + 2] = ex2(fmaf(s[4 * jj + 2], SC, b1));
        s[4 * jj + 3] = ex2(fmaf(s[4 * jj + 3], SC, b1));
        t0 += s[4 * jj]; t1 += s[4 * jj + 1]; t2 += s[4 * jj + 2]; t3 += s[4 * jj + 3];
      }
      l0 += t0 + t1; l1 += t2 + t3;
      return grow;
    };
    auto softmax_fast = [&](uint32_t (&pp)[16], auto first, auto hook) -> bool {
      const float b0 = -m0 * SC, b1 = -m1 * SC;
      float t0 = 0.f, t1 = 0.f, t2 = 0.f, t3 = 0.f;
#pragma unroll
      for (int jj = 0; jj < 8; jj++) {
        const float e0 = ex2(fmaf(s[4 * jj], SC, b0)), e1 = ex2(fmaf(s[4 * jj + 1], SC, b0));
        const float e2 = ex2(fmaf(s[4 * jj + 2], SC, b1)), e3 = ex2(fmaf(s[4 * jj + 3], SC, b1));
        hook(jj, e0);
        pp[2 * jj] = pack_bf16(e0, e1); pp[2 * jj + 1] = pack_bf16(e2, e3);
        if (jj == 0) { t0 = e0; t1 = e1; t2 = e2; t3 = e3; } else { t0 += e0; t1 += e1; t2 += e2; t3 += e3; }
      }
      t0 += t1; t2 += t3;
      bool redo = __any_sync(0xffffffffu, !(t0 + t2 <= 16777216.f));
      if (decltype(first)::value) {
        uint32_t u0 = __ballot_sync(0xffffffffu, t0 >= 1.52587890625e-05f), u1 = __ballot_sync(0xffffffffu, t2 >= 1.52587890625e-05f);
        u0 |= u0 >> 1; u1 |= u1 >> 1;
        redo |= (((u0 | (u0 >> 2)) & (u1 | (u1 >> 2))) & 0x11111111u) != 0x11111111u;
      }
      if (!redo) { l0 += t0; l1 += t2; }
      return redo;
    };
    auto rescale = [&]() {
#pragma unroll
      for (int i = 0; i < 32; i++) { acc[4 * i] *= a0; acc[4 * i + 1] *= a0; acc[4 * i + 2] *= a1; acc[4 * i + 3] *= a1; }
    };
    auto to_p = [&](uint32_t (&pp)[16]) {
#pragma unroll
      for (int i = 0; i < 16; i++) pp[i] = pack_bf16(s[2 * i], s[2 * i + 1]);
    };
    auto q_free = [&]() { if (lane == 0) mbar_arrive(bar_addr(sb, B_QFREE + w)); };

    const int n = 2 * q_tile(h, j, which) + 1 + (w ^ which);
    uint32_t ks = take(rdy0);
    TS(9 + 5 * which);
    prep_qk(sb + ks * SLOT);
    turn_begin();
    TS(20 + 10 * which);
    wg_fence();
    issue_qk();
    wg_commit();
    turn_end();
    if (which == 1) give(take(rdy1));
    TS(22 + 10 * which);
    wg_wait<0>();
    TS(21 + 10 * which);
    reg_fence(s);
    give(ks);
    if (which == 0 && n == 1) q_free();
    if (which == 1 || n == 1) mask_diag();
    {
      const uint4* dst = at<uint4>(g_qc, (uint32_t)((h * 8 + j) * 2 + w) * 32768 + (fresh_tid() & 127) * 16);
      const bool redo = softmax_fast(pa, Int<1>(), [&](int jj, float e) {
        if (jj == PEEK_JJ) peek2();
        const int i = CTX_SPLIT + jj;
        if (i < 16)
          asm volatile("{\n.reg .pred p, q;\nsetp.ne.b32 q, %6, 0;\nsetp.geu.and.f32 p, %5, 0fBF800000, q;\n@p st.global.v4.u32 [%0], {%1, %2, %3, %4};\n}"
                       :: "l"(dst + i * 128), "r"(pk[4 * (i & 15)]), "r"(pk[4 * (i & 15) + 1]), "r"(pk[4 * (i & 15) + 2]), "r"(pk[4 * (i & 15) + 3]), "f"(e), "r"(which) : "memory");
      });
      if (redo) {
        m0 = -INFINITY; m1 = -INFINITY;
        softmax();
        to_p(pa);
      }
    }
    if (which == 1) warp_arrive(bar_addr(sb, B_ST_CTX + w), lane);
    TS(10 + 5 * which);
#pragma unroll 1
    for (int jj = 1; jj < n; jj++) {
      ks = take(rdy0);
      const uint32_t vs = take(rdy1);
      prep_qk(sb + ks * SLOT);
      prep_pv(sb + vs * SLOT);
      TSC(23 + 10 * which, jj == 1);
      turn_begin();
      TSC(24 + 10 * which, jj == 1);
      TSC(26 + 10 * which, jj == n - 1);
      wg_fence();
      issue_qk();
      wg_commit();
      issue_pv(jj > 1);
      wg_commit();
      turn_end();
      wg_wait<1>();
      TSC(25 + 10 * which, jj == 1);
      reg_fence(s);
      give(ks);
      if (jj == n - 1 && which == 0) { q_free(); mask_diag(); }
      if (PF_CTX && which == 1 && jj == max(n - PF_CTX, 1)) {
        const uint8_t* src = at<const uint8_t>(g_qc, (uint32_t)(((h ^ 8) * 8 + j) * 2 + (w ^ 1)) * 32768 + (fresh_tid() & 127) * 128);
        asm volatile("prefetch.global.L2 [%0];" :: "l"(src));
        asm volatile("prefetch.global.L2 [%0];" :: "l"(src + 16384));
      }
      if (softmax_fast(pb, Int<0>(), [](int, float) {})) {
        wg_wait<0>();
        reg_fence(acc);
        if (softmax()) rescale();
        to_p(pb);
      }
      peek2();
      wg_wait<0>();
      reg_fence(acc);
      reg_fence(pa);
      give(vs);
#pragma unroll
      for (int i = 0; i < 16; i++) pa[i] = pb[i] | (vs >> 8);
    }
    TS(11 + 5 * which);
    if (which == 0) { give(take(rdy0)); rdy0 = rdy1; }
    {
      const uint32_t vs = take(rdy0);
      prep_pv(sb + vs * SLOT);
      TS(27 + 10 * which);
      turn_begin();
      TS(28 + 10 * which);
      wg_fence();
      issue_pv(n > 1);
      wg_commit();
      turn_end();
      l0 += __shfl_xor_sync(0xffffffffu, l0, 1); l1 += __shfl_xor_sync(0xffffffffu, l1, 1);
      l0 += __shfl_xor_sync(0xffffffffu, l0, 2); l1 += __shfl_xor_sync(0xffffffffu, l1, 2);
      asm("rcp.approx.ftz.f32 %0, %0;" : "+f"(l0));
      asm("rcp.approx.ftz.f32 %0, %0;" : "+f"(l1));
      peek2();
      if (which == 0) mbar_wait(bar_addr(sb, B_QFULL + w), 0);
      wg_wait<0>();
      reg_fence(acc);
      reg_fence(pa);
      give(vs);
    }
    TS(12 + 5 * which);
    {
      const uint4* dst = at<uint4>(g_qc, (uint32_t)((h * 8 + j) * 2 + w) * 32768 + (fresh_tid() & 127) * 16);
#pragma unroll
      for (int i = 0; i < 16; i++) {
        const int c = (i & 1) ? (i >> 1) + 8 : i >> 1;
        pk[4 * c]     = pack_bf16(acc[8 * c] * l0, acc[8 * c + 1] * l0);
        pk[4 * c + 1] = pack_bf16(acc[8 * c + 2] * l1, acc[8 * c + 3] * l1);
        pk[4 * c + 2] = pack_bf16(acc[8 * c + 4] * l0, acc[8 * c + 5] * l0);
        pk[4 * c + 3] = pack_bf16(acc[8 * c + 6] * l1, acc[8 * c + 7] * l1);
        if (c < CTX_SPLIT)
          asm volatile("{\n.reg .pred p;\nsetp.eq.b32 p, %5, 0;\n@p st.global.v4.u32 [%0], {%1, %2, %3, %4};\n}"
                       :: "l"(dst + c * 128), "r"(pk[4 * c]), "r"(pk[4 * c + 1]), "r"(pk[4 * c + 2]), "r"(pk[4 * c + 3]), "r"(which) : "memory");
      }
    }
    TS(13 + 5 * which);
  }

  {
    float oa[32], ob[32];
#pragma unroll
    for (int i = 0; i < 32; i++) { oa[i] = 0.f; ob[i] = 0.f; }
    uint32_t pk2[64];
    auto stage = [&](float (&o)[32], int ch) {
      reg_fence(o);
      uint32_t q[16];
#pragma unroll
      for (int i = 0; i < 16; i++) q[i] = pack_bf16(o[2 * i], o[2 * i + 1]);
      if (ch >= 4) mbar_wait(bar_addr(sb, B_S2_EMPTY + w * 4 + (ch & 3)), 0);
      store_block(qreg + (ch & 3) * 8192, lane_base16(), q);
    };
    auto hand_over = [&](int ch) {
      fence_async_smem();
      warp_arrive(bar_addr(sb, B_S2_FULL + w * 4 + (ch & 3)), lane);
    };
    uint32_t prev = 0;
    auto half = [&](int f, float (&o)[32], uint32_t (&a)[64], int accumulate) {
      const uint32_t sl = take(rdy0);
      const uint64_t d = desc_mn(sb + sl * SLOT);
      turn_begin();
      TS(40 + f);
      wg_fence();
#pragma unroll
      for (int kk = 0; kk < 16; kk++) {
        wgmma_rs_n64_tb(o, a[4 * kk], a[4 * kk + 1], a[4 * kk + 2], a[4 * kk + 3], desc_add(d, kk * 2048), accumulate | kk);
        if (kk == ARRIVE_KK && (f < 13 || w == 0)) turn_end();
      }
      wg_commit();
      if (f < 13) rdy0 = mbar_test(bar_addr(sb, B_FULL + r.slot), r.phase);
      wg_wait<1>();
      if (f >= 1 && f <= 9) give(prev);
      prev = sl;
    };
    auto load_ctx = [&](auto h0) {
      constexpr int I0 = decltype(h0)::value ? CTX_LD : 0, NL = decltype(h0)::value ? 16 - CTX_LD : CTX_LD;
      const uint4* src = at<const uint4>(g_qc, (uint32_t)(((h ^ 8) * 8 + j) * 2 + (w ^ 1)) * 32768 + (fresh_tid() & 127) * 16);
#pragma unroll
      for (int i = I0; i < I0 + NL; i++) { const uint4 v = __ldcg(src + i * 128); pk2[4 * i] = v.x; pk2[4 * i + 1] = v.y; pk2[4 * i + 2] = v.z; pk2[4 * i + 3] = v.w; }
    };
    half(0, oa, pk, 0);
    mbar_wait(bar_addr(sb, B_CTXOK + w), 0);
    load_ctx(Int<0>());
    half(1, ob, pk, 0);
    load_ctx(Int<1>());
    half(2, oa, pk2, 1);
#pragma unroll 1
    for (int i = 0; i < 3; i++) {
      half(4 * i + 3, ob, pk2, 1);
      if (i == 0) stage(oa, 0); else if (!HAND_NOW) hand_over(2 * i);
      half(4 * i + 4, oa, pk, 0);
      if (i == 0) hand_over(0);
      stage(ob, 2 * i + 1);
      if (HAND_NOW) hand_over(2 * i + 1);
      half(4 * i + 5, oa, pk2, 1);
      if (!HAND_NOW) hand_over(2 * i + 1);
      if (i == 2) break;
      half(4 * i + 6, ob, pk, 0);
      stage(oa, 2 * i + 2);
      if (HAND_NOW) hand_over(2 * i + 2);
    }
    wg_wait<0>();
    reg_fence(pk);
    reg_fence(pk2);
    stage(oa, 6);
    fence_async_smem();
    named_sync(1 + w, 128);
    if (wq == 0 && lane == 0) {
      tma_red2(&p.o, qreg + 2 * 8192, DA + 6 * 64, q_tile(h, j, 1) * 128 + (w ^ 1) * 64);
      bulk_commit();
      bulk_wait_read();
    }
  }
  TS(19);
  TDUMP();
}

namespace ssm {
constexpr int NCH = DA / NCONV;
constexpr int NS = 8, NP = 6;
constexpr uint32_t X0 = 384;
constexpr uint32_t HO = X0 + 4096;
constexpr uint32_t HE = HO + HO_STRIDE + 64;
constexpr uint32_t SSLOT = HE + 4096 + 64;
constexpr uint32_t PART = 264 * 16;
constexpr uint32_t OFF_P = NS * SSLOT, OFF_D = OFF_P + NP * 4 * PART, END = OFF_D + NCH * 4;
static_assert(SSLOT % 128 == 0 && HO % 128 == 0 && END <= BARS, "smem");
enum : uint32_t { B_FULL = 0, B_EMPTY = NS, B_PFULL = 2 * NS, B_PEMPTY = 2 * NS + NP };
__device__ __forceinline__ int channel(int cidx, int i) { return (i >> 4) * 64 + cidx * 16 + (i & 15); }

__device__ __forceinline__ void producer(const Params& p, uint32_t sb, int cidx, unsigned epoch) {
#pragma unroll 1
  for (int i = 0; i < NCH; i++) {
    const int s = i % NS, ch = channel(cidx, i);
    const uint32_t full = bar_addr(sb, B_FULL + s), dst = sb + s * SSLOT;
    mbar_wait(bar_addr(sb, B_EMPTY + s), ((i / NS) & 1) ^ 1);
    mbar_expect_tx(full, 4096 + 4128 + 4096);
    bulk_ld(dst + HE, at<uint8_t>(p.a_ssmk, ch * 4096), 4096, full);
    if ((i & 15) == 0) { flag_wait(flag_at(g_flags.x_ready, i >> 4), NMAIN, epoch); fence_async_all(); }
    bulk_ld(dst + HO, at<uint8_t>(g_ho, ch * HO_STRIDE), 4128, full);
    bulk_ld(dst + X0, at<uint8_t>(g_xs, ch * 4096), 4096, full);
  }
}

__device__ __forceinline__ void reducer(uint32_t sb, int cidx, int rw) {
  uint32_t n = 0;
#pragma unroll 1
  for (int i = rw; i < NCH; i += 3, n++) {
    const uint32_t b = rw + 3 * (n & 1), pb = sb + OFF_P + b * 4 * PART;
    uint8_t* dst = at<uint8_t>(g_xs, channel(cidx, i) * 4096);
    mbar_wait(bar_addr(sb, B_PFULL + b), (n >> 1) & 1);
    asm volatile("cp.async.bulk.global.shared::cta.bulk_group [%0], [%1], 4096;" :: "l"(dst), "r"(pb + 3 * PART) : "memory");
    bulk_commit();
    bulk_wait_all();
#pragma unroll
    for (int k = 2; k >= 0; k--)
      asm volatile("cp.reduce.async.bulk.global.shared::cta.bulk_group.add.noftz.bf16 [%0], [%1], 4096;" :: "l"(dst), "r"(pb + k * PART) : "memory");
    bulk_commit();
    bulk_wait_read();
    mbar_arrive(bar_addr(sb, B_PEMPTY + b));
    if (((i + 3) >> 4) != (i >> 4)) {
      bulk_wait_all();
      fence_async_all();
      flag_signal(flag_at(g_flags.z_ready, i >> 4));
    }
  }
}

__device__ __forceinline__ void mma_warpgroup(uint32_t sb, int w) {
  const int lane = threadIdx.x & 31, g = lane >> 2, c = lane & 3, wq = (threadIdx.x >> 5) & 3;
  const uint32_t aoff = ((g & 1) ? HO + 30 : HE) + (16 * wq - g + 2 * c) * 2;
  const uint32_t poff = OFF_P + wq * PART + (2 * wq + lane) * 16;
  const uint32_t dmask = (wq == 0 && c == (g >> 1)) ? ((g & 1) ? 0xffff0000u : 0xffffu) : 0u;
  float acc[8][16];
  uint32_t fa[16][4];
#pragma unroll
  for (int e = 0; e < 8; e++)
#pragma unroll
    for (int i = 0; i < 16; i++) acc[e][i] = 0.f;
  auto load_a = [&](int m, uint32_t ad) {
    fa[m][0] = lds4(ad + m * 256 + 16); fa[m][1] = lds4(ad + m * 256 + 144); fa[m][2] = lds4(ad + m * 256); fa[m][3] = lds4(ad + m * 256 + 128);
  };
  if (w == 1) named_arrive(PP_BAR, 256);
  mbar_wait(bar_addr(sb, B_FULL + w), 0);
#pragma unroll
  for (int m = 0; m < 16; m++) load_a(m, sb + w * SSLOT + aoff);
  uint32_t dd = lds4(sb + OFF_D + w * 4);
  if (threadIdx.x == 128) { GT(12); PT(10); }
  uint32_t pb = w, pphase = 1;
#pragma unroll 1
  for (int i = w; i < NCH; i += 2) {
    fa[0][2] = badd(fa[0][2], dd & dmask);
    const uint64_t db = (uint64_t)((((sb + (i % NS) * SSLOT + X0 - 16) & 0x3FFFF) >> 4) | (1u << 16)) | ((uint64_t)8 << 32);
    named_sync(PP_BAR + w, 256);
    wg_fence();
#pragma unroll
    for (int r = 0; r < 16; r++) {
      auto mm = [&](int e, int m) { wgmma_rs_n32(acc[e], fa[m][0], fa[m][1], fa[m][2], fa[m][3], db + (int64_t)(32 * e - 16 * m), m != 0); };
      mm(7, r);
      if (r < 14) mm(6, r); else mm(0, r - 14);
      if (r < 12) mm(5, r); else mm(1, r - 12);
      if (r < 10) mm(4, r); else mm(2, r - 10);
      if ((r & 1) == 0) mm(3, r >> 1);
      if (r == CONV_ARRIVE && (i + 1 < NCH)) named_arrive(PP_BAR + (w ^ 1), 256);
    }
    wg_commit();
    const int nx = i + 2 < NCH ? i + 2 : i;
    mbar_wait(bar_addr(sb, B_FULL + nx % NS), (nx / NS) & 1);
    mbar_wait(bar_addr(sb, B_PEMPTY + pb), pphase);
    const uint32_t ad = sb + (nx % NS) * SSLOT + aoff, pa = sb + pb * 4 * PART + poff;
    wg_wait<0>();
#pragma unroll
    for (int e = 0; e < 8; e++) reg_fence(acc[e]);
#pragma unroll
    for (int m = 0; m < 16; m++) reg_fence(fa[m]);
    if (lane == 0) mbar_arrive(bar_addr(sb, B_EMPTY + i % NS));
#pragma unroll
    for (int e = 0; e < 8; e++) {
      if (e < CONV_EARLY) load_a(e, ad);
      uint32_t u[4];
#pragma unroll
      for (int j = 0; j < 4; j++) {
        const int T = 4 * e + j, U = T - 1;
        float lo = acc[e][4 * j], hi = acc[e][4 * j + 1];
        if (T > 0) { lo += acc[U >> 2][4 * (U & 3) + 2]; hi += acc[U >> 2][4 * (U & 3) + 3]; }
        u[j] = pack_bf16(lo, hi);
      }
      asm volatile("stmatrix.sync.aligned.m8n8.x4.trans.shared.b16 [%0], {%1, %2, %3, %4};" :: "r"(pa + e * 512), "r"(u[0]), "r"(u[1]), "r"(u[2]), "r"(u[3]) : "memory");
    }
    dd = lds4(sb + OFF_D + nx * 4);
#pragma unroll
    for (int m = CONV_EARLY; m < CONV_FENCE; m++) load_a(m, ad);
    fence_async_smem();
    warp_arrive(bar_addr(sb, B_PFULL + pb), lane);
#pragma unroll
    for (int m = CONV_FENCE; m < 16; m++) load_a(m, ad);
    pb += 2;
    if (pb >= NP) { pb -= NP; pphase ^= 1; }
  }
  if (threadIdx.x == 128) { PT(9); GT(13); }
}

__device__ __forceinline__ void init(const Params& p, uint32_t sb, int cidx) {
  const uint32_t t = threadIdx.x;
  if (t < NCH) {
    const uint32_t d = (uint32_t)__ldg(reinterpret_cast<const unsigned short*>(p.a_D + channel(cidx, t))) * 0x10001u;
    asm volatile("st.shared.u32 [%0], %1;" :: "r"(sb + OFF_D + t * 4), "r"(d) : "memory");
  }
#pragma unroll 1
  for (uint32_t u = t; u < NS * 32; u += 128) {
    const uint32_t r = u & 31;
    if (r < 28) sts16(sb + (u >> 5) * SSLOT + (r < 24 ? r * 16 : HE - 64 + (r - 24) * 16), 0, 0, 0, 0);
    if (u < NP * 32) sts16(sb + OFF_P + (u >> 3) * PART + (u & 7) * 16, 0, 0, 0, 0);
  }
  if (t == 0) {
    for (int i = 0; i < NS; i++) { mbar_init(bar_addr(sb, B_FULL + i), 1); mbar_init(bar_addr(sb, B_EMPTY + i), 4); }
    for (int i = 0; i < NP; i++) { mbar_init(bar_addr(sb, B_PFULL + i), 4); mbar_init(bar_addr(sb, B_PEMPTY + i), 1); }
  }
  fence_async_smem();
}

__device__ __forceinline__ void side_prepare(const Params& p, int cta, int rd) {
  const int lane = threadIdx.x & 31, t0 = 16 * cta + 8 * (lane & 1);
  if (EXP_SIDE & 16) { if (lane == 0) flag_signal_after_bulk(flag_at(g_flags.x_ready, rd)); return; }
#pragma unroll 1
  for (int ch = 64 * rd + (lane & ~1); ch < 64 * rd + 64; ch += 32) {
    const uint4 sv = __ldg(at<const uint4>(p.a_shift, ch * 8));
    const uint32_t* kp = at<const uint32_t>(p.a_k, (t0 * DA + ch) * 2);
    const uint32_t* vp = at<const uint32_t>(p.a_v, (t0 * DA + ch) * 2);
    uint32_t k0 = 0, k1 = 0, k2 = 0, kk[8], x[8];
    if (t0 > 0) { k0 = __ldg(kp - 3 * (DA / 2)); k1 = __ldg(kp - 2 * (DA / 2)); k2 = __ldg(kp - DA / 2); }
#pragma unroll
    for (int i = 0; i < 8; i++) { kk[i] = __ldg(kp + i * (DA / 2)); x[i] = __ldg(vp + i * (DA / 2)); }
    const uint32_t sh0 = __byte_perm(sv.x, sv.z, 0x5410), sh1 = __byte_perm(sv.x, sv.z, 0x7632);
    const uint32_t sh2 = __byte_perm(sv.y, sv.w, 0x5410), sh3 = __byte_perm(sv.y, sv.w, 0x7632);
#pragma unroll
    for (int i = 0; i < 8; i++) {
      uint32_t ks = bmul(k0, sh3);
      ks = badd(ks, bmul(k1, sh2)); ks = badd(ks, bmul(k2, sh1)); ks = badd(ks, bmul(kk[i], sh0));
      x[i] = bmul(ks, x[i]);
      k0 = k1; k1 = k2; k2 = kk[i];
    }
    uint4* dst = at<uint4>(g_xs, ch * 4096 + t0 * 2);
    if ((EXP_SIDE & 4) && (x[0] ^ x[1] ^ x[2] ^ x[3] ^ x[4] ^ x[5] ^ x[6] ^ x[7]) != 0x12345) continue;
    dst[0]   = make_uint4(__byte_perm(x[7], x[6], 0x5410), __byte_perm(x[5], x[4], 0x5410), __byte_perm(x[3], x[2], 0x5410), __byte_perm(x[1], x[0], 0x5410));
    dst[256] = make_uint4(__byte_perm(x[7], x[6], 0x7632), __byte_perm(x[5], x[4], 0x7632), __byte_perm(x[3], x[2], 0x7632), __byte_perm(x[1], x[0], 0x7632));
  }
  if (!(EXP_SIDE & 8)) {
    const int hc = 64 * rd + (cta >> 1), r0 = (cta & 1) * 128 + lane;
    const uint4* src = at<const uint4>(p.a_ssmk, hc * 4096 + r0 * 16);
    uint4* dst = at<uint4>(g_ho, hc * HO_STRIDE + r0 * 16);
    uint4 w[4];
    uint32_t nx[4];
#pragma unroll
    for (int i = 0; i < 4; i++) { w[i] = __ldg(src + 32 * i); nx[i] = r0 + 32 * i < 255 ? __ldg(reinterpret_cast<const uint32_t*>(src + 32 * i + 1)) : 0u; }
#pragma unroll
    for (int i = 0; i < 4; i++)
      dst[32 * i + 2] = make_uint4(__byte_perm(w[i].x, w[i].y, 0x5432), __byte_perm(w[i].y, w[i].z, 0x5432), __byte_perm(w[i].z, w[i].w, 0x5432), __byte_perm(w[i].w, nx[i], 0x5432));
    const uint32_t h0 = __shfl_sync(0xffffffffu, w[0].x, 0);
    if (r0 < 2) dst[0] = make_uint4(0, 0, 0, r0 ? h0 << 16 : 0u);
  }
  __syncwarp();
  if (lane == 0) { if (EXP_SIDE & 2) flag_signal_after_bulk(flag_at(g_flags.x_ready, rd)); else flag_signal(flag_at(g_flags.x_ready, rd)); }
}
__device__ __forceinline__ void side_finish(const Params& p, int cta, int rd) {
  const int lane = threadIdx.x & 31, t0 = 16 * cta + 8 * (lane & 1);
#pragma unroll 1
  for (int ch = 64 * rd + (lane & ~1); ch < 64 * rd + 64; ch += 32) {
    const uint4* src = at<const uint4>(g_xs, ch * 4096 + t0 * 2);
    const uint32_t* qp = at<const uint32_t>(p.a_q, (t0 * DA + ch) * 2);
    uint32_t* op = at<uint32_t>(p.out, (t0 * OUTW + ch) * 2);
    const uint4 z0 = __ldcg(src), z1 = __ldcg(src + 256);
    uint32_t q[8];
#pragma unroll
    for (int i = 0; i < 8; i++) q[i] = __ldg(qp + i * (DA / 2));
    const uint32_t a[4] = {z0.w, z0.z, z0.y, z0.x}, b[4] = {z1.w, z1.z, z1.y, z1.x};
#pragma unroll
    for (int i = 0; i < 4; i++) {
      op[(2 * i) * (OUTW / 2)]     = bmul(q[2 * i], __byte_perm(a[i], b[i], 0x7632));
      op[(2 * i + 1) * (OUTW / 2)] = bmul(q[2 * i + 1], __byte_perm(a[i], b[i], 0x5410));
    }
  }
}
__device__ __forceinline__ void clear_rows(const Params& p, int qt, int part) {
  const int lane = threadIdx.x & 31;
  if (lane < 28) {
    uint4* z = at<uint4>(p.out, ((qt * 128 + part * 16) * OUTW + DA) * 2 + lane * 16);
#pragma unroll
    for (int i = 0; i < 32; i++) z[(i >> 1) * (OUTW / 8) + (i & 1) * 28] = make_uint4(0, 0, 0, 0);
  }
  __syncwarp();
  if (lane == 0) flag_signal(flag_at(g_flags.zero_ready, qt));
}
__device__ __forceinline__ void side_work(const Params& p, int cta, int qt, unsigned epoch) {
#pragma unroll 1
  for (int rd = -SIDE_AHEAD; rd < 7; rd++) {
    if (rd >= 0) {
      if ((threadIdx.x & 31) == 0) flag_wait_slow(flag_at(g_flags.z_ready, rd), 3 * NCONV, epoch);
      __syncwarp();
    }
    if (rd + SIDE_AHEAD < 7) side_prepare(p, cta, rd + SIDE_AHEAD);
    if (rd >= 0 && !(EXP_SIDE & 1)) side_finish(p, cta, rd);
    if (rd == ZERO_RD) clear_rows(p, qt, (cta >> 3) & 7);
  }
}
}

__global__ void __cluster_dims__(2, 1, 1) __launch_bounds__(NTHREADS, 1)
concat_heads__ssm_conv_h3__compressed_kv_cla__prompt_kernel(const __grid_constant__ Params p) {
  extern __shared__ uint8_t smem_raw[];
  const uint32_t sb = (smem_u32(smem_raw) + 1023) & ~1023u;
  const int warp = __shfl_sync(0xffffffffu, threadIdx.x >> 5, 0);
  const int wg = warp >> 2;
  const int cta = blockIdx.x;
  const bool attn = cta < NMAIN;
  int h, u;
  {
    const int c = cta >> 1;
    if (c < 4) { h = 9; u = c; }
    else if (c < 36) { h = (c - 4) & 7; u = (c - 4) >> 3; }
    else { const int i = (c - 36) % 7; h = i == 0 ? 8 : 9 + i; u = (c - 36) / 7; }
  }
  const int j = 2 * u + (cta & 1);
  const int lane = threadIdx.x & 31;
  if (wg != 0) {
    if (attn) {
      if (threadIdx.x == NTHREADS - 32) {
        if (PF_MAPS & 2) prefetch_map(QFIRST ? &p.wq : p1_isv(j, 0) ? &p.wuv : &p.wuk);
        for (int i = 0; i < NSLOT; i++) mbar_init(bar_addr(sb, B_FULL + i), 1);
        asm volatile("fence.mbarrier_init.release.cluster;" ::: "memory");
      }
      __syncwarp();
      cluster_arrive();
      if (wg == 2) named_arrive(PP_BAR, 256);
      if (threadIdx.x == NTHREADS - 32) {
        for (int k = 0; k < EARLY_LD; k++) {
          const uint32_t full = bar_addr(sb, B_FULL + k);
          mbar_expect_tx(full, 49152);
          if (QFIRST) {
            tma_ld2(sb + QREG + k * 16384, &p.x, full, k * 64, q_tile(h, j, 1) * 128);
            load_tile4(sb + k * SLOT, &p.wq, full, k * 64, att_head(h, 1) * 4, j & 1, false);
          } else {
            tma_ld2(sb + QREG + k * 16384, &p.ckv, full, k * 64, p1_rows(h, j, 0) * 128);
            load_tile4(sb + k * SLOT, p1_isv(j, 0) ? &p.wuv : &p.wuk, full, k * 64, p1_head(h, j, 0) * 4, j & 1, false);
          }
        }
      }
      __syncwarp();
    }
    asm volatile("setmaxnreg.inc.sync.aligned.u32 232;");
    if (!attn) {
      if (p.out != nullptr) { named_sync(0, NTHREADS); ssm::mma_warpgroup(sb, wg - 1); }
      return;
    }
    if (p.out != nullptr) consumer_main(p, sb, h, j, wg - 1, warp & 3);
  } else {
    asm volatile("setmaxnreg.dec.sync.aligned.u32 40;");
    if (!attn) {
      ssm::init(p, sb, cta - NMAIN);
      named_sync(0, NTHREADS);
      if (lane == 0) {
        if (warp == 0) { ssm::producer(p, sb, cta - NMAIN, load_epoch()); cta_done(32); }
        else ssm::reducer(sb, cta - NMAIN, warp - 1);
        if (warp == 1) GT(14);
      }
      return;
    }
    if (lane == 0) {
      if (warp == 1) {
        for (int i = 0; i < NSLOT; i++) mbar_init(bar_addr(sb, B_EMPTY + i), (UNICAST & 8) ? 8 : 16);
        for (int i = 0; i < 2; i++) {
          mbar_init(bar_addr(sb, B_QFREE + i), 4); mbar_init(bar_addr(sb, B_QFULL + i), 1);
          mbar_init(bar_addr(sb, B_KVOK + i), 1); mbar_init(bar_addr(sb, B_CTXOK + i), 1);
        }
      } else if (warp == 2) {
        for (int i = 0; i < 8; i++) { mbar_init(bar_addr(sb, B_S2_FULL + i), 4); mbar_init(bar_addr(sb, B_S2_EMPTY + i), 1); }
      } else if (warp == 0) {
        mbar_init(bar_addr(sb, B_DONE), 2);
        for (int i = 0; i < 2; i++) {
          mbar_init(bar_addr(sb, B_ST_KV + i), 4); mbar_init(bar_addr(sb, B_ST_KV + 2 + i), 4);
          mbar_init(bar_addr(sb, B_ST_Q + i), 4); mbar_init(bar_addr(sb, B_ST_CTX + i), 4);
        }
      }
      asm volatile("fence.mbarrier_init.release.cluster;" ::: "memory");
    }
    __syncwarp();
    cluster_arrive();
    cluster_wait();
    if (warp == 0) {
      if (lane == 0) producer_main(p, sb, h, j);
    } else if (warp < 3) {
      if (lane == 0) {
        if ((PF_MAPS & 1) && warp == 1) { __nanosleep(2000); prefetch_map(&p.wuv); prefetch_map(&p.x); prefetch_map(&p.wq); prefetch_map(&p.o); prefetch_map(&p.wo); }
        helper_main(p, sb, h, j, warp - 1);
      }
    } else {
      ssm::side_work(p, h * 8 + j, q_tile(h, j, 1), load_epoch());
      if (lane == 0) { GT(57); mbar_wait(bar_addr(sb, B_DONE), 0); cta_done(1); }
    }
  }
}

typedef CUresult (*EncodeTiledFn)(CUtensorMap*, CUtensorMapDataType, cuuint32_t, void*, const cuuint64_t*, const cuuint64_t*,
                                  const cuuint32_t*, const cuuint32_t*, CUtensorMapInterleave, CUtensorMapSwizzle,
                                  CUtensorMapL2promotion, CUtensorMapFloatOOBfill);

void make_map(EncodeTiledFn enc, CUtensorMap* m, const void* ptr, int rank, const uint64_t* dims, const uint64_t* strides, const uint32_t* box) {
  cuuint64_t d[5], s[4]; cuuint32_t b[5], e[5] = {1, 1, 1, 1, 1};
  for (int i = 0; i < rank; i++) { d[i] = dims[i]; b[i] = box[i]; if (i) s[i - 1] = strides[i - 1]; }
  enc(m, CU_TENSOR_MAP_DATA_TYPE_BFLOAT16, rank, const_cast<void*>(ptr), d, s, b, e, CU_TENSOR_MAP_INTERLEAVE_NONE,
      CU_TENSOR_MAP_SWIZZLE_128B, CU_TENSOR_MAP_L2_PROMOTION_L2_256B, CU_TENSOR_MAP_FLOAT_OOB_FILL_NONE);
}
void map2(EncodeTiledFn enc, CUtensorMap* m, const void* ptr, uint64_t cols, uint64_t rows, uint32_t bc, uint32_t br) {
  const uint64_t dims[2] = {cols, rows}, st[1] = {cols * 2}; const uint32_t box[2] = {bc, br};
  make_map(enc, m, ptr, 2, dims, st, box);
}
void map3(EncodeTiledFn enc, CUtensorMap* m, const void* ptr, uint64_t rows, uint32_t nblk) {
  const uint64_t dims[3] = {64, rows, 64}, st[2] = {8192, 128}; const uint32_t box[3] = {64, 64, nblk};
  make_map(enc, m, ptr, 3, dims, st, box);
}

}

extern "C" void kernel_launch(void* const* d_in, const int* in_sizes, int n_in, void* d_out, int out_size) {
  (void)in_sizes; (void)n_in; (void)out_size;
  static EncodeTiledFn enc = nullptr;
  if (!enc) {
    void* fn = nullptr; cudaDriverEntryPointQueryResult qr;
    cudaGetDriverEntryPoint("cuTensorMapEncodeTiled", &fn, cudaEnableDefault, &qr);
    enc = (EncodeTiledFn)fn;
    cudaFuncSetAttribute(concat_heads__ssm_conv_h3__compressed_kv_cla__prompt_kernel, cudaFuncAttributeMaxDynamicSharedMemorySize, SMEM_BYTES);
  }
  Params p;
  p.a_q = (const bf16*)d_in[0]; p.a_k = (const bf16*)d_in[1]; p.a_v = (const bf16*)d_in[2];
  p.a_shift = (const bf16*)d_in[3]; p.a_ssmk = (const bf16*)d_in[4]; p.a_D = (const bf16*)d_in[5];
  p.out = (bf16*)d_out;
  map2(enc, &p.x, d_in[6], DM, SEQ, 64, 128);
  map2(enc, &p.ckv, d_in[7], DC, SEQ, 64, 128);
  map3(enc, &p.wq, d_in[8], DM, 2);
  map3(enc, &p.wuk, d_in[9], DC, 2);
  map3(enc, &p.wuv, d_in[10], DC, 2);
  {
    const uint64_t dims[5] = {DM, 2, 4, 4, NH * HD / 32}, st[4] = {DM * 2, 8 * DM * 2, 2 * DM * 2, 32 * DM * 2}; const uint32_t box[5] = {64, 2, 4, 4, 4};
    make_map(enc, &p.wo, d_in[11], 5, dims, st, box);
  }
  map2(enc, &p.o, d_out, OUTW, SEQ, 64, 64);
  concat_heads__ssm_conv_h3__compressed_kv_cla__prompt_kernel<<<NCTA, NTHREADS, SMEM_BYTES>>>(p);
}
```

```cpp
#include <cuda_runtime.h>
#include <cuda_bf16.h>
#include <cuda.h>
#include <stdint.h>

namespace {

typedef __nv_bfloat16 bf16;

constexpr int SEQ  = 2048;
constexpr int DA   = 448;
constexpr int NH   = 16;
constexpr int HD   = 256;
constexpr int DM   = 448;
constexpr int DC   = 1024;
constexpr int OUTW = DA + DM;
constexpr int NMAIN = 128;
constexpr int NCONV = 4;
constexpr int NCTA  = NMAIN + NCONV;
constexpr int LOG_DONE = 8;
constexpr int NTHREADS = 384;

__device__ __align__(1024) bf16 g_kv[2ull * SEQ * NH * HD];
__device__ __align__(1024) bf16 g_qc[(size_t)NMAIN * 128 * HD];
__device__ __align__(128) uint8_t g_xs[DA * SEQ * 2];
constexpr uint32_t HO_STRIDE = 4224;
__device__ __align__(128) uint8_t g_ho[DA * HO_STRIDE];
struct alignas(128) Flag { unsigned v; unsigned pad[31]; };
struct Flags {
  Flag kv_ready[NH * 2];
  Flag ctx_ready[NMAIN * 2];
  Flag x_ready[7];
  Flag z_ready[7];
  Flag zero_ready[16];
  alignas(128) unsigned long long done;
};
__device__ Flags g_flags;
#define TS(i)
#define TSC(i, cond)
#define TDUMP()
#define GT(i)
#define PT(i)
#define PCLK(var)
#define PACC(acc, t0)

struct alignas(64) Params {
  CUtensorMap ckv;
  CUtensorMap wuk;
  CUtensorMap wuv;
  CUtensorMap x;
  CUtensorMap wq;
  CUtensorMap o;
  CUtensorMap wo;
  const bf16 *a_q, *a_k, *a_v, *a_shift, *a_ssmk, *a_D;
  bf16* out;
};

constexpr uint32_t SLOT     = 32768;
constexpr int      NSLOT    = 5;
constexpr uint32_t QREG     = 163840;
constexpr uint32_t BARS     = 229376;
constexpr uint32_t SMEM_BYTES = BARS + 1024 + 1024;
enum : uint32_t {
  B_FULL = 0, B_EMPTY = 5, B_KVOK = 12, B_ST_Q = 14, B_ST_CTX = 16, B_DONE = 19, B_QFREE = 20, B_QFULL = 22,
  B_S2_FULL = 24, B_S2_EMPTY = 32, B_CTXOK = 40, B_PF = 42, B_ST_KV = 44
};
constexpr int P1_STEPS = 4 * 16 + 2 * 7, P1_XS = P1_STEPS - 2;

template <typename T> __device__ __forceinline__ T* at(const void* base, uint32_t off) {
  asm volatile("" : "+r"(off));
  return reinterpret_cast<T*>(const_cast<char*>(static_cast<const char*>(base)) + off);
}
__device__ __forceinline__ unsigned* flag_at(Flag* f, uint32_t i) { return at<unsigned>(f, i * (uint32_t)sizeof(Flag)); }
__device__ __forceinline__ uint32_t smem_u32(const void* p) { return (uint32_t)__cvta_generic_to_shared(p); }
__device__ __forceinline__ void mbar_init(uint32_t bar, uint32_t cnt) {
  asm volatile("mbarrier.init.shared::cta.b64 [%0], %1;" :: "r"(bar), "r"(cnt) : "memory");
}
__device__ __forceinline__ void mbar_expect_tx(uint32_t bar, uint32_t bytes) {
  asm volatile("mbarrier.arrive.expect_tx.shared::cta.b64 _, [%0], %1;" :: "r"(bar), "r"(bytes) : "memory");
}
__device__ __forceinline__ void mbar_arrive(uint32_t bar) {
  asm volatile("mbarrier.arrive.shared::cta.b64 _, [%0];" :: "r"(bar) : "memory");
}
__device__ __forceinline__ void mbar_arrive_n(uint32_t bar, uint32_t n) {
  asm volatile("mbarrier.arrive.shared::cta.b64 _, [%0], %1;" :: "r"(bar), "r"(n) : "memory");
}
__device__ __forceinline__ void mbar_arrive_remote(uint32_t bar, uint32_t cta) {
  asm volatile("{\n.reg .b32 ra;\nmapa.shared::cluster.u32 ra, %0, %1;\n"
               "mbarrier.arrive.shared::cluster.b64 _, [ra];\n}" :: "r"(bar), "r"(cta) : "memory");
}
__device__ __forceinline__ bool mbar_try(uint32_t bar, uint32_t parity) {
  uint32_t ok;
  asm volatile("{\n.reg .pred p;\nmbarrier.try_wait.parity.shared::cta.b64 p, [%1], %2;\nselp.u32 %0, 1, 0, p;\n}"
               : "=r"(ok) : "r"(bar), "r"(parity) : "memory");
  return ok;
}
__device__ __forceinline__ uint32_t mbar_test(uint32_t bar, uint32_t parity) {
  uint32_t ok;
  asm volatile("{\n.reg .pred p;\nmbarrier.test_wait.parity.shared::cta.b64 p, [%1], %2;\nselp.u32 %0, 1, 0, p;\n}"
               : "=r"(ok) : "r"(bar), "r"(parity) : "memory");
  return ok;
}
constexpr uint32_t SPIN_LIMIT = 1u << 24;
__device__ __forceinline__ void mbar_wait(uint32_t bar, uint32_t parity) {
  if (mbar_try(bar, parity)) return;
  uint32_t n = 0;
  while (!mbar_try(bar, parity)) { if (++n > SPIN_LIMIT) __trap(); }
}
__device__ __forceinline__ void mbar_wait_unless(uint32_t ready, uint32_t bar, uint32_t parity) {
  asm volatile("{\n.reg .pred p;\n.reg .b32 n;\nsetp.ne.u32 p, %0, 0;\nvote.sync.all.pred p, p, 0xffffffff;\n@p bra.uni WDONE;\nmov.u32 n, 0;\n"
               "WLOOP:\nmbarrier.try_wait.parity.shared::cta.b64 p, [%1], %2;\n@p bra.uni WDONE;\nadd.u32 n, n, 1;\nsetp.lt.u32 p, n, %3;\n@p bra.uni WLOOP;\ntrap;\nWDONE:\n}"
               :: "r"(ready), "r"(bar), "r"(parity), "n"(SPIN_LIMIT) : "memory");
}
__device__ __forceinline__ unsigned load_epoch() {
  unsigned long long d; asm volatile("ld.relaxed.gpu.global.u64 %0, [%1];" : "=l"(d) : "l"(&g_flags.done) : "memory");
  return (unsigned)(d >> LOG_DONE);
}
__device__ __forceinline__ void flag_wait(const unsigned* f, unsigned count, unsigned epoch) {
  const unsigned target = (epoch + 1) * count;
  uint32_t n = 0;
  while (true) {
    unsigned v;
    asm volatile("ld.acquire.gpu.global.u32 %0, [%1];" : "=r"(v) : "l"(f) : "memory");
    if ((int)(v - target) >= 0) break;
    if (++n > SPIN_LIMIT) __trap();
    __nanosleep(20);
  }
}
__device__ __forceinline__ void flag_wait_slow(const unsigned* f, unsigned count, unsigned epoch) {
  const unsigned target = (epoch + 1) * count;
  uint32_t n = 0;
  while (true) {
    unsigned v;
    asm volatile("ld.acquire.gpu.global.u32 %0, [%1];" : "=r"(v) : "l"(f) : "memory");
    if ((int)(v - target) >= 0) break;
    if (++n > SPIN_LIMIT / 16) __trap();
    __nanosleep(1000);
  }
}
__device__ __forceinline__ void cta_done(unsigned long long n) { asm volatile("red.relaxed.gpu.global.add.u64 [%0], %1;" :: "l"(&g_flags.done), "l"(n) : "memory"); }
__device__ __forceinline__ void flag_wait_fast(const unsigned* f, unsigned count, unsigned epoch) {
  const unsigned target = (epoch + 1) * count;
  uint32_t n = 0;
  while (true) {
    unsigned v;
    asm volatile("ld.acquire.gpu.global.u32 %0, [%1];" : "=r"(v) : "l"(f) : "memory");
    if ((int)(v - target) >= 0) break;
    if (++n > SPIN_LIMIT) __trap();
  }
}
__device__ __forceinline__ void fence_async_all() { asm volatile("fence.proxy.async.global;" ::: "memory"); }
__device__ __forceinline__ void flag_signal(unsigned* f) { asm volatile("red.release.gpu.global.add.u32 [%0], 1;" :: "l"(f) : "memory"); }
__device__ __forceinline__ void flag_signal_after_bulk(unsigned* f) {
  asm volatile("red.relaxed.gpu.global.add.u32 [%0], 1;" :: "l"(f) : "memory");
}
__device__ __forceinline__ void fence_async_smem() { asm volatile("fence.proxy.async.shared::cta;" ::: "memory"); }
#define HINTS 40
constexpr uint64_t POL_NORMAL = 0x1000000000000000ull, POL_FIRST = 0x12F0000000000000ull;
__device__ __forceinline__ constexpr uint64_t pol(bool first) { return first ? POL_FIRST : POL_NORMAL; }
__device__ __forceinline__ void tma_ld2(uint32_t dst, const CUtensorMap* m, uint32_t bar, int c0, int c1, uint64_t pl = POL_NORMAL) {
  asm volatile("cp.async.bulk.tensor.2d.shared::cluster.global.mbarrier::complete_tx::bytes.L2::cache_hint [%0], [%1, {%3, %4}], [%2], %5;"
               :: "r"(dst), "l"(m), "r"(bar), "r"(c0), "r"(c1), "l"(pl) : "memory");
}
__device__ __forceinline__ void tma_ld3(uint32_t dst, const CUtensorMap* m, uint32_t bar, int c0, int c1, int c2, uint64_t pl = POL_NORMAL) {
  asm volatile("cp.async.bulk.tensor.3d.shared::cluster.global.mbarrier::complete_tx::bytes.L2::cache_hint [%0], [%1, {%3, %4, %5}], [%2], %6;"
               :: "r"(dst), "l"(m), "r"(bar), "r"(c0), "r"(c1), "r"(c2), "l"(pl) : "memory");
}
__device__ __forceinline__ void tma_ld3_mc(uint32_t dst, const CUtensorMap* m, uint32_t bar, int c0, int c1, int c2, uint64_t pl = POL_NORMAL) {
  asm volatile("cp.async.bulk.tensor.3d.shared::cluster.global.mbarrier::complete_tx::bytes.multicast::cluster.L2::cache_hint [%0], [%1, {%3, %4, %5}], [%2], %6, %7;"
               :: "r"(dst), "l"(m), "r"(bar), "r"(c0), "r"(c1), "r"(c2), "h"((uint16_t)3), "l"(pl) : "memory");
}
__device__ __forceinline__ void bulk_ld(uint32_t dst, const void* src, uint32_t bytes, uint32_t bar) {
  asm volatile("cp.async.bulk.shared::cluster.global.mbarrier::complete_tx::bytes [%0], [%1], %2, [%3];"
               :: "r"(dst), "l"(src), "r"(bytes), "r"(bar) : "memory");
}
__device__ __forceinline__ void bulk_ld_p(uint32_t dst, const void* src, uint32_t bytes, uint32_t bar, uint64_t pl) {
  asm volatile("cp.async.bulk.shared::cluster.global.mbarrier::complete_tx::bytes.L2::cache_hint [%0], [%1], %2, [%3], %4;"
               :: "r"(dst), "l"(src), "r"(bytes), "r"(bar), "l"(pl) : "memory");
}
__device__ __forceinline__ void bulk_ld_mc(uint32_t dst, const void* src, uint32_t bytes, uint32_t bar, uint64_t pl) {
  asm volatile("cp.async.bulk.shared::cluster.global.mbarrier::complete_tx::bytes.multicast::cluster.L2::cache_hint [%0], [%1], %2, [%3], %4, %5;"
               :: "r"(dst), "l"(src), "r"(bytes), "r"(bar), "h"((uint16_t)3), "l"(pl) : "memory");
}
__device__ __forceinline__ void tma_st3(const CUtensorMap* m, uint32_t src, int c0, int c1, int c2) {
  asm volatile("cp.async.bulk.tensor.3d.global.shared::cta.bulk_group.L2::cache_hint [%0, {%2, %3, %4}], [%1], %5;"
               :: "l"(m), "r"(src), "r"(c0), "r"(c1), "r"(c2), "l"(pol(HINTS & 1024)) : "memory");
}
__device__ __forceinline__ void tma_ld2_mc(uint32_t dst, const CUtensorMap* m, uint32_t bar, int c0, int c1, uint64_t pl = POL_NORMAL) {
  asm volatile("cp.async.bulk.tensor.2d.shared::cluster.global.mbarrier::complete_tx::bytes.multicast::cluster.L2::cache_hint [%0], [%1, {%3, %4}], [%2], %5, %6;"
               :: "r"(dst), "l"(m), "r"(bar), "r"(c0), "r"(c1), "h"((uint16_t)3), "l"(pl) : "memory");
}
__device__ __forceinline__ void tma_ld5_mc(uint32_t dst, const CUtensorMap* m, uint32_t bar, int c0, int c4, uint64_t pl = POL_NORMAL) {
  asm volatile("cp.async.bulk.tensor.5d.shared::cluster.global.mbarrier::complete_tx::bytes.multicast::cluster.L2::cache_hint [%0], [%1, {%3, %7, %7, %7, %4}], [%2], %5, %6;"
               :: "r"(dst), "l"(m), "r"(bar), "r"(c0), "r"(c4), "h"((uint16_t)3), "l"(pl), "r"(0) : "memory");
}
__device__ __forceinline__ void tma_ld5(uint32_t dst, const CUtensorMap* m, uint32_t bar, int c0, int c4, uint64_t pl = POL_NORMAL) {
  asm volatile("cp.async.bulk.tensor.5d.shared::cluster.global.mbarrier::complete_tx::bytes.L2::cache_hint [%0], [%1, {%3, %6, %6, %6, %4}], [%2], %5;"
               :: "r"(dst), "l"(m), "r"(bar), "r"(c0), "r"(c4), "l"(pl), "r"(0) : "memory");
}
__device__ __forceinline__ void tma_st2(const CUtensorMap* m, uint32_t src, int c0, int c1) {
  asm volatile("cp.async.bulk.tensor.2d.global.shared::cta.bulk_group [%0, {%2, %3}], [%1];"
               :: "l"(m), "r"(src), "r"(c0), "r"(c1) : "memory");
}
__device__ __forceinline__ void tma_red2(const CUtensorMap* m, uint32_t src, int c0, int c1) {
  asm volatile("cp.reduce.async.bulk.tensor.2d.global.shared::cta.add.bulk_group [%0, {%2, %3}], [%1];"
               :: "l"(m), "r"(src), "r"(c0), "r"(c1) : "memory");
}
__device__ __forceinline__ void bulk_commit() { asm volatile("cp.async.bulk.commit_group;" ::: "memory"); }
__device__ __forceinline__ void bulk_wait_read() { asm volatile("cp.async.bulk.wait_group.read 0;" ::: "memory"); }
__device__ __forceinline__ void bulk_wait_all() { asm volatile("cp.async.bulk.wait_group 0;" ::: "memory"); }
__device__ __forceinline__ void prefetch_map(const CUtensorMap* m) { asm volatile("prefetch.tensormap [%0];" :: "l"(m) : "memory"); }
__device__ __forceinline__ void wg_fence() { asm volatile("wgmma.fence.sync.aligned;" ::: "memory"); }
__device__ __forceinline__ void wg_commit() { asm volatile("wgmma.commit_group.sync.aligned;" ::: "memory"); }
template <int N> __device__ __forceinline__ void wg_wait() { asm volatile("wgmma.wait_group.sync.aligned %0;" :: "n"(N) : "memory"); }
template <int N> __device__ __forceinline__ void reg_fence(float (&d)[N]) {
#pragma unroll
  for (int i = 0; i < N; i++) asm volatile("" : "+f"(d[i]) :: "memory");
}
template <int N> __device__ __forceinline__ void reg_fence(uint32_t (&d)[N]) {
#pragma unroll
  for (int i = 0; i < N; i++) asm volatile("" : "+r"(d[i]) :: "memory");
}
__device__ __forceinline__ uint32_t fresh_tid() { uint32_t t; asm volatile("mov.u32 %0, %%tid.x;" : "=r"(t)); return t; }
__device__ __forceinline__ uint32_t lane_base16() {
  const uint32_t t = fresh_tid(), lane = t & 31, wq = (t >> 5) & 3;
  return (16 * wq + (lane & 7) + 8 * ((lane >> 3) & 1)) * 128 + (((lane >> 4) ^ (lane & 7)) << 4);
}
__device__ __forceinline__ void cluster_arrive() { asm volatile("barrier.cluster.arrive.relaxed.aligned;" ::: "memory"); }
__device__ __forceinline__ void cluster_wait() { asm volatile("barrier.cluster.wait.acquire.aligned;" ::: "memory"); }
__device__ __forceinline__ void named_sync(int id, int n) { asm volatile("bar.sync %0, %1;" :: "r"(id), "r"(n) : "memory"); }
__device__ __forceinline__ void named_arrive(int id, int n) { asm volatile("bar.arrive %0, %1;" :: "r"(id), "r"(n) : "memory"); }
__device__ __forceinline__ uint32_t pack_bf16(float lo, float hi) {
  uint32_t r; asm("cvt.rn.bf16x2.f32 %0, %1, %2;" : "=r"(r) : "f"(hi), "f"(lo)); return r;
}
__device__ __forceinline__ float ex2(float x) { float y; asm("ex2.approx.ftz.f32 %0, %1;" : "=f"(y) : "f"(x)); return y; }
__device__ __forceinline__ void stsm4(uint32_t addr, uint32_t a, uint32_t b, uint32_t c, uint32_t d) {
  asm volatile("stmatrix.sync.aligned.m8n8.x4.shared.b16 [%0], {%1, %2, %3, %4};" :: "r"(addr), "r"(a), "r"(b), "r"(c), "r"(d) : "memory");
}
__device__ __forceinline__ uint64_t mk_desc(uint32_t addr, uint32_t lbo, uint32_t sbo) {
  return (uint64_t)(((addr & 0x3FFFF) >> 4) | ((lbo >> 4) << 16)) | ((uint64_t)((sbo >> 4) | (1u << 30)) << 32);
}
__device__ __forceinline__ uint64_t desc_k(uint32_t addr)  { return mk_desc(addr, 16, 1024); }
__device__ __forceinline__ uint64_t desc_mn(uint32_t addr) { return mk_desc(addr, 8192, 1024); }
__device__ __forceinline__ uint64_t desc_64(uint32_t addr) { return (uint64_t)(((addr & 0x3FFFF) >> 4) | ((4096u >> 4) << 16)) | ((uint64_t)((512u >> 4) | (2u << 30)) << 32); }
__device__ __forceinline__ uint64_t desc_add(uint64_t d, uint32_t bytes) { return d + (bytes >> 4); }

__device__ __forceinline__ void wgmma_ss_n256_tb(float (&d)[128], uint64_t da, uint64_t db, int sd) {
  asm volatile("{\n.reg .pred p;\nsetp.ne.b32 p, %130, 0;\n"
    "wgmma.mma_async.sync.aligned.m64n256k16.f32.bf16.bf16 "
    "{%0, %1, %2, %3, %4, %5, %6, %7, %8, %9, %10, %11, %12, %13, %14, %15, "
    "%16, %17, %18, %19, %20, %21, %22, %23, %24, %25, %26, %27, %28, %29, %30, %31, "
    "%32, %33, %34, %35, %36, %37, %38, %39, %40, %41, %42, %43, %44, %45, %46, %47, "
    "%48, %49, %50, %51, %52, %53, %54, %55, %56, %57, %58, %59, %60, %61, %62, %63, "
    "%64, %65, %66, %67, %68, %69, %70, %71, %72, %73, %74, %75, %76, %77, %78, %79, "
    "%80, %81, %82, %83, %84, %85, %86, %87, %88, %89, %90, %91, %92, %93, %94, %95, "
    "%96, %97, %98, %99, %100, %101, %102, %103, %104, %105, %106, %107, %108, %109, %110, %111, "
    "%112, %113, %114, %115, %116, %117, %118, %119, %120, %121, %122, %123, %124, %125, %126, %127}, "
    "%128, %129, p, 1, 1, 0, 1;\n}"
    : "+f"(d[0]), "+f"(d[1]), "+f"(d[2]), "+f"(d[3]), "+f"(d[4]), "+f"(d[5]), "+f"(d[6]), "+f"(d[7]),
      "+f"(d[8]), "+f"(d[9]), "+f"(d[10]), "+f"(d[11]), "+f"(d[12]), "+f"(d[13]), "+f"(d[14]), "+f"(d[15]),
      "+f"(d[16]), "+f"(d[17]), "+f"(d[18]), "+f"(d[19]), "+f"(d[20]), "+f"(d[21]), "+f"(d[22]), "+f"(d[23]),
      "+f"(d[24]), "+f"(d[25]), "+f"(d[26]), "+f"(d[27]), "+f"(d[28]), "+f"(d[29]), "+f"(d[30]), "+f"(d[31]),
      "+f"(d[32]), "+f"(d[33]), "+f"(d[34]), "+f"(d[35]), "+f"(d[36]), "+f"(d[37]), "+f"(d[38]), "+f"(d[39]),
      "+f"(d[40]), "+f"(d[41]), "+f"(d[42]), "+f"(d[43]), "+f"(d[44]), "+f"(d[45]), "+f"(d[46]), "+f"(d[47]),
      "+f"(d[48]), "+f"(d[49]), "+f"(d[50]), "+f"(d[51]), "+f"(d[52]), "+f"(d[53]), "+f"(d[54]), "+f"(d[55]),
      "+f"(d[56]), "+f"(d[57]), "+f"(d[58]), "+f"(d[59]), "+f"(d[60]), "+f"(d[61]), "+f"(d[62]), "+f"(d[63]),
      "+f"(d[64]), "+f"(d[65]), "+f"(d[66]), "+f"(d[67]), "+f"(d[68]), "+f"(d[69]), "+f"(d[70]), "+f"(d[71]),
      "+f"(d[72]), "+f"(d[73]), "+f"(d[74]), "+f"(d[75]), "+f"(d[76]), "+f"(d[77]), "+f"(d[78]), "+f"(d[79]),
      "+f"(d[80]), "+f"(d[81]), "+f"(d[82]), "+f"(d[83]), "+f"(d[84]), "+f"(d[85]), "+f"(d[86]), "+f"(d[87]),
      "+f"(d[88]), "+f"(d[89]), "+f"(d[90]), "+f"(d[91]), "+f"(d[92]), "+f"(d[93]), "+f"(d[94]), "+f"(d[95]),
      "+f"(d[96]), "+f"(d[97]), "+f"(d[98]), "+f"(d[99]), "+f"(d[100]), "+f"(d[101]), "+f"(d[102]), "+f"(d[103]),
      "+f"(d[104]), "+f"(d[105]), "+f"(d[106]), "+f"(d[107]), "+f"(d[108]), "+f"(d[109]), "+f"(d[110]), "+f"(d[111]),
      "+f"(d[112]), "+f"(d[113]), "+f"(d[114]), "+f"(d[115]), "+f"(d[116]), "+f"(d[117]), "+f"(d[118]), "+f"(d[119]),
      "+f"(d[120]), "+f"(d[121]), "+f"(d[122]), "+f"(d[123]), "+f"(d[124]), "+f"(d[125]), "+f"(d[126]), "+f"(d[127])
    : "l"(da), "l"(db), "r"(sd));
}
__device__ __forceinline__ void wgmma_ss_n64(float (&d)[32], uint64_t da, uint64_t db, int sd) {
  asm volatile("{\n.reg .pred p;\nsetp.ne.b32 p, %34, 0;\n"
    "wgmma.mma_async.sync.aligned.m64n64k16.f32.bf16.bf16 "
    "{%0, %1, %2, %3, %4, %5, %6, %7, %8, %9, %10, %11, %12, %13, %14, %15, "
    "%16, %17, %18, %19, %20, %21, %22, %23, %24, %25, %26, %27, %28, %29, %30, %31}, "
    "%32, %33, p, 1, 1, 0, 0;\n}"
    : "+f"(d[0]), "+f"(d[1]), "+f"(d[2]), "+f"(d[3]), "+f"(d[4]), "+f"(d[5]), "+f"(d[6]), "+f"(d[7]),
      "+f"(d[8]), "+f"(d[9]), "+f"(d[10]), "+f"(d[11]), "+f"(d[12]), "+f"(d[13]), "+f"(d[14]), "+f"(d[15]),
      "+f"(d[16]), "+f"(d[17]), "+f"(d[18]), "+f"(d[19]), "+f"(d[20]), "+f"(d[21]), "+f"(d[22]), "+f"(d[23]),
      "+f"(d[24]), "+f"(d[25]), "+f"(d[26]), "+f"(d[27]), "+f"(d[28]), "+f"(d[29]), "+f"(d[30]), "+f"(d[31])
    : "l"(da), "l"(db), "r"(sd));
}
__device__ __forceinline__ void wgmma_rs_n256_tb(float (&d)[128], uint32_t a0, uint32_t a1, uint32_t a2, uint32_t a3, uint64_t db, int sd) {
  asm volatile("{\n.reg .pred p;\nsetp.ne.b32 p, %133, 0;\n"
    "wgmma.mma_async.sync.aligned.m64n256k16.f32.bf16.bf16 "
    "{%0, %1, %2, %3, %4, %5, %6, %7, %8, %9, %10, %11, %12, %13, %14, %15, "
    "%16, %17, %18, %19, %20, %21, %22, %23, %24, %25, %26, %27, %28, %29, %30, %31, "
    "%32, %33, %34, %35, %36, %37, %38, %39, %40, %41, %42, %43, %44, %45, %46, %47, "
    "%48, %49, %50, %51, %52, %53, %54, %55, %56, %57, %58, %59, %60, %61, %62, %63, "
    "%64, %65, %66, %67, %68, %69, %70, %71, %72, %73, %74, %75, %76, %77, %78, %79, "
    "%80, %81, %82, %83, %84, %85, %86, %87, %88, %89, %90, %91, %92, %93, %94, %95, "
    "%96, %97, %98, %99, %100, %101, %102, %103, %104, %105, %106, %107, %108, %109, %110, %111, "
    "%112, %113, %114, %115, %116, %117, %118, %119, %120, %121, %122, %123, %124, %125, %126, %127}, "
    "{%128, %129, %130, %131}, %132, p, 1, 1, 1;\n}"
    : "+f"(d[0]), "+f"(d[1]), "+f"(d[2]), "+f"(d[3]), "+f"(d[4]), "+f"(d[5]), "+f"(d[6]), "+f"(d[7]),
      "+f"(d[8]), "+f"(d[9]), "+f"(d[10]), "+f"(d[11]), "+f"(d[12]), "+f"(d[13]), "+f"(d[14]), "+f"(d[15]),
      "+f"(d[16]), "+f"(d[17]), "+f"(d[18]), "+f"(d[19]), "+f"(d[20]), "+f"(d[21]), "+f"(d[22]), "+f"(d[23]),
      "+f"(d[24]), "+f"(d[25]), "+f"(d[26]), "+f"(d[27]), "+f"(d[28]), "+f"(d[29]), "+f"(d[30]), "+f"(d[31]),
      "+f"(d[32]), "+f"(d[33]), "+f"(d[34]), "+f"(d[35]), "+f"(d[36]), "+f"(d[37]), "+f"(d[38]), "+f"(d[39]),
      "+f"(d[40]), "+f"(d[41]), "+f"(d[42]), "+f"(d[43]), "+f"(d[44]), "+f"(d[45]), "+f"(d[46]), "+f"(d[47]),
      "+f"(d[48]), "+f"(d[49]), "+f"(d[50]), "+f"(d[51]), "+f"(d[52]), "+f"(d[53]), "+f"(d[54]), "+f"(d[55]),
      "+f"(d[56]), "+f"(d[57]), "+f"(d[58]), "+f"(d[59]), "+f"(d[60]), "+f"(d[61]), "+f"(d[62]), "+f"(d[63]),
      "+f"(d[64]), "+f"(d[65]), "+f"(d[66]), "+f"(d[67]), "+f"(d[68]), "+f"(d[69]), "+f"(d[70]), "+f"(d[71]),
      "+f"(d[72]), "+f"(d[73]), "+f"(d[74]), "+f"(d[75]), "+f"(d[76]), "+f"(d[77]), "+f"(d[78]), "+f"(d[79]),
      "+f"(d[80]), "+f"(d[81]), "+f"(d[82]), "+f"(d[83]), "+f"(d[84]), "+f"(d[85]), "+f"(d[86]), "+f"(d[87]),
      "+f"(d[88]), "+f"(d[89]), "+f"(d[90]), "+f"(d[91]), "+f"(d[92]), "+f"(d[93]), "+f"(d[94]), "+f"(d[95]),
      "+f"(d[96]), "+f"(d[97]), "+f"(d[98]), "+f"(d[99]), "+f"(d[100]), "+f"(d[101]), "+f"(d[102]), "+f"(d[103]),
      "+f"(d[104]), "+f"(d[105]), "+f"(d[106]), "+f"(d[107]), "+f"(d[108]), "+f"(d[109]), "+f"(d[110]), "+f"(d[111]),
      "+f"(d[112]), "+f"(d[113]), "+f"(d[114]), "+f"(d[115]), "+f"(d[116]), "+f"(d[117]), "+f"(d[118]), "+f"(d[119]),
      "+f"(d[120]), "+f"(d[121]), "+f"(d[122]), "+f"(d[123]), "+f"(d[124]), "+f"(d[125]), "+f"(d[126]), "+f"(d[127])
    : "r"(a0), "r"(a1), "r"(a2), "r"(a3), "l"(db), "r"(sd));
}
__device__ __forceinline__ void wgmma_rs_n64_tb(float (&d)[32], uint32_t a0, uint32_t a1, uint32_t a2, uint32_t a3, uint64_t db, int sd) {
  asm volatile("{\n.reg .pred p;\nsetp.ne.b32 p, %37, 0;\n"
    "wgmma.mma_async.sync.aligned.m64n64k16.f32.bf16.bf16 "
    "{%0, %1, %2, %3, %4, %5, %6, %7, %8, %9, %10, %11, %12, %13, %14, %15, "
    "%16, %17, %18, %19, %20, %21, %22, %23, %24, %25, %26, %27, %28, %29, %30, %31}, "
    "{%32, %33, %34, %35}, %36, p, 1, 1, 1;\n}"
    : "+f"(d[0]), "+f"(d[1]), "+f"(d[2]), "+f"(d[3]), "+f"(d[4]), "+f"(d[5]), "+f"(d[6]), "+f"(d[7]),
      "+f"(d[8]), "+f"(d[9]), "+f"(d[10]), "+f"(d[11]), "+f"(d[12]), "+f"(d[13]), "+f"(d[14]), "+f"(d[15]),
      "+f"(d[16]), "+f"(d[17]), "+f"(d[18]), "+f"(d[19]), "+f"(d[20]), "+f"(d[21]), "+f"(d[22]), "+f"(d[23]),
      "+f"(d[24]), "+f"(d[25]), "+f"(d[26]), "+f"(d[27]), "+f"(d[28]), "+f"(d[29]), "+f"(d[30]), "+f"(d[31])
    : "r"(a0), "r"(a1), "r"(a2), "r"(a3), "l"(db), "r"(sd));
}
__device__ __forceinline__ void wgmma_rs_n32(float (&d)[16], uint32_t a0, uint32_t a1, uint32_t a2, uint32_t a3, uint64_t db, int sd) {
  asm volatile("{\n.reg .pred p;\nsetp.ne.b32 p, %21, 0;\n"
    "wgmma.mma_async.sync.aligned.m64n32k16.f32.bf16.bf16 "
    "{%0, %1, %2, %3, %4, %5, %6, %7, %8, %9, %10, %11, %12, %13, %14, %15}, "
    "{%16, %17, %18, %19}, %20, p, 1, 1, 0;\n}"
    : "+f"(d[0]), "+f"(d[1]), "+f"(d[2]), "+f"(d[3]), "+f"(d[4]), "+f"(d[5]), "+f"(d[6]), "+f"(d[7]),
      "+f"(d[8]), "+f"(d[9]), "+f"(d[10]), "+f"(d[11]), "+f"(d[12]), "+f"(d[13]), "+f"(d[14]), "+f"(d[15])
    : "r"(a0), "r"(a1), "r"(a2), "r"(a3), "l"(db), "r"(sd));
}
__device__ __forceinline__ void wgmma_rs_n64(float (&d)[32], uint32_t a0, uint32_t a1, uint32_t a2, uint32_t a3, uint64_t db, int sd) {
  asm volatile("{\n.reg .pred p;\nsetp.ne.b32 p, %37, 0;\n"
    "wgmma.mma_async.sync.aligned.m64n64k16.f32.bf16.bf16 "
    "{%0, %1, %2, %3, %4, %5, %6, %7, %8, %9, %10, %11, %12, %13, %14, %15, "
    "%16, %17, %18, %19, %20, %21, %22, %23, %24, %25, %26, %27, %28, %29, %30, %31}, "
    "{%32, %33, %34, %35}, %36, p, 1, 1, 0;\n}"
    : "+f"(d[0]), "+f"(d[1]), "+f"(d[2]), "+f"(d[3]), "+f"(d[4]), "+f"(d[5]), "+f"(d[6]), "+f"(d[7]),
      "+f"(d[8]), "+f"(d[9]), "+f"(d[10]), "+f"(d[11]), "+f"(d[12]), "+f"(d[13]), "+f"(d[14]), "+f"(d[15]),
      "+f"(d[16]), "+f"(d[17]), "+f"(d[18]), "+f"(d[19]), "+f"(d[20]), "+f"(d[21]), "+f"(d[22]), "+f"(d[23]),
      "+f"(d[24]), "+f"(d[25]), "+f"(d[26]), "+f"(d[27]), "+f"(d[28]), "+f"(d[29]), "+f"(d[30]), "+f"(d[31])
    : "r"(a0), "r"(a1), "r"(a2), "r"(a3), "l"(db), "r"(sd));
}

__device__ __forceinline__ uint4 lds16(uint32_t a) {
  uint4 v; asm volatile("ld.shared.v4.u32 {%0, %1, %2, %3}, [%4];" : "=r"(v.x), "=r"(v.y), "=r"(v.z), "=r"(v.w) : "r"(a) : "memory"); return v;
}
__device__ __forceinline__ void sts16(uint32_t a, uint32_t x, uint32_t y, uint32_t z, uint32_t w) {
  asm volatile("st.shared.v4.u32 [%0], {%1, %2, %3, %4};" :: "r"(a), "r"(x), "r"(y), "r"(z), "r"(w) : "memory");
}
__device__ __forceinline__ uint32_t lds4(uint32_t a) { uint32_t v; asm volatile("ld.shared.u32 %0, [%1];" : "=r"(v) : "r"(a) : "memory"); return v; }
__device__ __forceinline__ uint32_t lds4v(uint32_t a) { uint32_t v; asm volatile("ld.volatile.shared.u32 %0, [%1];" : "=r"(v) : "r"(a) : "memory"); return v; }
__device__ __forceinline__ uint32_t bmul(uint32_t a, uint32_t b) { uint32_t r; asm("mul.rn.bf16x2 %0, %1, %2;" : "=r"(r) : "r"(a), "r"(b)); return r; }
__device__ __forceinline__ uint32_t badd(uint32_t a, uint32_t b) { uint32_t r; asm("add.rn.bf16x2 %0, %1, %2;" : "=r"(r) : "r"(a), "r"(b)); return r; }

__device__ __forceinline__ void ldsm4(uint32_t (&r)[4], uint32_t a) {
  asm volatile("ldmatrix.sync.aligned.m8n8.x4.shared.b16 {%0, %1, %2, %3}, [%4];" : "=r"(r[0]), "=r"(r[1]), "=r"(r[2]), "=r"(r[3]) : "r"(a) : "memory");
}
__device__ __forceinline__ uint32_t transpose8(uint32_t a) { uint32_t d; asm volatile("movmatrix.sync.aligned.m8n8.trans.b16 %0, %1;" : "=r"(d) : "r"(a)); return d; }

__device__ __forceinline__ void mma16816(float (&d)[4], const uint32_t (&a)[4], uint32_t b0, uint32_t b1) {
  asm volatile("mma.sync.aligned.m16n8k16.row.col.f32.bf16.bf16.f32 {%0, %1, %2, %3}, {%4, %5, %6, %7}, {%8, %9}, {%0, %1, %2, %3};"
               : "+f"(d[0]), "+f"(d[1]), "+f"(d[2]), "+f"(d[3]) : "r"(a[0]), "r"(a[1]), "r"(a[2]), "r"(a[3]), "r"(b0), "r"(b1));
}

#define EXP_SIDE 0
#define SIDE_AHEAD 3
#define ZERO_RD 4
#define CTX_SPLIT 8
#define CONV_EARLY 8
#define CONV_FENCE 12
#define CTX_LD 8
#define PEEK_JJ 7
#define PF_CTX 0
#define KV_ORDER 3
#define QFIRST 0
#define UNICAST 2
#define PF_MAPS 3
#define SINGLE0 0
#define LAST_DIRECT 1
#define HAND_NOW 1
#define GRID1 0
#define GRID2 0
#define GRID3 0
#define GRID_W 64
#define XMAP 2
#define XB 1
#define CONV_ARRIVE 13
#define ARRIVE_KK 12
#define SIDE_DELAY_NS 4000
#define KVH(h) (h)
#define HEAD_MAP 2
#define EARLY_LD 4
#define EARLY_GAP 200
constexpr int RED_BAR = 6;
constexpr int CV_BAR = 5;
constexpr int PP_BAR = 3;
template <int V> struct Int { static constexpr int value = V; };
struct Ring {
  uint32_t slot, phase;
  __device__ __forceinline__ void next() { if (++slot == NSLOT) { slot = 0; phase ^= 1; } }
};
__device__ __forceinline__ uint32_t bar_addr(uint32_t sb, uint32_t i) { return sb + BARS + 8 * i; }

__device__ __forceinline__ int q_tile(int h, int j, int which) { return ((h < 8) == (which == 0)) ? 15 - j : j; }

constexpr int T_QB = QFIRST ? 0 : 4, IT_KV = QFIRST ? 7 : 0, IT_QB = QFIRST ? 0 : 64;
constexpr int KV_ISV  = KV_ORDER == 0 ? 0xC : KV_ORDER == 1 ? 0xA : KV_ORDER == 2 ? 0x6 : KV_ORDER == 3 ? 0xA : 0xC;
constexpr int KV_PART = KV_ORDER == 0 ? 0xA : KV_ORDER == 1 ? 0xC : KV_ORDER == 2 ? 0xC : KV_ORDER == 3 ? 0x3 : KV_ORDER == 4 ? 0x5 : 0x9;
constexpr int LAST_PART = KV_PART >> 3;
constexpr int T_FIRST = (((KV_PART >> 2) & 1) != LAST_PART ? 3 : 2) + QFIRST;
constexpr int T_LAST = 4 + QFIRST;
__device__ __forceinline__ int p1_isv(int j, int n) { return XMAP == 1 ? j & 1 : XMAP == 3 ? (j ^ n) & 1 : (KV_ISV >> n) & 1; }
__device__ __forceinline__ int att_head(int h, int which) { return (h & 7) + 8 * which; }
__device__ __forceinline__ int p1_pos(int h) { return HEAD_MAP == 2 ? (h < 9 ? h & 7 : h == 9 ? 7 : h - 9) : h & 7; }
__device__ __forceinline__ int p1_group(int h, int j) {
  return XMAP == 4 ? (j & 1) + 2 * (p1_pos(h) & 1) + 4 * (h >> 3) : XMAP == 2 ? (h & 7 & ~XB) | ((j & 1) * XB) : h & 7;
}
__device__ __forceinline__ int p1_head(int h, int j, int n) { return p1_group(h, j) + 8 * ((KV_PART >> n) & 1); }
__device__ __forceinline__ int p1_rows(int h, int j, int n) { return XMAP == 4 ? 4 * (p1_pos(h) >> 1) + (j >> 1) : XMAP == 0 ? q_tile(h, j, 0) : (q_tile(h, j, 0) & ~1) | (XMAP == 2 ? (h & XB) != 0 : n & 1); }
#define KV_FLAG(h) ((h) & 7)
#define KV_COUNT 32
#define F_PART1 (2 * own - 1)

__device__ __forceinline__ void producer_main(const Params& p, uint32_t sb, int h, int j) {
  const int rank = j & 1;
  Ring r{EARLY_LD, 0};
  auto wait_slot = [&](uint32_t period) {
    mbar_wait(bar_addr(sb, B_EMPTY + r.slot), r.phase ^ 1);
    if (period) { while (((uint32_t)clock() & (period - 1)) >= GRID_W) {} }
  };
  auto load_a = [&](int it, uint32_t dst, uint32_t full) {
    const unsigned u = it - IT_KV;
    if (u < 64) tma_ld2(dst, &p.ckv, full, (u & 15) * 64, p1_rows(h, j, u >> 4) * 128, pol((HINTS & 2) && u >= 48));
    else tma_ld2(dst, &p.x, full, (it < 71 ? it - IT_QB : it - 71) * 64, q_tile(h, j, it < 71) * 128, pol((HINTS & 64) && it >= 71));
  };
  uint32_t prev = 0;
#pragma unroll 1
  for (int it = EARLY_LD; it < P1_STEPS; it++) {
    wait_slot(it >= NSLOT ? GRID1 : 0);
    if (it > EARLY_LD && it <= P1_XS) load_a(it - 1, sb + QREG + ((it - 1) & 3) * 16384, prev);
    const uint32_t full = bar_addr(sb, B_FULL + r.slot), dst = sb + r.slot * SLOT;
    mbar_expect_tx(full, it < P1_XS ? 49152 : 32768);
    const unsigned u = it - IT_KV;
    if (u < 64) tma_ld3(dst, p1_isv(j, u >> 4) ? &p.wuv : &p.wuk, full, 0, (u & 15) * 64, p1_head(h, j, u >> 4) * 4);
    else tma_ld3(dst, &p.wq, full, 0, (it < 71 ? it - IT_QB : it - 71) * 64, att_head(h, it < 71) * 4);
    prev = full;
    r.next();
    if (it == P1_XS) {
      wait_slot(0);
      const uint32_t f2 = bar_addr(sb, B_FULL + r.slot);
      mbar_expect_tx(f2, 32768);
      load_a(P1_XS, sb + r.slot * SLOT, f2);
      load_a(P1_XS + 1, sb + r.slot * SLOT + 16384, f2);
      r.next();
    }
  }
  const int qa = q_tile(h, j, 0), na = 2 * qa + 2, own = 2 * (qa & ~1) + 2;
#pragma unroll 1
  for (int f = 0; f < 68; f++) {
    const bool isK = (f == 0) || ((f & 1) && f < 67);
    const int i = isK ? (f + 1) >> 1 : (f - 1) >> 1, which = i >= na;
    if (f == 0 || f == F_PART1) mbar_wait(bar_addr(sb, B_KVOK + (f & 1)), 0);
    wait_slot(GRID2);
    const uint32_t full = bar_addr(sb, B_FULL + r.slot);
    mbar_expect_tx(full, 32768);
    const uint32_t src = (uint32_t)(((isK ? 0 : NH) + KVH(att_head(h, which))) * 32 + (which ? 33 - i : i)) * 32768;
    const uint64_t pl = pol(which ? (HINTS & 32) : (HINTS & 8));
    if (!(UNICAST & 1) && (i & ~1) != own) bulk_ld_mc(sb + r.slot * SLOT + rank * 16384, at<uint8_t>(g_kv, src + rank * 16384), 16384, full, pl);
    else bulk_ld_p(sb + r.slot * SLOT, at<uint8_t>(g_kv, src), 32768, full, pl);
    r.next();
  }
#pragma unroll 1
  for (int f = 0; f < 14; f++) {
    const int ch = f < 4 ? f & 1 : f >> 1, par = f < 4 ? f >> 1 : f & 1;
    wait_slot(GRID3);
    const uint32_t full = bar_addr(sb, B_FULL + r.slot);
    mbar_expect_tx(full, 32768);
    if (UNICAST & 4) {
      tma_ld5(sb + r.slot * SLOT, &p.wo, full, ch * 64, (par ? att_head(h ^ 8, 0) : att_head(h, 1)) * 8, pol(HINTS & 16));
      tma_ld5(sb + r.slot * SLOT + 16384, &p.wo, full, ch * 64, (par ? att_head(h ^ 8, 0) : att_head(h, 1)) * 8 + 4, pol(HINTS & 16));
    } else {
      tma_ld5_mc(sb + r.slot * SLOT + rank * 16384, &p.wo, full, ch * 64, (par ? att_head(h ^ 8, 0) : att_head(h, 1)) * 8 + rank * 4, pol(HINTS & 16));
    }
    r.next();
  }
}

__device__ __forceinline__ void helper_main(const Params& p, uint32_t sb, int h, int j, int w) {
  const unsigned epoch = load_epoch();
  const int cta = h * 8 + j, qb = q_tile(h, j, 1);
  const uint32_t qreg = sb + QREG + w * 32768, qfull = bar_addr(sb, B_QFULL + w);
  auto acquire = [&]() {
    flag_wait(flag_at(g_flags.kv_ready, KV_FLAG(h) * 2 + w), KV_COUNT, epoch);
    fence_async_all();
    mbar_arrive(bar_addr(sb, B_KVOK + w));
  };
  if (QFIRST) mbar_wait(bar_addr(sb, B_ST_Q + w), 0);
  mbar_wait(bar_addr(sb, B_ST_KV + w), 0);
  flag_signal(flag_at(g_flags.kv_ready, p1_group(h, j) * 2 + (LAST_PART ^ 1)));
  if (w != LAST_PART) acquire();
  mbar_wait(bar_addr(sb, B_ST_KV + 2 + w), 0);
  flag_signal(flag_at(g_flags.kv_ready, p1_group(h, j) * 2 + LAST_PART));
  const bool late = false;
  if (w == LAST_PART && !late) acquire();
  if (!QFIRST) { mbar_wait(bar_addr(sb, B_ST_Q + w), 0); asm volatile("fence.release.gpu;" ::: "memory"); }
  fence_async_all();
  mbar_wait(bar_addr(sb, B_QFREE + w), 0);
  mbar_expect_tx(qfull, 32768);
  bulk_ld(qreg, at<uint8_t>(g_qc, (cta * 2 + w) * 32768), 32768, qfull);
  if (w == LAST_PART && late) acquire();
  auto publish = [&]() { mbar_wait(bar_addr(sb, B_ST_CTX + w), 0); flag_signal(flag_at(g_flags.ctx_ready, cta * 2 + w)); };
  if (qb >= 8) publish();
  flag_wait(flag_at(g_flags.ctx_ready, (cta ^ 64) * 2 + (w ^ 1)), 1, epoch);
  mbar_arrive(bar_addr(sb, B_CTXOK + w));
  mbar_arrive(bar_addr(sb, B_DONE));
  if (qb < 8) publish();
  flag_wait(flag_at(g_flags.zero_ready, qb), 8, epoch);
  fence_async_all();
#pragma unroll 1
  for (int ch = 0; ch < (LAST_DIRECT ? 6 : 7); ch++) {
    mbar_wait(bar_addr(sb, B_S2_FULL + w * 4 + (ch & 3)), ch >> 2);
    tma_red2(&p.o, qreg + (ch & 3) * 8192, DA + ch * 64, qb * 128 + (w ^ 1) * 64);
    bulk_commit();
    if (ch < 3) { bulk_wait_read(); mbar_arrive(bar_addr(sb, B_S2_EMPTY + w * 4 + ch)); }
  }
  bulk_wait_read();
  GT(48 + w);
}

__device__ __forceinline__ void store_block(uint32_t base, uint32_t lanebase, const uint32_t (&pk)[16]) {
#pragma unroll
  for (int J = 0; J < 8; J += 2) stsm4(base + (lanebase ^ (J << 4)), pk[2 * J], pk[2 * J + 1], pk[2 * J + 2], pk[2 * J + 3]);
}
__device__ __forceinline__ void pack_chunks(uint32_t (&pk)[64], const float (&acc)[128]) {
#pragma unroll
  for (int i = 0; i < 64; i++) { const int e = 16 * (i >> 3) + 4 * (i & 3) + 2 * ((i >> 2) & 1); pk[i] = pack_bf16(acc[e], acc[e + 1]); }
}
__device__ __forceinline__ uint32_t chunk_off() { const uint32_t t = fresh_tid(); return (t & 96) * 32 + (t & 28) * 16 + (((t ^ (t >> 3)) & 3) << 4); }
__device__ __forceinline__ void warp_arrive(uint32_t bar, int lane) { __syncwarp(); if (lane == 0) mbar_arrive(bar); }

__device__ __forceinline__ void consumer_main(const Params& p, uint32_t sb, int h, int j, int w, int wq) {
  const int lane = threadIdx.x & 31;
  const int rank = j & 1;

  auto turn_begin = [&]() { named_sync(PP_BAR + w, 256); };
  auto turn_end = [&]() { named_arrive(PP_BAR + (w ^ 1), 256); };
  Ring r{0, 0};
  auto take = [&](uint32_t ready = 0) { const uint32_t sl = r.slot; mbar_wait_unless(ready, bar_addr(sb, B_FULL + sl), r.phase); r.next(); return sl; };
  uint32_t rdy0 = 0, rdy1 = 0;
  auto peek2 = [&]() { Ring q = r; rdy0 = mbar_test(bar_addr(sb, B_FULL + q.slot), q.phase); q.next(); rdy1 = mbar_test(bar_addr(sb, B_FULL + q.slot), q.phase); };
  auto give = [&](uint32_t sl) {
    if (UNICAST & 8) { if (lane == 0) mbar_arrive(bar_addr(sb, B_EMPTY + sl)); }
    else if (lane < 2) mbar_arrive_remote(bar_addr(sb, B_EMPTY + sl), rank ^ lane);
  };
  float acc[128];
#pragma unroll
  for (int i = 0; i < 128; i++) acc[i] = 0.f;
  uint32_t pk[64];
#pragma unroll
  for (int i = 0; i < 64; i++) pk[i] = 0;
  reg_fence(acc);
  reg_fence(pk);
  cluster_wait();
  TS(0);
  const uint32_t qreg = sb + QREG + w * 32768;
  {
    uint32_t xs = 0;
    uint4* row = nullptr;
    int it = 0;
#pragma unroll 1
    for (int t = 0; t < 6; t++) {
      const bool isq = t == T_QB || t == 5;
      const uint32_t abase = sb + QREG + (w ^ (t == T_QB)) * 8192;
#pragma unroll 1
      for (int u = 0, end = it + (isq ? 7 : 16); it < end; u++) {
        const bool two = !(isq && u == 1) && it >= SINGLE0, last = it == P1_XS;
        const uint32_t w0 = take(rdy0);
        TSC(1, it == 0);
        if (last) { xs = take(rdy1); rdy1 = 0; }
        const uint32_t xb = sb + xs * SLOT + w * 8192;
        const uint64_t da = desc_k(last ? xb : abase + (it & 3) * 16384), db = desc_mn(sb + w0 * SLOT);
        turn_begin();
        wg_fence();
#pragma unroll
        for (int kk = 0; kk < 4; kk++) wgmma_ss_n256_tb(acc, desc_add(da, kk * 32), desc_add(db, kk * 2048), (u | kk) != 0);
        wg_commit();
        uint32_t w1 = w0;
        if (two) {
          w1 = take(rdy1);
          const uint64_t da1 = desc_k(last ? xb + 16384 : abase + ((it + 1) & 3) * 16384), db1 = desc_mn(sb + w1 * SLOT);
          wg_fence();
#pragma unroll
          for (int kk = 0; kk < 4; kk++) wgmma_ss_n256_tb(acc, desc_add(da1, kk * 32), desc_add(db1, kk * 2048), 1);
          wg_commit();
          turn_end();
          wg_wait<1>();
          give(w0);
        } else {
          turn_end();
        }
        if (t > 0) {
          uint32_t m = isq ? 0xC0380403u >> (8 * u) : 1u << u;
          asm volatile("" : "+r"(m));
#pragma unroll
          for (int i = 0; i < 16; i++)
            if (m & (1u << (i >> 1))) row[(i >> 1) * 256 + (i & 1) * 32] = make_uint4(pk[4 * i], pk[4 * i + 1], pk[4 * i + 2], pk[4 * i + 3]);
        }
        peek2();
        wg_wait<0>();
        give(w1);
        it += 1 + two;
      }
      reg_fence(acc);
      if (t == T_QB + 1 || t == T_FIRST || t == T_LAST)
        warp_arrive(bar_addr(sb, (t == T_QB + 1 ? B_ST_Q : t == T_LAST ? B_ST_KV + 2 : B_ST_KV) + w), lane);
      pack_chunks(pk, acc);
      const int n = t - QFIRST;
      row = at<uint4>(t != T_QB ? (const void*)g_kv : (const void*)g_qc, chunk_off() +
                      (t != T_QB ? (uint32_t)((p1_isv(j, n) * NH + KVH(p1_head(h, j, n))) * 32 + p1_rows(h, j, n) * 2 + w) : (uint32_t)((h * 8 + j) * 2 + w)) * 32768);
      TS(2 + t);
    }
    give(xs);
    const uint32_t qa = qreg + chunk_off();
#pragma unroll
    for (int i = 0; i < 16; i++) sts16(qa + (i >> 1) * 4096 + (i & 1) * 512, pk[4 * i], pk[4 * i + 1], pk[4 * i + 2], pk[4 * i + 3]);
    fence_async_smem();
  }
  TS(8);

  constexpr float SC = 0.0625f * 1.4426950408889634f;
#pragma unroll 1
  for (int which = 0; which < 2; which++) {
    float s[32];
#pragma unroll
    for (int i = 0; i < 32; i++) s[i] = 0.f;
    uint32_t pa[16], pb[16];
    float m0 = 0.f, m1 = 0.f, l0 = 0.f, l1 = 0.f;
    const uint64_t dq = desc_64(qreg);
    uint64_t dk = 0, dqq = 0, dv = 0;
    auto prep_qk = [&](uint32_t kaddr) { dk = desc_64(kaddr); dqq = dq + (kaddr >> 31); asm volatile("" : "+l"(dk), "+l"(dqq)); };
    auto prep_pv = [&](uint32_t vaddr) { dv = desc_64(vaddr); asm volatile("" : "+l"(dv)); };
    auto issue_qk = [&]() {
#pragma unroll
      for (int kk = 0; kk < 16; kk++)
        wgmma_ss_n64(s, desc_add(dqq, (kk >> 1) * 4096 + (kk & 1) * 32), desc_add(dk, (kk >> 1) * 4096 + (kk & 1) * 32), kk != 0);
    };
    auto issue_pv = [&](int accumulate) {
#pragma unroll
      for (int kk = 0; kk < 4; kk++)
        wgmma_rs_n256_tb(acc, pa[4 * kk], pa[4 * kk + 1], pa[4 * kk + 2], pa[4 * kk + 3], desc_add(dv, kk * 1024), accumulate | kk);
    };
    auto mask_diag = [&]() {
      const int d = 16 * wq + (lane >> 2) - 2 * (lane & 3);
#pragma unroll
      for (int jj = 0; jj < 8; jj++) {
        if (8 * jj > d)     { s[4 * jj] = -INFINITY;     if (jj < 7) s[4 * jj + 6] = -INFINITY; }
        if (8 * jj + 1 > d) { s[4 * jj + 1] = -INFINITY; if (jj < 7) s[4 * jj + 7] = -INFINITY; }
      }
    };
    float a0, a1;
    auto softmax = [&]() -> bool {
      float x0 = fmaxf(s[0], s[1]), x1 = fmaxf(s[2], s[3]);
#pragma unroll
      for (int jj = 1; jj < 8; jj++) {
        x0 = fmaxf(x0, fmaxf(s[4 * jj], s[4 * jj + 1]));
        x1 = fmaxf(x1, fmaxf(s[4 * jj + 2], s[4 * jj + 3]));
      }
      x0 = fmaxf(x0, __shfl_xor_sync(0xffffffffu, x0, 1));
      x1 = fmaxf(x1, __shfl_xor_sync(0xffffffffu, x1, 1));
      x0 = fmaxf(x0, __shfl_xor_sync(0xffffffffu, x0, 2));
      x1 = fmaxf(x1, __shfl_xor_sync(0xffffffffu, x1, 2));
      const bool grow = __any_sync(0xffffffffu, fmaxf(x0 - m0, x1 - m1) * SC > 8.f);
      if (grow) {
        x0 = fmaxf(x0, m0); x1 = fmaxf(x1, m1);
        a0 = ex2((m0 - x0) * SC); a1 = ex2((m1 - x1) * SC);
        m0 = x0; m1 = x1;
        l0 *= a0; l1 *= a1;
      }
      const float b0 = -m0 * SC, b1 = -m1 * SC;
      float t0 = 0.f, t1 = 0.f, t2 = 0.f, t3 = 0.f;
#pragma unroll
      for (int jj = 0; jj < 8; jj++) {
        s[4 * jj]     = ex2(fmaf(s[4 * jj], SC, b0));
        s[4 * jj + 1] = ex2(fmaf(s[4 * jj + 1], SC, b0));
        s[4 * jj + 2] = ex2(fmaf(s[4 * jj + 2], SC, b1));
        s[4 * jj + 3] = ex2(fmaf(s[4 * jj + 3], SC, b1));
        t0 += s[4 * jj]; t1 += s[4 * jj + 1]; t2 += s[4 * jj + 2]; t3 += s[4 * jj + 3];
      }
      l0 += t0 + t1; l1 += t2 + t3;
      return grow;
    };
    auto softmax_fast = [&](uint32_t (&pp)[16], auto first, auto hook) -> bool {
      const float b0 = -m0 * SC, b1 = -m1 * SC;
      float t0 = 0.f, t1 = 0.f, t2 = 0.f, t3 = 0.f;
#pragma unroll
      for (int jj = 0; jj < 8; jj++) {
        const float e0 = ex2(fmaf(s[4 * jj], SC, b0)), e1 = ex2(fmaf(s[4 * jj + 1], SC, b0));
        const float e2 = ex2(fmaf(s[4 * jj + 2], SC, b1)), e3 = ex2(fmaf(s[4 * jj + 3], SC, b1));
        hook(jj, e0);
        pp[2 * jj] = pack_bf16(e0, e1); pp[2 * jj + 1] = pack_bf16(e2, e3);
        if (jj == 0) { t0 = e0; t1 = e1; t2 = e2; t3 = e3; } else { t0 += e0; t1 += e1; t2 += e2; t3 += e3; }
      }
      t0 += t1; t2 += t3;
      bool redo = __any_sync(0xffffffffu, !(t0 + t2 <= 16777216.f));
      if (decltype(first)::value) {
        uint32_t u0 = __ballot_sync(0xffffffffu, t0 >= 1.52587890625e-05f), u1 = __ballot_sync(0xffffffffu, t2 >= 1.52587890625e-05f);
        u0 |= u0 >> 1; u1 |= u1 >> 1;
        redo |= (((u0 | (u0 >> 2)) & (u1 | (u1 >> 2))) & 0x11111111u) != 0x11111111u;
      }
      if (!redo) { l0 += t0; l1 += t2; }
      return redo;
    };
    auto rescale = [&]() {
#pragma unroll
      for (int i = 0; i < 32; i++) { acc[4 * i] *= a0; acc[4 * i + 1] *= a0; acc[4 * i + 2] *= a1; acc[4 * i + 3] *= a1; }
    };
    auto to_p = [&](uint32_t (&pp)[16]) {
#pragma unroll
      for (int i = 0; i < 16; i++) pp[i] = pack_bf16(s[2 * i], s[2 * i + 1]);
    };
    auto q_free = [&]() { if (lane == 0) mbar_arrive(bar_addr(sb, B_QFREE + w)); };

    const int n = 2 * q_tile(h, j, which) + 1 + (w ^ which);
    uint32_t ks = take(rdy0);
    TS(9 + 5 * which);
    prep_qk(sb + ks * SLOT);
    turn_begin();
    TS(20 + 10 * which);
    wg_fence();
    issue_qk();
    wg_commit();
    turn_end();
    if (which == 1) give(take(rdy1));
    TS(22 + 10 * which);
    wg_wait<0>();
    TS(21 + 10 * which);
    reg_fence(s);
    give(ks);
    if (which == 0 && n == 1) q_free();
    if (which == 1 || n == 1) mask_diag();
    {
      const uint4* dst = at<uint4>(g_qc, (uint32_t)((h * 8 + j) * 2 + w) * 32768 + (fresh_tid() & 127) * 16);
      const bool redo = softmax_fast(pa, Int<1>(), [&](int jj, float e) {
        if (jj == PEEK_JJ) peek2();
        const int i = CTX_SPLIT + jj;
        if (i < 16)
          asm volatile("{\n.reg .pred p, q;\nsetp.ne.b32 q, %6, 0;\nsetp.geu.and.f32 p, %5, 0fBF800000, q;\n@p st.global.v4.u32 [%0], {%1, %2, %3, %4};\n}"
                       :: "l"(dst + i * 128), "r"(pk[4 * (i & 15)]), "r"(pk[4 * (i & 15) + 1]), "r"(pk[4 * (i & 15) + 2]), "r"(pk[4 * (i & 15) + 3]), "f"(e), "r"(which) : "memory");
      });
      if (redo) {
        m0 = -INFINITY; m1 = -INFINITY;
        softmax();
        to_p(pa);
      }
    }
    if (which == 1) warp_arrive(bar_addr(sb, B_ST_CTX + w), lane);
    TS(10 + 5 * which);
#pragma unroll 1
    for (int jj = 1; jj < n; jj++) {
      ks = take(rdy0);
      const uint32_t vs = take(rdy1);
      prep_qk(sb + ks * SLOT);
      prep_pv(sb + vs * SLOT);
      TSC(23 + 10 * which, jj == 1);
      turn_begin();
      TSC(24 + 10 * which, jj == 1);
      TSC(26 + 10 * which, jj == n - 1);
      wg_fence();
      issue_qk();
      wg_commit();
      issue_pv(jj > 1);
      wg_commit();
      turn_end();
      wg_wait<1>();
      TSC(25 + 10 * which, jj == 1);
      reg_fence(s);
      give(ks);
      if (jj == n - 1 && which == 0) { q_free(); mask_diag(); }
      if (PF_CTX && which == 1 && jj == max(n - PF_CTX, 1)) {
        const uint8_t* src = at<const uint8_t>(g_qc, (uint32_t)(((h ^ 8) * 8 + j) * 2 + (w ^ 1)) * 32768 + (fresh_tid() & 127) * 128);
        asm volatile("prefetch.global.L2 [%0];" :: "l"(src));
        asm volatile("prefetch.global.L2 [%0];" :: "l"(src + 16384));
      }
      if (softmax_fast(pb, Int<0>(), [](int, float) {})) {
        wg_wait<0>();
        reg_fence(acc);
        if (softmax()) rescale();
        to_p(pb);
      }
      peek2();
      wg_wait<0>();
      reg_fence(acc);
      reg_fence(pa);
      give(vs);
#pragma unroll
      for (int i = 0; i < 16; i++) pa[i] = pb[i] | (vs >> 8);
    }
    TS(11 + 5 * which);
    if (which == 0) { give(take(rdy0)); rdy0 = rdy1; }
    {
      const uint32_t vs = take(rdy0);
      prep_pv(sb + vs * SLOT);
      TS(27 + 10 * which);
      turn_begin();
      TS(28 + 10 * which);
      wg_fence();
      issue_pv(n > 1);
      wg_commit();
      turn_end();
      l0 += __shfl_xor_sync(0xffffffffu, l0, 1); l1 += __shfl_xor_sync(0xffffffffu, l1, 1);
      l0 += __shfl_xor_sync(0xffffffffu, l0, 2); l1 += __shfl_xor_sync(0xffffffffu, l1, 2);
      asm("rcp.approx.ftz.f32 %0, %0;" : "+f"(l0));
      asm("rcp.approx.ftz.f32 %0, %0;" : "+f"(l1));
      peek2();
      if (which == 0) mbar_wait(bar_addr(sb, B_QFULL + w), 0);
      wg_wait<0>();
      reg_fence(acc);
      reg_fence(pa);
      give(vs);
    }
    TS(12 + 5 * which);
    {
      const uint4* dst = at<uint4>(g_qc, (uint32_t)((h * 8 + j) * 2 + w) * 32768 + (fresh_tid() & 127) * 16);
#pragma unroll
      for (int i = 0; i < 16; i++) {
        const int c = (i & 1) ? (i >> 1) + 8 : i >> 1;
        pk[4 * c]     = pack_bf16(acc[8 * c] * l0, acc[8 * c + 1] * l0);
        pk[4 * c + 1] = pack_bf16(acc[8 * c + 2] * l1, acc[8 * c + 3] * l1);
        pk[4 * c + 2] = pack_bf16(acc[8 * c + 4] * l0, acc[8 * c + 5] * l0);
        pk[4 * c + 3] = pack_bf16(acc[8 * c + 6] * l1, acc[8 * c + 7] * l1);
        if (c < CTX_SPLIT)
          asm volatile("{\n.reg .pred p;\nsetp.eq.b32 p, %5, 0;\n@p st.global.v4.u32 [%0], {%1, %2, %3, %4};\n}"
                       :: "l"(dst + c * 128), "r"(pk[4 * c]), "r"(pk[4 * c + 1]), "r"(pk[4 * c + 2]), "r"(pk[4 * c + 3]), "r"(which) : "memory");
      }
    }
    TS(13 + 5 * which);
  }

  {
    float oa[32], ob[32];
#pragma unroll
    for (int i = 0; i < 32; i++) { oa[i] = 0.f; ob[i] = 0.f; }
    uint32_t pk2[64];
    auto stage = [&](float (&o)[32], int ch) {
      reg_fence(o);
      uint32_t q[16];
#pragma unroll
      for (int i = 0; i < 16; i++) q[i] = pack_bf16(o[2 * i], o[2 * i + 1]);
      if (ch >= 4) mbar_wait(bar_addr(sb, B_S2_EMPTY + w * 4 + (ch & 3)), 0);
      store_block(qreg + (ch & 3) * 8192, lane_base16(), q);
    };
    auto hand_over = [&](int ch) {
      fence_async_smem();
      warp_arrive(bar_addr(sb, B_S2_FULL + w * 4 + (ch & 3)), lane);
    };
    uint32_t prev = 0;
    auto half = [&](int f, float (&o)[32], uint32_t (&a)[64], int accumulate) {
      const uint32_t sl = take(rdy0);
      const uint64_t d = desc_mn(sb + sl * SLOT);
      turn_begin();
      TS(40 + f);
      wg_fence();
#pragma unroll
      for (int kk = 0; kk < 16; kk++) {
        wgmma_rs_n64_tb(o, a[4 * kk], a[4 * kk + 1], a[4 * kk + 2], a[4 * kk + 3], desc_add(d, kk * 2048), accumulate | kk);
        if (kk == ARRIVE_KK && (f < 13 || w == 0)) turn_end();
      }
      wg_commit();
      if (f < 13) rdy0 = mbar_test(bar_addr(sb, B_FULL + r.slot), r.phase);
      wg_wait<1>();
      if (f >= 1 && f <= 9) give(prev);
      prev = sl;
    };
    auto load_ctx = [&](auto h0) {
      constexpr int I0 = decltype(h0)::value ? CTX_LD : 0, NL = decltype(h0)::value ? 16 - CTX_LD : CTX_LD;
      const uint4* src = at<const uint4>(g_qc, (uint32_t)(((h ^ 8) * 8 + j) * 2 + (w ^ 1)) * 32768 + (fresh_tid() & 127) * 16);
#pragma unroll
      for (int i = I0; i < I0 + NL; i++) { const uint4 v = __ldcg(src + i * 128); pk2[4 * i] = v.x; pk2[4 * i + 1] = v.y; pk2[4 * i + 2] = v.z; pk2[4 * i + 3] = v.w; }
    };
    half(0, oa, pk, 0);
    mbar_wait(bar_addr(sb, B_CTXOK + w), 0);
    load_ctx(Int<0>());
    half(1, ob, pk, 0);
    load_ctx(Int<1>());
    half(2, oa, pk2, 1);
#pragma unroll 1
    for (int i = 0; i < 3; i++) {
      half(4 * i + 3, ob, pk2, 1);
      if (i == 0) stage(oa, 0); else if (!HAND_NOW) hand_over(2 * i);
      half(4 * i + 4, oa, pk, 0);
      if (i == 0) hand_over(0);
      stage(ob, 2 * i + 1);
      if (HAND_NOW) hand_over(2 * i + 1);
      half(4 * i + 5, oa, pk2, 1);
      if (!HAND_NOW) hand_over(2 * i + 1);
      if (i == 2) break;
      half(4 * i + 6, ob, pk, 0);
      stage(oa, 2 * i + 2);
      if (HAND_NOW) hand_over(2 * i + 2);
    }
    wg_wait<0>();
    reg_fence(pk);
    reg_fence(pk2);
    stage(oa, 6);
    fence_async_smem();
    named_sync(1 + w, 128);
    if (wq == 0 && lane == 0) {
      tma_red2(&p.o, qreg + 2 * 8192, DA + 6 * 64, q_tile(h, j, 1) * 128 + (w ^ 1) * 64);
      bulk_commit();
      bulk_wait_read();
    }
  }
  TS(19);
  TDUMP();
}

namespace ssm {
constexpr int NCH = DA / NCONV;
constexpr int NS = 8, NP = 6;
constexpr uint32_t X0 = 384;
constexpr uint32_t HO = X0 + 4096;
constexpr uint32_t HE = HO + HO_STRIDE + 64;
constexpr uint32_t SSLOT = HE + 4096 + 64;
constexpr uint32_t PART = 264 * 16;
constexpr uint32_t OFF_P = NS * SSLOT, OFF_D = OFF_P + NP * 4 * PART, END = OFF_D + NCH * 4;
static_assert(SSLOT % 128 == 0 && HO % 128 == 0 && END <= BARS, "smem");
enum : uint32_t { B_FULL = 0, B_EMPTY = NS, B_PFULL = 2 * NS, B_PEMPTY = 2 * NS + NP };
__device__ __forceinline__ int channel(int cidx, int i) { return (i >> 4) * 64 + cidx * 16 + (i & 15); }

__device__ __forceinline__ void producer(const Params& p, uint32_t sb, int cidx, unsigned epoch) {
#pragma unroll 1
  for (int i = 0; i < NCH; i++) {
    const int s = i % NS, ch = channel(cidx, i);
    const uint32_t full = bar_addr(sb, B_FULL + s), dst = sb + s * SSLOT;
    mbar_wait(bar_addr(sb, B_EMPTY + s), ((i / NS) & 1) ^ 1);
    mbar_expect_tx(full, 4096 + 4128 + 4096);
    bulk_ld(dst + HE, at<uint8_t>(p.a_ssmk, ch * 4096), 4096, full);
    if ((i & 15) == 0) { flag_wait(flag_at(g_flags.x_ready, i >> 4), NMAIN, epoch); fence_async_all(); }
    bulk_ld(dst + HO, at<uint8_t>(g_ho, ch * HO_STRIDE), 4128, full);
    bulk_ld(dst + X0, at<uint8_t>(g_xs, ch * 4096), 4096, full);
  }
}

__device__ __forceinline__ void reducer(uint32_t sb, int cidx, int rw) {
  uint32_t n = 0;
#pragma unroll 1
  for (int i = rw; i < NCH; i += 3, n++) {
    const uint32_t b = rw + 3 * (n & 1), pb = sb + OFF_P + b * 4 * PART;
    uint8_t* dst = at<uint8_t>(g_xs, channel(cidx, i) * 4096);
    mbar_wait(bar_addr(sb, B_PFULL + b), (n >> 1) & 1);
    asm volatile("cp.async.bulk.global.shared::cta.bulk_group [%0], [%1], 4096;" :: "l"(dst), "r"(pb + 3 * PART) : "memory");
    bulk_commit();
    bulk_wait_all();
#pragma unroll
    for (int k = 2; k >= 0; k--)
      asm volatile("cp.reduce.async.bulk.global.shared::cta.bulk_group.add.noftz.bf16 [%0], [%1], 4096;" :: "l"(dst), "r"(pb + k * PART) : "memory");
    bulk_commit();
    bulk_wait_read();
    mbar_arrive(bar_addr(sb, B_PEMPTY + b));
    if (((i + 3) >> 4) != (i >> 4)) {
      bulk_wait_all();
      fence_async_all();
      flag_signal(flag_at(g_flags.z_ready, i >> 4));
    }
  }
}

__device__ __forceinline__ void mma_warpgroup(uint32_t sb, int w) {
  const int lane = threadIdx.x & 31, g = lane >> 2, c = lane & 3, wq = (threadIdx.x >> 5) & 3;
  const uint32_t aoff = ((g & 1) ? HO + 30 : HE) + (16 * wq - g + 2 * c) * 2;
  const uint32_t poff = OFF_P + wq * PART + (2 * wq + lane) * 16;
  const uint32_t dmask = (wq == 0 && c == (g >> 1)) ? ((g & 1) ? 0xffff0000u : 0xffffu) : 0u;
  float acc[8][16];
  uint32_t fa[16][4];
#pragma unroll
  for (int e = 0; e < 8; e++)
#pragma unroll
    for (int i = 0; i < 16; i++) acc[e][i] = 0.f;
  auto load_a = [&](int m, uint32_t ad) {
    fa[m][0] = lds4(ad + m * 256 + 16); fa[m][1] = lds4(ad + m * 256 + 144); fa[m][2] = lds4(ad + m * 256); fa[m][3] = lds4(ad + m * 256 + 128);
  };
  if (w == 1) named_arrive(PP_BAR, 256);
  mbar_wait(bar_addr(sb, B_FULL + w), 0);
#pragma unroll
  for (int m = 0; m < 16; m++) load_a(m, sb + w * SSLOT + aoff);
  uint32_t dd = lds4(sb + OFF_D + w * 4);
  if (threadIdx.x == 128) { GT(12); PT(10); }
  uint32_t pb = w, pphase = 1;
#pragma unroll 1
  for (int i = w; i < NCH; i += 2) {
    fa[0][2] = badd(fa[0][2], dd & dmask);
    const uint64_t db = (uint64_t)((((sb + (i % NS) * SSLOT + X0 - 16) & 0x3FFFF) >> 4) | (1u << 16)) | ((uint64_t)8 << 32);
    named_sync(PP_BAR + w, 256);
    wg_fence();
#pragma unroll
    for (int r = 0; r < 16; r++) {
      auto mm = [&](int e, int m) { wgmma_rs_n32(acc[e], fa[m][0], fa[m][1], fa[m][2], fa[m][3], db + (int64_t)(32 * e - 16 * m), m != 0); };
      mm(7, r);
      if (r < 14) mm(6, r); else mm(0, r - 14);
      if (r < 12) mm(5, r); else mm(1, r - 12);
      if (r < 10) mm(4, r); else mm(2, r - 10);
      if ((r & 1) == 0) mm(3, r >> 1);
      if (r == CONV_ARRIVE && (i + 1 < NCH)) named_arrive(PP_BAR + (w ^ 1), 256);
    }
    wg_commit();
    const int nx = i + 2 < NCH ? i + 2 : i;
    mbar_wait(bar_addr(sb, B_FULL + nx % NS), (nx / NS) & 1);
    mbar_wait(bar_addr(sb, B_PEMPTY + pb), pphase);
    const uint32_t ad = sb + (nx % NS) * SSLOT + aoff, pa = sb + pb * 4 * PART + poff;
    wg_wait<0>();
#pragma unroll
    for (int e = 0; e < 8; e++) reg_fence(acc[e]);
#pragma unroll
    for (int m = 0; m < 16; m++) reg_fence(fa[m]);
    if (lane == 0) mbar_arrive(bar_addr(sb, B_EMPTY + i % NS));
#pragma unroll
    for (int e = 0; e < 8; e++) {
      if (e < CONV_EARLY) load_a(e, ad);
      uint32_t u[4];
#pragma unroll
      for (int j = 0; j < 4; j++) {
        const int T = 4 * e + j, U = T - 1;
        float lo = acc[e][4 * j], hi = acc[e][4 * j + 1];
        if (T > 0) { lo += acc[U >> 2][4 * (U & 3) + 2]; hi += acc[U >> 2][4 * (U & 3) + 3]; }
        u[j] = pack_bf16(lo, hi);
      }
      asm volatile("stmatrix.sync.aligned.m8n8.x4.trans.shared.b16 [%0], {%1, %2, %3, %4};" :: "r"(pa + e * 512), "r"(u[0]), "r"(u[1]), "r"(u[2]), "r"(u[3]) : "memory");
    }
    dd = lds4(sb + OFF_D + nx * 4);
#pragma unroll
    for (int m = CONV_EARLY; m < CONV_FENCE; m++) load_a(m, ad);
    fence_async_smem();
    warp_arrive(bar_addr(sb, B_PFULL + pb), lane);
#pragma unroll
    for (int m = CONV_FENCE; m < 16; m++) load_a(m, ad);
    pb += 2;
    if (pb >= NP) { pb -= NP; pphase ^= 1; }
  }
  if (threadIdx.x == 128) { PT(9); GT(13); }
}

__device__ __forceinline__ void init(const Params& p, uint32_t sb, int cidx) {
  const uint32_t t = threadIdx.x;
  if (t < NCH) {
    const uint32_t d = (uint32_t)__ldg(reinterpret_cast<const unsigned short*>(p.a_D + channel(cidx, t))) * 0x10001u;
    asm volatile("st.shared.u32 [%0], %1;" :: "r"(sb + OFF_D + t * 4), "r"(d) : "memory");
  }
#pragma unroll 1
  for (uint32_t u = t; u < NS * 32; u += 128) {
    const uint32_t r = u & 31;
    if (r < 28) sts16(sb + (u >> 5) * SSLOT + (r < 24 ? r * 16 : HE - 64 + (r - 24) * 16), 0, 0, 0, 0);
    if (u < NP * 32) sts16(sb + OFF_P + (u >> 3) * PART + (u & 7) * 16, 0, 0, 0, 0);
  }
  if (t == 0) {
    for (int i = 0; i < NS; i++) { mbar_init(bar_addr(sb, B_FULL + i), 1); mbar_init(bar_addr(sb, B_EMPTY + i), 4); }
    for (int i = 0; i < NP; i++) { mbar_init(bar_addr(sb, B_PFULL + i), 4); mbar_init(bar_addr(sb, B_PEMPTY + i), 1); }
  }
  fence_async_smem();
}

__device__ __forceinline__ void side_prepare(const Params& p, int cta, int rd) {
  const int lane = threadIdx.x & 31, t0 = 16 * cta + 8 * (lane & 1);
  if (EXP_SIDE & 16) { if (lane == 0) flag_signal_after_bulk(flag_at(g_flags.x_ready, rd)); return; }
#pragma unroll 1
  for (int ch = 64 * rd + (lane & ~1); ch < 64 * rd + 64; ch += 32) {
    const uint4 sv = __ldg(at<const uint4>(p.a_shift, ch * 8));
    const uint32_t* kp = at<const uint32_t>(p.a_k, (t0 * DA + ch) * 2);
    const uint32_t* vp = at<const uint32_t>(p.a_v, (t0 * DA + ch) * 2);
    uint32_t k0 = 0, k1 = 0, k2 = 0, kk[8], x[8];
    if (t0 > 0) { k0 = __ldg(kp - 3 * (DA / 2)); k1 = __ldg(kp - 2 * (DA / 2)); k2 = __ldg(kp - DA / 2); }
#pragma unroll
    for (int i = 0; i < 8; i++) { kk[i] = __ldg(kp + i * (DA / 2)); x[i] = __ldg(vp + i * (DA / 2)); }
    const uint32_t sh0 = __byte_perm(sv.x, sv.z, 0x5410), sh1 = __byte_perm(sv.x, sv.z, 0x7632);
    const uint32_t sh2 = __byte_perm(sv.y, sv.w, 0x5410), sh3 = __byte_perm(sv.y, sv.w, 0x7632);
#pragma unroll
    for (int i = 0; i < 8; i++) {
      uint32_t ks = bmul(k0, sh3);
      ks = badd(ks, bmul(k1, sh2)); ks = badd(ks, bmul(k2, sh1)); ks = badd(ks, bmul(kk[i], sh0));
      x[i] = bmul(ks, x[i]);
      k0 = k1; k1 = k2; k2 = kk[i];
    }
    uint4* dst = at<uint4>(g_xs, ch * 4096 + t0 * 2);
    if ((EXP_SIDE & 4) && (x[0] ^ x[1] ^ x[2] ^ x[3] ^ x[4] ^ x[5] ^ x[6] ^ x[7]) != 0x12345) continue;
    dst[0]   = make_uint4(__byte_perm(x[7], x[6], 0x5410), __byte_perm(x[5], x[4], 0x5410), __byte_perm(x[3], x[2], 0x5410), __byte_perm(x[1], x[0], 0x5410));
    dst[256] = make_uint4(__byte_perm(x[7], x[6], 0x7632), __byte_perm(x[5], x[4], 0x7632), __byte_perm(x[3], x[2], 0x7632), __byte_perm(x[1], x[0], 0x7632));
  }
  if (!(EXP_SIDE & 8)) {
    const int hc = 64 * rd + (cta >> 1), r0 = (cta & 1) * 128 + lane;
    const uint4* src = at<const uint4>(p.a_ssmk, hc * 4096 + r0 * 16);
    uint4* dst = at<uint4>(g_ho, hc * HO_STRIDE + r0 * 16);
    uint4 w[4];
    uint32_t nx[4];
#pragma unroll
    for (int i = 0; i < 4; i++) { w[i] = __ldg(src + 32 * i); nx[i] = r0 + 32 * i < 255 ? __ldg(reinterpret_cast<const uint32_t*>(src + 32 * i + 1)) : 0u; }
#pragma unroll
    for (int i = 0; i < 4; i++)
      dst[32 * i + 2] = make_uint4(__byte_perm(w[i].x, w[i].y, 0x5432), __byte_perm(w[i].y, w[i].z, 0x5432), __byte_perm(w[i].z, w[i].w, 0x5432), __byte_perm(w[i].w, nx[i], 0x5432));
    const uint32_t h0 = __shfl_sync(0xffffffffu, w[0].x, 0);
    if (r0 < 2) dst[0] = make_uint4(0, 0, 0, r0 ? h0 << 16 : 0u);
  }
  __syncwarp();
  if (lane == 0) { if (EXP_SIDE & 2) flag_signal_after_bulk(flag_at(g_flags.x_ready, rd)); else flag_signal(flag_at(g_flags.x_ready, rd)); }
}
__device__ __forceinline__ void side_finish(const Params& p, int cta, int rd) {
  const int lane = threadIdx.x & 31, t0 = 16 * cta + 8 * (lane & 1);
#pragma unroll 1
  for (int ch = 64 * rd + (lane & ~1); ch < 64 * rd + 64; ch += 32) {
    const uint4* src = at<const uint4>(g_xs, ch * 4096 + t0 * 2);
    const uint32_t* qp = at<const uint32_t>(p.a_q, (t0 * DA + ch) * 2);
    uint32_t* op = at<uint32_t>(p.out, (t0 * OUTW + ch) * 2);
    const uint4 z0 = __ldcg(src), z1 = __ldcg(src + 256);
    uint32_t q[8];
#pragma unroll
    for (int i = 0; i < 8; i++) q[i] = __ldg(qp + i * (DA / 2));
    const uint32_t a[4] = {z0.w, z0.z, z0.y, z0.x}, b[4] = {z1.w, z1.z, z1.y, z1.x};
#pragma unroll
    for (int i = 0; i < 4; i++) {
      op[(2 * i) * (OUTW / 2)]     = bmul(q[2 * i], __byte_perm(a[i], b[i], 0x7632));
      op[(2 * i + 1) * (OUTW / 2)] = bmul(q[2 * i + 1], __byte_perm(a[i], b[i], 0x5410));
    }
  }
}
__device__ __forceinline__ void clear_rows(const Params& p, int qt, int part) {
  const int lane = threadIdx.x & 31;
  if (lane < 28) {
    uint4* z = at<uint4>(p.out, ((qt * 128 + part * 16) * OUTW + DA) * 2 + lane * 16);
#pragma unroll
    for (int i = 0; i < 32; i++) z[(i >> 1) * (OUTW / 8) + (i & 1) * 28] = make_uint4(0, 0, 0, 0);
  }
  __syncwarp();
  if (lane == 0) flag_signal(flag_at(g_flags.zero_ready, qt));
}
__device__ __forceinline__ void side_work(const Params& p, int cta, int qt, unsigned epoch) {
#pragma unroll 1
  for (int rd = -SIDE_AHEAD; rd < 7; rd++) {
    if (rd >= 0) {
      if ((threadIdx.x & 31) == 0) flag_wait_slow(flag_at(g_flags.z_ready, rd), 3 * NCONV, epoch);
      __syncwarp();
    }
    if (rd + SIDE_AHEAD < 7) side_prepare(p, cta, rd + SIDE_AHEAD);
    if (rd >= 0 && !(EXP_SIDE & 1)) side_finish(p, cta, rd);
    if (rd == ZERO_RD) clear_rows(p, qt, (cta >> 3) & 7);
  }
}
}

__global__ void __cluster_dims__(2, 1, 1) __launch_bounds__(NTHREADS, 1)
concat_heads__ssm_conv_h3__compressed_kv_cla__prompt_kernel(const __grid_constant__ Params p) {
  extern __shared__ uint8_t smem_raw[];
  const uint32_t sb = (smem_u32(smem_raw) + 1023) & ~1023u;
  if ((PF_MAPS & 2) && threadIdx.x == NTHREADS - 64) { prefetch_map(&p.wuk); prefetch_map(&p.ckv); }
  const int cta = blockIdx.x;
  const bool attn = cta < NMAIN;
  int h, u;
  {
    const int c = cta >> 1;
    const int u2 = ((c - 36) * 37) >> 8, i = c - 36 - 7 * u2;
    h = c < 4 ? 9 : c < 36 ? (c - 4) & 7 : i == 0 ? 8 : 9 + i;
    u = c < 4 ? c : c < 36 ? (c - 4) >> 3 : u2;
  }
  const int j = 2 * u + (cta & 1);
  if (attn && threadIdx.x == NTHREADS - 32) {
    const uint32_t full = bar_addr(sb, B_FULL);
    mbar_init(full, 1);
    asm volatile("fence.mbarrier_init.release.cluster;" ::: "memory");
    mbar_expect_tx(full, 49152);
    tma_ld3(sb, p1_isv(j, 0) ? &p.wuv : &p.wuk, full, 0, 0, p1_head(h, j, 0) * 4);
    tma_ld2(sb + QREG, &p.ckv, full, 0, p1_rows(h, j, 0) * 128);
  }
  __syncwarp();
  const int lane = threadIdx.x & 31;
  const int warp = __shfl_sync(0xffffffffu, threadIdx.x >> 5, 0);
  const int wg = warp >> 2;
  if (wg != 0) {
    if (attn) {
      cluster_arrive();
      if (wg == 2) named_arrive(PP_BAR, 256);
    }
    asm volatile("setmaxnreg.inc.sync.aligned.u32 232;");
    if (!attn) {
      if (p.out != nullptr) { named_sync(0, NTHREADS); ssm::mma_warpgroup(sb, wg - 1); }
      return;
    }
    if (p.out != nullptr) consumer_main(p, sb, h, j, wg - 1, warp & 3);
  } else {
    asm volatile("setmaxnreg.dec.sync.aligned.u32 40;");
    if (!attn) {
      ssm::init(p, sb, cta - NMAIN);
      named_sync(0, NTHREADS);
      if (lane == 0) {
        if (warp == 0) { ssm::producer(p, sb, cta - NMAIN, load_epoch()); cta_done(32); }
        else ssm::reducer(sb, cta - NMAIN, warp - 1);
        if (warp == 1) GT(14);
      }
      return;
    }
    if (warp == 0) {
      if (lane == 0) {
        for (int i = 1; i < NSLOT; i++) mbar_init(bar_addr(sb, B_FULL + i), 1);
        asm volatile("fence.mbarrier_init.release.cluster;" ::: "memory");
      }
      __syncwarp();
      cluster_arrive();
      if (lane == 0) {
#pragma unroll 1
        for (int k = 1; k < EARLY_LD; k++) {
          const uint32_t full = bar_addr(sb, B_FULL + k);
          mbar_expect_tx(full, 49152);
          tma_ld3(sb + k * SLOT, p1_isv(j, 0) ? &p.wuv : &p.wuk, full, 0, k * 64, p1_head(h, j, 0) * 4);
          tma_ld2(sb + QREG + k * 16384, &p.ckv, full, k * 64, p1_rows(h, j, 0) * 128);
          if (EARLY_GAP) __nanosleep(EARLY_GAP);
        }
      }
      __syncwarp();
      cluster_wait();
      if (lane == 0) producer_main(p, sb, h, j);
      return;
    }
    if (lane == 0) {
      if (warp == 1) {
        for (int i = 0; i < NSLOT; i++) mbar_init(bar_addr(sb, B_EMPTY + i), (UNICAST & 8) ? 8 : 16);
        for (int i = 0; i < 2; i++) {
          mbar_init(bar_addr(sb, B_QFREE + i), 4); mbar_init(bar_addr(sb, B_QFULL + i), 1);
          mbar_init(bar_addr(sb, B_KVOK + i), 1); mbar_init(bar_addr(sb, B_CTXOK + i), 1);
        }
      } else if (warp == 2) {
        for (int i = 0; i < 8; i++) { mbar_init(bar_addr(sb, B_S2_FULL + i), 4); mbar_init(bar_addr(sb, B_S2_EMPTY + i), 1); }
      } else {
        mbar_init(bar_addr(sb, B_DONE), 2);
        for (int i = 0; i < 2; i++) {
          mbar_init(bar_addr(sb, B_ST_KV + i), 4); mbar_init(bar_addr(sb, B_ST_KV + 2 + i), 4);
          mbar_init(bar_addr(sb, B_ST_Q + i), 4); mbar_init(bar_addr(sb, B_ST_CTX + i), 4);
        }
      }
      asm volatile("fence.mbarrier_init.release.cluster;" ::: "memory");
    }
    __syncwarp();
    cluster_arrive();
    cluster_wait();
    if (warp < 3) {
      if (lane == 0) {
        if ((PF_MAPS & 1) && warp == 1) { __nanosleep(2000); prefetch_map(&p.wuv); prefetch_map(&p.x); prefetch_map(&p.wq); prefetch_map(&p.o); prefetch_map(&p.wo); }
        helper_main(p, sb, h, j, warp - 1);
      }
    } else {
      ssm::side_work(p, h * 8 + j, q_tile(h, j, 1), load_epoch());
      if (lane == 0) { GT(57); mbar_wait(bar_addr(sb, B_DONE), 0); cta_done(1); }
    }
  }
}

typedef CUresult (*EncodeTiledFn)(CUtensorMap*, CUtensorMapDataType, cuuint32_t, void*, const cuuint64_t*, const cuuint64_t*,
                                  const cuuint32_t*, const cuuint32_t*, CUtensorMapInterleave, CUtensorMapSwizzle,
                                  CUtensorMapL2promotion, CUtensorMapFloatOOBfill);

void make_map(EncodeTiledFn enc, CUtensorMap* m, const void* ptr, int rank, const uint64_t* dims, const uint64_t* strides, const uint32_t* box) {
  cuuint64_t d[5], s[4]; cuuint32_t b[5], e[5] = {1, 1, 1, 1, 1};
  for (int i = 0; i < rank; i++) { d[i] = dims[i]; b[i] = box[i]; if (i) s[i - 1] = strides[i - 1]; }
  enc(m, CU_TENSOR_MAP_DATA_TYPE_BFLOAT16, rank, const_cast<void*>(ptr), d, s, b, e, CU_TENSOR_MAP_INTERLEAVE_NONE,
      CU_TENSOR_MAP_SWIZZLE_128B, CU_TENSOR_MAP_L2_PROMOTION_L2_256B, CU_TENSOR_MAP_FLOAT_OOB_FILL_NONE);
}
void map2(EncodeTiledFn enc, CUtensorMap* m, const void* ptr, uint64_t cols, uint64_t rows, uint32_t bc, uint32_t br) {
  const uint64_t dims[2] = {cols, rows}, st[1] = {cols * 2}; const uint32_t box[2] = {bc, br};
  make_map(enc, m, ptr, 2, dims, st, box);
}
void map3(EncodeTiledFn enc, CUtensorMap* m, const void* ptr, uint64_t rows, uint32_t nblk) {
  const uint64_t dims[3] = {64, rows, 64}, st[2] = {8192, 128}; const uint32_t box[3] = {64, 64, nblk};
  make_map(enc, m, ptr, 3, dims, st, box);
}

}

extern "C" void kernel_launch(void* const* d_in, const int* in_sizes, int n_in, void* d_out, int out_size) {
  (void)in_sizes; (void)n_in; (void)out_size;
  static EncodeTiledFn enc = nullptr;
  if (!enc) {
    void* fn = nullptr; cudaDriverEntryPointQueryResult qr;
    cudaGetDriverEntryPoint("cuTensorMapEncodeTiled", &fn, cudaEnableDefault, &qr);
    enc = (EncodeTiledFn)fn;
    cudaFuncSetAttribute(concat_heads__ssm_conv_h3__compressed_kv_cla__prompt_kernel, cudaFuncAttributeMaxDynamicSharedMemorySize, SMEM_BYTES);
  }
  Params p;
  p.a_q = (const bf16*)d_in[0]; p.a_k = (const bf16*)d_in[1]; p.a_v = (const bf16*)d_in[2];
  p.a_shift = (const bf16*)d_in[3]; p.a_ssmk = (const bf16*)d_in[4]; p.a_D = (const bf16*)d_in[5];
  p.out = (bf16*)d_out;
  map2(enc, &p.x, d_in[6], DM, SEQ, 64, 128);
  map2(enc, &p.ckv, d_in[7], DC, SEQ, 64, 128);
  map3(enc, &p.wq, d_in[8], DM, 4);
  map3(enc, &p.wuk, d_in[9], DC, 4);
  map3(enc, &p.wuv, d_in[10], DC, 4);
  {
    const uint64_t dims[5] = {DM, 2, 4, 4, NH * HD / 32}, st[4] = {DM * 2, 8 * DM * 2, 2 * DM * 2, 32 * DM * 2}; const uint32_t box[5] = {64, 2, 4, 4, 4};
    make_map(enc, &p.wo, d_in[11], 5, dims, st, box);
  }
  map2(enc, &p.o, d_out, OUTW, SEQ, 64, 64);
  concat_heads__ssm_conv_h3__compressed_kv_cla__prompt_kernel<<<NCTA, NTHREADS, SMEM_BYTES>>>(p);
}
```

```cpp
#include <cuda_runtime.h>
#include <cuda_bf16.h>
#include <cuda.h>
#include <stdint.h>

namespace {

typedef __nv_bfloat16 bf16;

constexpr int SEQ  = 2048;
constexpr int DA   = 448;
constexpr int NH   = 16;
constexpr int HD   = 256;
constexpr int DM   = 448;
constexpr int DC   = 1024;
constexpr int OUTW = DA + DM;
constexpr int NMAIN = 128;
constexpr int NCONV = 4;
constexpr int NCTA  = NMAIN + NCONV;
constexpr int LOG_DONE = 8;
constexpr int NTHREADS = 384;

__device__ __align__(1024) bf16 g_kv[2ull * SEQ * NH * HD];
__device__ __align__(1024) bf16 g_qc[(size_t)NMAIN * 128 * HD];
__device__ __align__(128) uint8_t g_xs[DA * SEQ * 2];
constexpr uint32_t HO_STRIDE = 4224;
__device__ __align__(128) uint8_t g_ho[DA * HO_STRIDE];
struct alignas(128) Flag { unsigned v; unsigned pad[31]; };
struct Flags {
  Flag kv_ready[8];
  Flag ctx_ready[NMAIN * 2];
  Flag x_ready[7];
  Flag z_ready[7];
  Flag zero_ready[16];
  alignas(128) unsigned long long done;
};
__device__ Flags g_flags;
#define TS(i)
#define TSC(i, cond)
#define TDUMP()
#define GT(i)
#define PT(i)

struct alignas(64) Params {
  CUtensorMap ckv;
  CUtensorMap wuk;
  CUtensorMap wuv;
  CUtensorMap x;
  CUtensorMap wq;
  CUtensorMap o;
  CUtensorMap wo;
  const bf16 *a_q, *a_k, *a_v, *a_shift, *a_ssmk, *a_D;
  bf16* out;
};

constexpr uint32_t SLOT     = 32768;
constexpr int      NSLOT    = 5;
constexpr uint32_t QREG     = 163840;
constexpr uint32_t BARS     = 229376;
constexpr uint32_t SMEM_BYTES = BARS + 1024 + 1024;
enum : uint32_t {
  B_FULL = 0, B_EMPTY = 5, B_KVOK = 10, B_DONE = 11, B_ST_KV = 12, B_ST_Q = 14, B_ST_CTX = 16, B_CTXOK = 18, B_QFREE = 20, B_QFULL = 22,
  B_S2_FULL = 24, B_S2_EMPTY = 32
};
constexpr int P1_STEPS = 4 * 16 + 2 * 7, P1_XS = P1_STEPS - 2;

template <typename T> __device__ __forceinline__ T* at(const void* base, uint32_t off) {
  asm volatile("" : "+r"(off));
  return reinterpret_cast<T*>(const_cast<char*>(static_cast<const char*>(base)) + off);
}
__device__ __forceinline__ unsigned* flag_at(Flag* f, uint32_t i) { return at<unsigned>(f, i * (uint32_t)sizeof(Flag)); }
__device__ __forceinline__ uint32_t smem_u32(const void* p) { return (uint32_t)__cvta_generic_to_shared(p); }
__device__ __forceinline__ void mbar_init(uint32_t bar, uint32_t cnt) {
  asm volatile("mbarrier.init.shared::cta.b64 [%0], %1;" :: "r"(bar), "r"(cnt) : "memory");
}
__device__ __forceinline__ void mbar_expect_tx(uint32_t bar, uint32_t bytes) {
  asm volatile("mbarrier.arrive.expect_tx.shared::cta.b64 _, [%0], %1;" :: "r"(bar), "r"(bytes) : "memory");
}
__device__ __forceinline__ void mbar_arrive(uint32_t bar) {
  asm volatile("mbarrier.arrive.shared::cta.b64 _, [%0];" :: "r"(bar) : "memory");
}
__device__ __forceinline__ void mbar_arrive_remote(uint32_t bar, uint32_t cta) {
  asm volatile("{\n.reg .b32 ra;\nmapa.shared::cluster.u32 ra, %0, %1;\n"
               "mbarrier.arrive.shared::cluster.b64 _, [ra];\n}" :: "r"(bar), "r"(cta) : "memory");
}
__device__ __forceinline__ bool mbar_try(uint32_t bar, uint32_t parity) {
  uint32_t ok;
  asm volatile("{\n.reg .pred p;\nmbarrier.try_wait.parity.shared::cta.b64 p, [%1], %2;\nselp.u32 %0, 1, 0, p;\n}"
               : "=r"(ok) : "r"(bar), "r"(parity) : "memory");
  return ok;
}
__device__ __forceinline__ uint32_t mbar_test(uint32_t bar, uint32_t parity) {
  uint32_t ok;
  asm volatile("{\n.reg .pred p;\nmbarrier.test_wait.parity.shared::cta.b64 p, [%1], %2;\nselp.u32 %0, 1, 0, p;\n}"
               : "=r"(ok) : "r"(bar), "r"(parity) : "memory");
  return ok;
}
constexpr uint32_t SPIN_LIMIT = 1u << 24;
__device__ __forceinline__ void mbar_wait(uint32_t bar, uint32_t parity) {
  if (mbar_try(bar, parity)) return;
  uint32_t n = 0;
  while (!mbar_try(bar, parity)) { if (++n > SPIN_LIMIT) __trap(); }
}
__device__ __forceinline__ void mbar_wait_unless(uint32_t ready, uint32_t bar, uint32_t parity) {
  asm volatile("{\n.reg .pred p;\n.reg .b32 n;\nsetp.ne.u32 p, %0, 0;\nvote.sync.all.pred p, p, 0xffffffff;\n@p bra.uni WDONE;\nmov.u32 n, 0;\n"
               "WLOOP:\nmbarrier.try_wait.parity.shared::cta.b64 p, [%1], %2;\n@p bra.uni WDONE;\nadd.u32 n, n, 1;\nsetp.lt.u32 p, n, %3;\n@p bra.uni WLOOP;\ntrap;\nWDONE:\n}"
               :: "r"(ready), "r"(bar), "r"(parity), "n"(SPIN_LIMIT) : "memory");
}
__device__ __forceinline__ unsigned load_epoch() {
  unsigned long long d; asm volatile("ld.relaxed.gpu.global.u64 %0, [%1];" : "=l"(d) : "l"(&g_flags.done) : "memory");
  return (unsigned)(d >> LOG_DONE);
}
template <int SLEEP_NS>
__device__ __forceinline__ void flag_wait(const unsigned* f, unsigned count, unsigned epoch) {
  const unsigned target = (epoch + 1) * count;
  uint32_t n = 0;
  while (true) {
    unsigned v;
    asm volatile("ld.acquire.gpu.global.u32 %0, [%1];" : "=r"(v) : "l"(f) : "memory");
    if ((int)(v - target) >= 0) break;
    if (++n > SPIN_LIMIT / 4) __trap();
    __nanosleep(SLEEP_NS);
  }
}
__device__ __forceinline__ void flag_signal(unsigned* f) { asm volatile("red.release.gpu.global.add.u32 [%0], 1;" :: "l"(f) : "memory"); }
__device__ __forceinline__ void cta_done(unsigned long long n) { asm volatile("red.relaxed.gpu.global.add.u64 [%0], %1;" :: "l"(&g_flags.done), "l"(n) : "memory"); }
__device__ __forceinline__ void fence_async_global() { asm volatile("fence.proxy.async.global;" ::: "memory"); }
__device__ __forceinline__ void fence_async_smem() { asm volatile("fence.proxy.async.shared::cta;" ::: "memory"); }
__device__ __forceinline__ void tma_ld2(uint32_t dst, const CUtensorMap* m, uint32_t bar, int c0, int c1) {
  asm volatile("cp.async.bulk.tensor.2d.shared::cluster.global.mbarrier::complete_tx::bytes [%0], [%1, {%3, %4}], [%2];"
               :: "r"(dst), "l"(m), "r"(bar), "r"(c0), "r"(c1) : "memory");
}
__device__ __forceinline__ void tma_ld3(uint32_t dst, const CUtensorMap* m, uint32_t bar, int c0, int c1, int c2) {
  asm volatile("cp.async.bulk.tensor.3d.shared::cluster.global.mbarrier::complete_tx::bytes [%0], [%1, {%3, %4, %5}], [%2];"
               :: "r"(dst), "l"(m), "r"(bar), "r"(c0), "r"(c1), "r"(c2) : "memory");
}
__device__ __forceinline__ void tma_ld5_mc(uint32_t dst, const CUtensorMap* m, uint32_t bar, int c0, int c4) {
  asm volatile("cp.async.bulk.tensor.5d.shared::cluster.global.mbarrier::complete_tx::bytes.multicast::cluster [%0], [%1, {%3, %6, %6, %6, %4}], [%2], %5;"
               :: "r"(dst), "l"(m), "r"(bar), "r"(c0), "r"(c4), "h"((uint16_t)3), "r"(0) : "memory");
}
__device__ __forceinline__ void bulk_ld(uint32_t dst, const void* src, uint32_t bytes, uint32_t bar) {
  asm volatile("cp.async.bulk.shared::cluster.global.mbarrier::complete_tx::bytes [%0], [%1], %2, [%3];"
               :: "r"(dst), "l"(src), "r"(bytes), "r"(bar) : "memory");
}
__device__ __forceinline__ void bulk_ld_p(uint32_t dst, const void* src, uint32_t bytes, uint32_t bar, uint64_t pl) {
  asm volatile("cp.async.bulk.shared::cluster.global.mbarrier::complete_tx::bytes.L2::cache_hint [%0], [%1], %2, [%3], %4;"
               :: "r"(dst), "l"(src), "r"(bytes), "r"(bar), "l"(pl) : "memory");
}
__device__ __forceinline__ void bulk_ld_mc(uint32_t dst, const void* src, uint32_t bytes, uint32_t bar, uint64_t pl) {
  asm volatile("cp.async.bulk.shared::cluster.global.mbarrier::complete_tx::bytes.multicast::cluster.L2::cache_hint [%0], [%1], %2, [%3], %4, %5;"
               :: "r"(dst), "l"(src), "r"(bytes), "r"(bar), "h"((uint16_t)3), "l"(pl) : "memory");
}
__device__ __forceinline__ void tma_red2(const CUtensorMap* m, uint32_t src, int c0, int c1) {
  asm volatile("cp.reduce.async.bulk.tensor.2d.global.shared::cta.add.bulk_group [%0, {%2, %3}], [%1];"
               :: "l"(m), "r"(src), "r"(c0), "r"(c1) : "memory");
}
__device__ __forceinline__ void bulk_commit() { asm volatile("cp.async.bulk.commit_group;" ::: "memory"); }
__device__ __forceinline__ void bulk_wait_read() { asm volatile("cp.async.bulk.wait_group.read 0;" ::: "memory"); }
__device__ __forceinline__ void bulk_wait_all() { asm volatile("cp.async.bulk.wait_group 0;" ::: "memory"); }
__device__ __forceinline__ void prefetch_map(const CUtensorMap* m) { asm volatile("prefetch.tensormap [%0];" :: "l"(m) : "memory"); }
__device__ __forceinline__ void wg_fence() { asm volatile("wgmma.fence.sync.aligned;" ::: "memory"); }
__device__ __forceinline__ void wg_commit() { asm volatile("wgmma.commit_group.sync.aligned;" ::: "memory"); }
template <int N> __device__ __forceinline__ void wg_wait() { asm volatile("wgmma.wait_group.sync.aligned %0;" :: "n"(N) : "memory"); }
template <int N> __device__ __forceinline__ void reg_fence(float (&d)[N]) {
#pragma unroll
  for (int i = 0; i < N; i++) asm volatile("" : "+f"(d[i]) :: "memory");
}
template <int N> __device__ __forceinline__ void reg_fence(uint32_t (&d)[N]) {
#pragma unroll
  for (int i = 0; i < N; i++) asm volatile("" : "+r"(d[i]) :: "memory");
}
__device__ __forceinline__ uint32_t fresh_tid() { uint32_t t; asm volatile("mov.u32 %0, %%tid.x;" : "=r"(t)); return t; }
__device__ __forceinline__ uint32_t lane_base16() {
  const uint32_t t = fresh_tid(), lane = t & 31, wq = (t >> 5) & 3;
  return (16 * wq + (lane & 7) + 8 * ((lane >> 3) & 1)) * 128 + (((lane >> 4) ^ (lane & 7)) << 4);
}
__device__ __forceinline__ void cluster_arrive() { asm volatile("barrier.cluster.arrive.relaxed.aligned;" ::: "memory"); }
__device__ __forceinline__ void cluster_wait() { asm volatile("barrier.cluster.wait.acquire.aligned;" ::: "memory"); }
__device__ __forceinline__ void named_sync(int id, int n) { asm volatile("bar.sync %0, %1;" :: "r"(id), "r"(n) : "memory"); }
__device__ __forceinline__ void named_arrive(int id, int n) { asm volatile("bar.arrive %0, %1;" :: "r"(id), "r"(n) : "memory"); }
__device__ __forceinline__ uint32_t pack_bf16(float lo, float hi) {
  uint32_t r; asm("cvt.rn.bf16x2.f32 %0, %1, %2;" : "=r"(r) : "f"(hi), "f"(lo)); return r;
}
__device__ __forceinline__ float ex2(float x) { float y; asm("ex2.approx.ftz.f32 %0, %1;" : "=f"(y) : "f"(x)); return y; }
__device__ __forceinline__ void stsm4(uint32_t addr, uint32_t a, uint32_t b, uint32_t c, uint32_t d) {
  asm volatile("stmatrix.sync.aligned.m8n8.x4.shared.b16 [%0], {%1, %2, %3, %4};" :: "r"(addr), "r"(a), "r"(b), "r"(c), "r"(d) : "memory");
}
__device__ __forceinline__ uint64_t mk_desc(uint32_t addr, uint32_t lbo, uint32_t sbo) {
  return (uint64_t)(((addr & 0x3FFFF) >> 4) | ((lbo >> 4) << 16)) | ((uint64_t)((sbo >> 4) | (1u << 30)) << 32);
}
__device__ __forceinline__ uint64_t desc_k(uint32_t addr)  { return mk_desc(addr, 16, 1024); }
__device__ __forceinline__ uint64_t desc_mn(uint32_t addr) { return mk_desc(addr, 8192, 1024); }
__device__ __forceinline__ uint64_t desc_64(uint32_t addr) { return (uint64_t)(((addr & 0x3FFFF) >> 4) | ((4096u >> 4) << 16)) | ((uint64_t)((512u >> 4) | (2u << 30)) << 32); }
__device__ __forceinline__ uint64_t desc_add(uint64_t d, uint32_t bytes) { return d + (bytes >> 4); }

__device__ __forceinline__ void wgmma_ss_n256_tb(float (&d)[128], uint64_t da, uint64_t db, int sd) {
  asm volatile("{\n.reg .pred p;\nsetp.ne.b32 p, %130, 0;\n"
    "wgmma.mma_async.sync.aligned.m64n256k16.f32.bf16.bf16 "
    "{%0, %1, %2, %3, %4, %5, %6, %7, %8, %9, %10, %11, %12, %13, %14, %15, "
    "%16, %17, %18, %19, %20, %21, %22, %23, %24, %25, %26, %27, %28, %29, %30, %31, "
    "%32, %33, %34, %35, %36, %37, %38, %39, %40, %41, %42, %43, %44, %45, %46, %47, "
    "%48, %49, %50, %51, %52, %53, %54, %55, %56, %57, %58, %59, %60, %61, %62, %63, "
    "%64, %65, %66, %67, %68, %69, %70, %71, %72, %73, %74, %75, %76, %77, %78, %79, "
    "%80, %81, %82, %83, %84, %85, %86, %87, %88, %89, %90, %91, %92, %93, %94, %95, "
    "%96, %97, %98, %99, %100, %101, %102, %103, %104, %105, %106, %107, %108, %109, %110, %111, "
    "%112, %113, %114, %115, %116, %117, %118, %119, %120, %121, %122, %123, %124, %125, %126, %127}, "
    "%128, %129, p, 1, 1, 0, 1;\n}"
    : "+f"(d[0]), "+f"(d[1]), "+f"(d[2]), "+f"(d[3]), "+f"(d[4]), "+f"(d[5]), "+f"(d[6]), "+f"(d[7]),
      "+f"(d[8]), "+f"(d[9]), "+f"(d[10]), "+f"(d[11]), "+f"(d[12]), "+f"(d[13]), "+f"(d[14]), "+f"(d[15]),
      "+f"(d[16]), "+f"(d[17]), "+f"(d[18]), "+f"(d[19]), "+f"(d[20]), "+f"(d[21]), "+f"(d[22]), "+f"(d[23]),
      "+f"(d[24]), "+f"(d[25]), "+f"(d[26]), "+f"(d[27]), "+f"(d[28]), "+f"(d[29]), "+f"(d[30]), "+f"(d[31]),
      "+f"(d[32]), "+f"(d[33]), "+f"(d[34]), "+f"(d[35]), "+f"(d[36]), "+f"(d[37]), "+f"(d[38]), "+f"(d[39]),
      "+f"(d[40]), "+f"(d[41]), "+f"(d[42]), "+f"(d[43]), "+f"(d[44]), "+f"(d[45]), "+f"(d[46]), "+f"(d[47]),
      "+f"(d[48]), "+f"(d[49]), "+f"(d[50]), "+f"(d[51]), "+f"(d[52]), "+f"(d[53]), "+f"(d[54]), "+f"(d[55]),
      "+f"(d[56]), "+f"(d[57]), "+f"(d[58]), "+f"(d[59]), "+f"(d[60]), "+f"(d[61]), "+f"(d[62]), "+f"(d[63]),
      "+f"(d[64]), "+f"(d[65]), "+f"(d[66]), "+f"(d[67]), "+f"(d[68]), "+f"(d[69]), "+f"(d[70]), "+f"(d[71]),
      "+f"(d[72]), "+f"(d[73]), "+f"(d[74]), "+f"(d[75]), "+f"(d[76]), "+f"(d[77]), "+f"(d[78]), "+f"(d[79]),
      "+f"(d[80]), "+f"(d[81]), "+f"(d[82]), "+f"(d[83]), "+f"(d[84]), "+f"(d[85]), "+f"(d[86]), "+f"(d[87]),
      "+f"(d[88]), "+f"(d[89]), "+f"(d[90]), "+f"(d[91]), "+f"(d[92]), "+f"(d[93]), "+f"(d[94]), "+f"(d[95]),
      "+f"(d[96]), "+f"(d[97]), "+f"(d[98]), "+f"(d[99]), "+f"(d[100]), "+f"(d[101]), "+f"(d[102]), "+f"(d[103]),
      "+f"(d[104]), "+f"(d[105]), "+f"(d[106]), "+f"(d[107]), "+f"(d[108]), "+f"(d[109]), "+f"(d[110]), "+f"(d[111]),
      "+f"(d[112]), "+f"(d[113]), "+f"(d[114]), "+f"(d[115]), "+f"(d[116]), "+f"(d[117]), "+f"(d[118]), "+f"(d[119]),
      "+f"(d[120]), "+f"(d[121]), "+f"(d[122]), "+f"(d[123]), "+f"(d[124]), "+f"(d[125]), "+f"(d[126]), "+f"(d[127])
    : "l"(da), "l"(db), "r"(sd));
}
__device__ __forceinline__ void wgmma_ss_n64(float (&d)[32], uint64_t da, uint64_t db, int sd) {
  asm volatile("{\n.reg .pred p;\nsetp.ne.b32 p, %34, 0;\n"
    "wgmma.mma_async.sync.aligned.m64n64k16.f32.bf16.bf16 "
    "{%0, %1, %2, %3, %4, %5, %6, %7, %8, %9, %10, %11, %12, %13, %14, %15, "
    "%16, %17, %18, %19, %20, %21, %22, %23, %24, %25, %26, %27, %28, %29, %30, %31}, "
    "%32, %33, p, 1, 1, 0, 0;\n}"
    : "+f"(d[0]), "+f"(d[1]), "+f"(d[2]), "+f"(d[3]), "+f"(d[4]), "+f"(d[5]), "+f"(d[6]), "+f"(d[7]),
      "+f"(d[8]), "+f"(d[9]), "+f"(d[10]), "+f"(d[11]), "+f"(d[12]), "+f"(d[13]), "+f"(d[14]), "+f"(d[15]),
      "+f"(d[16]), "+f"(d[17]), "+f"(d[18]), "+f"(d[19]), "+f"(d[20]), "+f"(d[21]), "+f"(d[22]), "+f"(d[23]),
      "+f"(d[24]), "+f"(d[25]), "+f"(d[26]), "+f"(d[27]), "+f"(d[28]), "+f"(d[29]), "+f"(d[30]), "+f"(d[31])
    : "l"(da), "l"(db), "r"(sd));
}
__device__ __forceinline__ void wgmma_rs_n256_tb(float (&d)[128], uint32_t a0, uint32_t a1, uint32_t a2, uint32_t a3, uint64_t db, int sd) {
  asm volatile("{\n.reg .pred p;\nsetp.ne.b32 p, %133, 0;\n"
    "wgmma.mma_async.sync.aligned.m64n256k16.f32.bf16.bf16 "
    "{%0, %1, %2, %3, %4, %5, %6, %7, %8, %9, %10, %11, %12, %13, %14, %15, "
    "%16, %17, %18, %19, %20, %21, %22, %23, %24, %25, %26, %27, %28, %29, %30, %31, "
    "%32, %33, %34, %35, %36, %37, %38, %39, %40, %41, %42, %43, %44, %45, %46, %47, "
    "%48, %49, %50, %51, %52, %53, %54, %55, %56, %57, %58, %59, %60, %61, %62, %63, "
    "%64, %65, %66, %67, %68, %69, %70, %71, %72, %73, %74, %75, %76, %77, %78, %79, "
    "%80, %81, %82, %83, %84, %85, %86, %87, %88, %89, %90, %91, %92, %93, %94, %95, "
    "%96, %97, %98, %99, %100, %101, %102, %103, %104, %105, %106, %107, %108, %109, %110, %111, "
    "%112, %113, %114, %115, %116, %117, %118, %119, %120, %121, %122, %123, %124, %125, %126, %127}, "
    "{%128, %129, %130, %131}, %132, p, 1, 1, 1;\n}"
    : "+f"(d[0]), "+f"(d[1]), "+f"(d[2]), "+f"(d[3]), "+f"(d[4]), "+f"(d[5]), "+f"(d[6]), "+f"(d[7]),
      "+f"(d[8]), "+f"(d[9]), "+f"(d[10]), "+f"(d[11]), "+f"(d[12]), "+f"(d[13]), "+f"(d[14]), "+f"(d[15]),
      "+f"(d[16]), "+f"(d[17]), "+f"(d[18]), "+f"(d[19]), "+f"(d[20]), "+f"(d[21]), "+f"(d[22]), "+f"(d[23]),
      "+f"(d[24]), "+f"(d[25]), "+f"(d[26]), "+f"(d[27]), "+f"(d[28]), "+f"(d[29]), "+f"(d[30]), "+f"(d[31]),
      "+f"(d[32]), "+f"(d[33]), "+f"(d[34]), "+f"(d[35]), "+f"(d[36]), "+f"(d[37]), "+f"(d[38]), "+f"(d[39]),
      "+f"(d[40]), "+f"(d[41]), "+f"(d[42]), "+f"(d[43]), "+f"(d[44]), "+f"(d[45]), "+f"(d[46]), "+f"(d[47]),
      "+f"(d[48]), "+f"(d[49]), "+f"(d[50]), "+f"(d[51]), "+f"(d[52]), "+f"(d[53]), "+f"(d[54]), "+f"(d[55]),
      "+f"(d[56]), "+f"(d[57]), "+f"(d[58]), "+f"(d[59]), "+f"(d[60]), "+f"(d[61]), "+f"(d[62]), "+f"(d[63]),
      "+f"(d[64]), "+f"(d[65]), "+f"(d[66]), "+f"(d[67]), "+f"(d[68]), "+f"(d[69]), "+f"(d[70]), "+f"(d[71]),
      "+f"(d[72]), "+f"(d[73]), "+f"(d[74]), "+f"(d[75]), "+f"(d[76]), "+f"(d[77]), "+f"(d[78]), "+f"(d[79]),
      "+f"(d[80]), "+f"(d[81]), "+f"(d[82]), "+f"(d[83]), "+f"(d[84]), "+f"(d[85]), "+f"(d[86]), "+f"(d[87]),
      "+f"(d[88]), "+f"(d[89]), "+f"(d[90]), "+f"(d[91]), "+f"(d[92]), "+f"(d[93]), "+f"(d[94]), "+f"(d[95]),
      "+f"(d[96]), "+f"(d[97]), "+f"(d[98]), "+f"(d[99]), "+f"(d[100]), "+f"(d[101]), "+f"(d[102]), "+f"(d[103]),
      "+f"(d[104]), "+f"(d[105]), "+f"(d[106]), "+f"(d[107]), "+f"(d[108]), "+f"(d[109]), "+f"(d[110]), "+f"(d[111]),
      "+f"(d[112]), "+f"(d[113]), "+f"(d[114]), "+f"(d[115]), "+f"(d[116]), "+f"(d[117]), "+f"(d[118]), "+f"(d[119]),
      "+f"(d[120]), "+f"(d[121]), "+f"(d[122]), "+f"(d[123]), "+f"(d[124]), "+f"(d[125]), "+f"(d[126]), "+f"(d[127])
    : "r"(a0), "r"(a1), "r"(a2), "r"(a3), "l"(db), "r"(sd));
}
__device__ __forceinline__ void wgmma_rs_n64_tb(float (&d)[32], uint32_t a0, uint32_t a1, uint32_t a2, uint32_t a3, uint64_t db, int sd) {
  asm volatile("{\n.reg .pred p;\nsetp.ne.b32 p, %37, 0;\n"
    "wgmma.mma_async.sync.aligned.m64n64k16.f32.bf16.bf16 "
    "{%0, %1, %2, %3, %4, %5, %6, %7, %8, %9, %10, %11, %12, %13, %14, %15, "
    "%16, %17, %18, %19, %20, %21, %22, %23, %24, %25, %26, %27, %28, %29, %30, %31}, "
    "{%32, %33, %34, %35}, %36, p, 1, 1, 1;\n}"
    : "+f"(d[0]), "+f"(d[1]), "+f"(d[2]), "+f"(d[3]), "+f"(d[4]), "+f"(d[5]), "+f"(d[6]), "+f"(d[7]),
      "+f"(d[8]), "+f"(d[9]), "+f"(d[10]), "+f"(d[11]), "+f"(d[12]), "+f"(d[13]), "+f"(d[14]), "+f"(d[15]),
      "+f"(d[16]), "+f"(d[17]), "+f"(d[18]), "+f"(d[19]), "+f"(d[20]), "+f"(d[21]), "+f"(d[22]), "+f"(d[23]),
      "+f"(d[24]), "+f"(d[25]), "+f"(d[26]), "+f"(d[27]), "+f"(d[28]), "+f"(d[29]), "+f"(d[30]), "+f"(d[31])
    : "r"(a0), "r"(a1), "r"(a2), "r"(a3), "l"(db), "r"(sd));
}
__device__ __forceinline__ void wgmma_rs_n32(float (&d)[16], uint32_t a0, uint32_t a1, uint32_t a2, uint32_t a3, uint64_t db, int sd) {
  asm volatile("{\n.reg .pred p;\nsetp.ne.b32 p, %21, 0;\n"
    "wgmma.mma_async.sync.aligned.m64n32k16.f32.bf16.bf16 "
    "{%0, %1, %2, %3, %4, %5, %6, %7, %8, %9, %10, %11, %12, %13, %14, %15}, "
    "{%16, %17, %18, %19}, %20, p, 1, 1, 0;\n}"
    : "+f"(d[0]), "+f"(d[1]), "+f"(d[2]), "+f"(d[3]), "+f"(d[4]), "+f"(d[5]), "+f"(d[6]), "+f"(d[7]),
      "+f"(d[8]), "+f"(d[9]), "+f"(d[10]), "+f"(d[11]), "+f"(d[12]), "+f"(d[13]), "+f"(d[14]), "+f"(d[15])
    : "r"(a0), "r"(a1), "r"(a2), "r"(a3), "l"(db), "r"(sd));
}

__device__ __forceinline__ void sts16(uint32_t a, uint32_t x, uint32_t y, uint32_t z, uint32_t w) {
  asm volatile("st.shared.v4.u32 [%0], {%1, %2, %3, %4};" :: "r"(a), "r"(x), "r"(y), "r"(z), "r"(w) : "memory");
}
__device__ __forceinline__ uint32_t lds4(uint32_t a) { uint32_t v; asm volatile("ld.shared.u32 %0, [%1];" : "=r"(v) : "r"(a) : "memory"); return v; }
__device__ __forceinline__ uint32_t bmul(uint32_t a, uint32_t b) { uint32_t r; asm("mul.rn.bf16x2 %0, %1, %2;" : "=r"(r) : "r"(a), "r"(b)); return r; }
__device__ __forceinline__ uint32_t badd(uint32_t a, uint32_t b) { uint32_t r; asm("add.rn.bf16x2 %0, %1, %2;" : "=r"(r) : "r"(a), "r"(b)); return r; }

#define SIDE_AHEAD 3
#define ZERO_RD 4
constexpr int EARLY_LD = 4;
constexpr int PP_BAR = 3;
template <int V> struct Int { static constexpr int value = V; };
struct Ring {
  uint32_t slot, phase;
  __device__ __forceinline__ void next() { if (++slot == NSLOT) { slot = 0; phase ^= 1; } }
};
__device__ __forceinline__ uint32_t bar_addr(uint32_t sb, uint32_t i) { return sb + BARS + 8 * i; }

__device__ __forceinline__ int kv_group(int g, int t) { return (g & 6) | (t & 1); }
__device__ __forceinline__ int kv_rows(int g, int t) { return (t & 14) | (g & 1); }
__device__ __forceinline__ void load_w(const Params& p, int g, int t, int it, uint32_t dst, uint32_t full) {
  if (it < 64) tma_ld3(dst, (it & 16) ? &p.wuv : &p.wuk, full, 0, (it & 15) * 64, (kv_group(g, t) + (it < 32 ? 8 : 0)) * 4);
  else tma_ld3(dst, &p.wq, full, 0, (it < 71 ? it - 64 : it - 71) * 64, (it < 71 ? g + 8 : g) * 4);
}
__device__ __forceinline__ void load_a(const Params& p, int g, int t, int it, uint32_t dst, uint32_t full) {
  if (it < 64) tma_ld2(dst, &p.ckv, full, (it & 15) * 64, kv_rows(g, t) * 128);
  else tma_ld2(dst, &p.x, full, (it < 71 ? it - 64 : it - 71) * 64, (it < 71 ? 15 - t : t) * 128);
}

__device__ __forceinline__ void producer_main(const Params& p, uint32_t sb, int g, int t) {
  const int rank = t & 1;
  Ring r{EARLY_LD, 0};
  auto wait_slot = [&]() { mbar_wait(bar_addr(sb, B_EMPTY + r.slot), r.phase ^ 1); };
  uint32_t prev = 0;
#pragma unroll 1
  for (int it = EARLY_LD; it < P1_STEPS; it++) {
    wait_slot();
    if (it > EARLY_LD && it <= P1_XS) load_a(p, g, t, it - 1, sb + QREG + ((it - 1) & 3) * 16384, prev);
    const uint32_t full = bar_addr(sb, B_FULL + r.slot);
    mbar_expect_tx(full, it < P1_XS ? 49152 : 32768);
    load_w(p, g, t, it, sb + r.slot * SLOT, full);
    prev = full;
    r.next();
    if (it == P1_XS) {
      wait_slot();
      const uint32_t f2 = bar_addr(sb, B_FULL + r.slot);
      mbar_expect_tx(f2, 32768);
      load_a(p, g, t, P1_XS, sb + r.slot * SLOT, f2);
      load_a(p, g, t, P1_XS + 1, sb + r.slot * SLOT + 16384, f2);
      r.next();
    }
  }
  uint64_t once;
  asm volatile("createpolicy.fractional.L2::evict_first.b64 %0, 1.0;" : "=l"(once));
  const int na = 2 * t + 2, own = 2 * (t & ~1) + 2;
  mbar_wait(bar_addr(sb, B_KVOK), 0);
#pragma unroll 1
  for (int f = 0; f < 68; f++) {
    const bool isK = (f == 0) || ((f & 1) && f < 67);
    const int i = isK ? (f + 1) >> 1 : (f - 1) >> 1;
    wait_slot();
    const uint32_t full = bar_addr(sb, B_FULL + r.slot);
    mbar_expect_tx(full, 32768);
    const uint32_t src = (uint32_t)(((isK ? 0 : NH) + g) * 32 + (i >= na ? 8 * 32 + 33 - i : i)) * 32768;
    if ((i & ~1) != own) bulk_ld_mc(sb + r.slot * SLOT + rank * 16384, at<uint8_t>(g_kv, src + rank * 16384), 16384, full, once);
    else bulk_ld_p(sb + r.slot * SLOT, at<uint8_t>(g_kv, src), 32768, full, once);
    r.next();
  }
#pragma unroll 1
  for (int f = 0; f < 14; f++) {
    const int ch = f < 4 ? f & 1 : f >> 1, par = f < 4 ? f >> 1 : f & 1;
    wait_slot();
    const uint32_t full = bar_addr(sb, B_FULL + r.slot);
    mbar_expect_tx(full, 32768);
    tma_ld5_mc(sb + r.slot * SLOT + rank * 16384, &p.wo, full, ch * 64, (par ? g : g + 8) * 8 + rank * 4);
    r.next();
  }
}

__device__ __forceinline__ void helper_main(const Params& p, uint32_t sb, int g, int t, int w) {
  const unsigned epoch = load_epoch();
  const uint32_t qreg = sb + QREG + w * 32768, qfull = bar_addr(sb, B_QFULL + w);
  mbar_wait(bar_addr(sb, B_ST_KV + w), 0);
  flag_signal(flag_at(g_flags.kv_ready, kv_group(g, t)));
  if (w == 0) {
    flag_wait<20>(flag_at(g_flags.kv_ready, g), 32, epoch);
    fence_async_global();
    mbar_arrive(bar_addr(sb, B_KVOK));
  }
  mbar_wait(bar_addr(sb, B_ST_Q + w), 0);
  asm volatile("fence.release.gpu;" ::: "memory");
  fence_async_global();
  mbar_wait(bar_addr(sb, B_QFREE + w), 0);
  mbar_expect_tx(qfull, 32768);
  bulk_ld(qreg, at<uint8_t>(g_qc, ((g * 16 + t) * 2 + w) * 32768), 32768, qfull);
  auto publish = [&]() { mbar_wait(bar_addr(sb, B_ST_CTX + w), 0); flag_signal(flag_at(g_flags.ctx_ready, (g * 16 + t) * 2 + w)); };
  if (t < 8) publish();
  flag_wait<20>(flag_at(g_flags.ctx_ready, (g * 16 + 15 - t) * 2 + (w ^ 1)), 1, epoch);
  mbar_arrive(bar_addr(sb, B_CTXOK + w));
  mbar_arrive(bar_addr(sb, B_DONE));
  if (t >= 8) publish();
  flag_wait<20>(flag_at(g_flags.zero_ready, 15 - t), 8, epoch);
  fence_async_global();
#pragma unroll 1
  for (int ch = 0; ch < 6; ch++) {
    mbar_wait(bar_addr(sb, B_S2_FULL + w * 4 + (ch & 3)), ch >> 2);
    tma_red2(&p.o, qreg + (ch & 3) * 8192, DA + ch * 64, (15 - t) * 128 + (w ^ 1) * 64);
    bulk_commit();
    if (ch < 3) { bulk_wait_read(); mbar_arrive(bar_addr(sb, B_S2_EMPTY + w * 4 + ch)); }
  }
  bulk_wait_read();
  GT(48 + w);
}

__device__ __forceinline__ void store_block(uint32_t base, uint32_t lanebase, const uint32_t (&pk)[16]) {
#pragma unroll
  for (int J = 0; J < 8; J += 2) stsm4(base + (lanebase ^ (J << 4)), pk[2 * J], pk[2 * J + 1], pk[2 * J + 2], pk[2 * J + 3]);
}
__device__ __forceinline__ void pack_chunks(uint32_t (&pk)[64], const float (&acc)[128]) {
#pragma unroll
  for (int i = 0; i < 64; i++) { const int e = 16 * (i >> 3) + 4 * (i & 3) + 2 * ((i >> 2) & 1); pk[i] = pack_bf16(acc[e], acc[e + 1]); }
}
__device__ __forceinline__ uint32_t chunk_off() { const uint32_t t = fresh_tid(); return (t & 96) * 32 + (t & 28) * 16 + (((t ^ (t >> 3)) & 3) << 4); }
__device__ __forceinline__ void warp_arrive(uint32_t bar, int lane) { __syncwarp(); if (lane == 0) mbar_arrive(bar); }

__device__ __forceinline__ void consumer_main(const Params& p, uint32_t sb, int g, int t, int w, int wq) {
  const int lane = threadIdx.x & 31;
  const int rank = t & 1;

  auto turn_begin = [&]() { named_sync(PP_BAR + w, 256); };
  auto turn_end = [&]() { named_arrive(PP_BAR + (w ^ 1), 256); };
  Ring r{0, 0};
  auto take = [&](uint32_t ready = 0) { const uint32_t sl = r.slot; mbar_wait_unless(ready, bar_addr(sb, B_FULL + sl), r.phase); r.next(); return sl; };
  uint32_t rdy0 = 0, rdy1 = 0;
  auto peek2 = [&]() { Ring q = r; rdy0 = mbar_test(bar_addr(sb, B_FULL + q.slot), q.phase); q.next(); rdy1 = mbar_test(bar_addr(sb, B_FULL + q.slot), q.phase); };
  auto give = [&](uint32_t sl) { if (lane < 2) mbar_arrive_remote(bar_addr(sb, B_EMPTY + sl), rank ^ lane); };
  float acc[128];
#pragma unroll
  for (int i = 0; i < 128; i++) acc[i] = 0.f;
  uint32_t pk[64];
#pragma unroll
  for (int i = 0; i < 64; i++) pk[i] = 0;
  reg_fence(acc);
  reg_fence(pk);
  cluster_wait();
  TS(0);
  const uint32_t qreg = sb + QREG + w * 32768;
  {
    uint32_t xs = 0;
    uint4* row = nullptr;
    int it = 0;
#pragma unroll 1
    for (int tile = 0; tile < 6; tile++) {
      const bool isq = tile >= 4;
      const uint32_t abase = sb + QREG + (w ^ (tile == 4)) * 8192;
#pragma unroll 1
      for (int u = 0; u < (isq ? 4 : 8); u++) {
        const bool two = !(isq && u == 1), last = it == P1_XS;
        const uint32_t w0 = take(rdy0);
        TSC(1, it == 0);
        if (last) { xs = take(rdy1); rdy1 = 0; }
        const uint32_t xb = sb + xs * SLOT + w * 8192;
        const uint64_t da = desc_k(last ? xb : abase + (it & 3) * 16384), db = desc_mn(sb + w0 * SLOT);
        turn_begin();
        wg_fence();
#pragma unroll
        for (int kk = 0; kk < 4; kk++) wgmma_ss_n256_tb(acc, desc_add(da, kk * 32), desc_add(db, kk * 2048), (u | kk) != 0);
        wg_commit();
        uint32_t w1 = w0;
        if (two) {
          w1 = take(rdy1);
          const uint64_t da1 = desc_k(last ? xb + 16384 : abase + ((it + 1) & 3) * 16384), db1 = desc_mn(sb + w1 * SLOT);
          wg_fence();
#pragma unroll
          for (int kk = 0; kk < 4; kk++) wgmma_ss_n256_tb(acc, desc_add(da1, kk * 32), desc_add(db1, kk * 2048), 1);
          wg_commit();
          turn_end();
          wg_wait<1>();
          give(w0);
        } else {
          turn_end();
        }
        if (tile > 0) {
          uint32_t m = isq ? 0xC0380403u >> (8 * u) : 1u << u;
          asm volatile("" : "+r"(m));
#pragma unroll
          for (int i = 0; i < 16; i++)
            if (m & (1u << (i >> 1))) row[(i >> 1) * 256 + (i & 1) * 32] = make_uint4(pk[4 * i], pk[4 * i + 1], pk[4 * i + 2], pk[4 * i + 3]);
        }
        peek2();
        wg_wait<0>();
        give(w1);
        it += 1 + two;
      }
      reg_fence(acc);
      if (isq) warp_arrive(bar_addr(sb, (tile == 4 ? B_ST_KV : B_ST_Q) + w), lane);
      pack_chunks(pk, acc);
      row = at<uint4>(isq ? (const void*)g_qc : (const void*)g_kv, chunk_off() +
                      (uint32_t)(isq ? (g * 16 + t) * 2 + w : ((tile & 1) * NH + kv_group(g, t) + (tile < 2 ? 8 : 0)) * 32 + kv_rows(g, t) * 2 + w) * 32768);
      TS(2 + tile);
    }
    give(xs);
    const uint32_t qa = qreg + chunk_off();
#pragma unroll
    for (int i = 0; i < 16; i++) sts16(qa + (i >> 1) * 4096 + (i & 1) * 512, pk[4 * i], pk[4 * i + 1], pk[4 * i + 2], pk[4 * i + 3]);
    fence_async_smem();
  }
  TS(8);

  constexpr float SC = 0.0625f * 1.4426950408889634f;
#pragma unroll 1
  for (int which = 0; which < 2; which++) {
    float s[32];
#pragma unroll
    for (int i = 0; i < 32; i++) s[i] = 0.f;
    uint32_t pa[16], pb[16];
    float m0 = 0.f, m1 = 0.f, l0 = 0.f, l1 = 0.f;
    const uint64_t dq = desc_64(qreg);
    uint64_t dk = 0, dqq = 0, dv = 0;
    auto prep_qk = [&](uint32_t kaddr) { dk = desc_64(kaddr); dqq = dq + (kaddr >> 31); asm volatile("" : "+l"(dk), "+l"(dqq)); };
    auto prep_pv = [&](uint32_t vaddr) { dv = desc_64(vaddr); asm volatile("" : "+l"(dv)); };
    auto issue_qk = [&]() {
#pragma unroll
      for (int kk = 0; kk < 16; kk++)
        wgmma_ss_n64(s, desc_add(dqq, (kk >> 1) * 4096 + (kk & 1) * 32), desc_add(dk, (kk >> 1) * 4096 + (kk & 1) * 32), kk != 0);
    };
    auto issue_pv = [&](int accumulate) {
#pragma unroll
      for (int kk = 0; kk < 4; kk++)
        wgmma_rs_n256_tb(acc, pa[4 * kk], pa[4 * kk + 1], pa[4 * kk + 2], pa[4 * kk + 3], desc_add(dv, kk * 1024), accumulate | kk);
    };
    auto mask_diag = [&]() {
      const int d = 16 * wq + (lane >> 2) - 2 * (lane & 3);
#pragma unroll
      for (int jj = 0; jj < 8; jj++) {
        if (8 * jj > d)     { s[4 * jj] = -INFINITY;     if (jj < 7) s[4 * jj + 6] = -INFINITY; }
        if (8 * jj + 1 > d) { s[4 * jj + 1] = -INFINITY; if (jj < 7) s[4 * jj + 7] = -INFINITY; }
      }
    };
    float a0, a1;
    auto softmax = [&]() -> bool {
      float x0 = fmaxf(s[0], s[1]), x1 = fmaxf(s[2], s[3]);
#pragma unroll
      for (int jj = 1; jj < 8; jj++) {
        x0 = fmaxf(x0, fmaxf(s[4 * jj], s[4 * jj + 1]));
        x1 = fmaxf(x1, fmaxf(s[4 * jj + 2], s[4 * jj + 3]));
      }
      x0 = fmaxf(x0, __shfl_xor_sync(0xffffffffu, x0, 1));
      x1 = fmaxf(x1, __shfl_xor_sync(0xffffffffu, x1, 1));
      x0 = fmaxf(x0, __shfl_xor_sync(0xffffffffu, x0, 2));
      x1 = fmaxf(x1, __shfl_xor_sync(0xffffffffu, x1, 2));
      const bool grow = __any_sync(0xffffffffu, fmaxf(x0 - m0, x1 - m1) * SC > 8.f);
      if (grow) {
        x0 = fmaxf(x0, m0); x1 = fmaxf(x1, m1);
        a0 = ex2((m0 - x0) * SC); a1 = ex2((m1 - x1) * SC);
        m0 = x0; m1 = x1;
        l0 *= a0; l1 *= a1;
      }
      const float b0 = -m0 * SC, b1 = -m1 * SC;
      float t0 = 0.f, t1 = 0.f, t2 = 0.f, t3 = 0.f;
#pragma unroll
      for (int jj = 0; jj < 8; jj++) {
        s[4 * jj]     = ex2(fmaf(s[4 * jj], SC, b0));
        s[4 * jj + 1] = ex2(fmaf(s[4 * jj + 1], SC, b0));
        s[4 * jj + 2] = ex2(fmaf(s[4 * jj + 2], SC, b1));
        s[4 * jj + 3] = ex2(fmaf(s[4 * jj + 3], SC, b1));
        t0 += s[4 * jj]; t1 += s[4 * jj + 1]; t2 += s[4 * jj + 2]; t3 += s[4 * jj + 3];
      }
      l0 += t0 + t1; l1 += t2 + t3;
      return grow;
    };
    auto softmax_fast = [&](uint32_t (&pp)[16], auto first, auto hook) -> bool {
      const float b0 = -m0 * SC, b1 = -m1 * SC;
      float t0 = 0.f, t1 = 0.f, t2 = 0.f, t3 = 0.f;
#pragma unroll
      for (int jj = 0; jj < 8; jj++) {
        const float e0 = ex2(fmaf(s[4 * jj], SC, b0)), e1 = ex2(fmaf(s[4 * jj + 1], SC, b0));
        const float e2 = ex2(fmaf(s[4 * jj + 2], SC, b1)), e3 = ex2(fmaf(s[4 * jj + 3], SC, b1));
        hook(jj, e0);
        pp[2 * jj] = pack_bf16(e0, e1); pp[2 * jj + 1] = pack_bf16(e2, e3);
        if (jj == 0) { t0 = e0; t1 = e1; t2 = e2; t3 = e3; } else { t0 += e0; t1 += e1; t2 += e2; t3 += e3; }
      }
      t0 += t1; t2 += t3;
      bool redo = __any_sync(0xffffffffu, !(t0 + t2 <= 16777216.f));
      if (decltype(first)::value) {
        uint32_t u0 = __ballot_sync(0xffffffffu, t0 >= 1.52587890625e-05f), u1 = __ballot_sync(0xffffffffu, t2 >= 1.52587890625e-05f);
        u0 |= u0 >> 1; u1 |= u1 >> 1;
        redo |= (((u0 | (u0 >> 2)) & (u1 | (u1 >> 2))) & 0x11111111u) != 0x11111111u;
      }
      if (!redo) { l0 += t0; l1 += t2; }
      return redo;
    };
    auto rescale = [&]() {
#pragma unroll
      for (int i = 0; i < 32; i++) { acc[4 * i] *= a0; acc[4 * i + 1] *= a0; acc[4 * i + 2] *= a1; acc[4 * i + 3] *= a1; }
    };
    auto to_p = [&](uint32_t (&pp)[16]) {
#pragma unroll
      for (int i = 0; i < 16; i++) pp[i] = pack_bf16(s[2 * i], s[2 * i + 1]);
    };
    auto q_free = [&]() { if (lane == 0) mbar_arrive(bar_addr(sb, B_QFREE + w)); };

    const int n = 2 * (which ? 15 - t : t) + 1 + (w ^ which);
    uint32_t ks = take(rdy0);
    TS(9 + 5 * which);
    prep_qk(sb + ks * SLOT);
    turn_begin();
    TS(20 + 10 * which);
    wg_fence();
    issue_qk();
    wg_commit();
    turn_end();
    if (which == 1) give(take(rdy1));
    TS(22 + 10 * which);
    wg_wait<0>();
    TS(21 + 10 * which);
    reg_fence(s);
    give(ks);
    if (which == 0 && n == 1) q_free();
    if (which == 1 || n == 1) mask_diag();
    {
      const uint4* dst = at<uint4>(g_qc, (uint32_t)((g * 16 + t) * 2 + w) * 32768 + (fresh_tid() & 127) * 16);
      const bool redo = softmax_fast(pa, Int<1>(), [&](int jj, float e) {
        if (jj == 7) peek2();
        const int i = 8 + jj;
        asm volatile("{\n.reg .pred p, q;\nsetp.ne.b32 q, %6, 0;\nsetp.geu.and.f32 p, %5, 0fBF800000, q;\n@p st.global.v4.u32 [%0], {%1, %2, %3, %4};\n}"
                       :: "l"(dst + i * 128), "r"(pk[4 * i]), "r"(pk[4 * i + 1]), "r"(pk[4 * i + 2]), "r"(pk[4 * i + 3]), "f"(e), "r"(which) : "memory");
      });
      if (redo) {
        m0 = -INFINITY; m1 = -INFINITY;
        softmax();
        to_p(pa);
      }
    }
    if (which == 1) warp_arrive(bar_addr(sb, B_ST_CTX + w), lane);
    TS(10 + 5 * which);
#pragma unroll 1
    for (int jj = 1; jj < n; jj++) {
      ks = take(rdy0);
      const uint32_t vs = take(rdy1);
      prep_qk(sb + ks * SLOT);
      prep_pv(sb + vs * SLOT);
      TSC(23 + 10 * which, jj == 1);
      turn_begin();
      TSC(24 + 10 * which, jj == 1);
      TSC(26 + 10 * which, jj == n - 1);
      wg_fence();
      issue_qk();
      wg_commit();
      issue_pv(jj > 1);
      wg_commit();
      turn_end();
      wg_wait<1>();
      TSC(25 + 10 * which, jj == 1);
      reg_fence(s);
      give(ks);
      if (jj == n - 1 && which == 0) { q_free(); mask_diag(); }
      if (softmax_fast(pb, Int<0>(), [](int, float) {})) {
        wg_wait<0>();
        reg_fence(acc);
        if (softmax()) rescale();
        to_p(pb);
      }
      peek2();
      wg_wait<0>();
      reg_fence(acc);
      reg_fence(pa);
      give(vs);
#pragma unroll
      for (int i = 0; i < 16; i++) pa[i] = pb[i] | (vs >> 8);
    }
    TS(11 + 5 * which);
    if (which == 0) { give(take(rdy0)); rdy0 = rdy1; }
    {
      const uint32_t vs = take(rdy0);
      prep_pv(sb + vs * SLOT);
      TS(27 + 10 * which);
      turn_begin();
      TS(28 + 10 * which);
      wg_fence();
      issue_pv(n > 1);
      wg_commit();
      turn_end();
      l0 += __shfl_xor_sync(0xffffffffu, l0, 1); l1 += __shfl_xor_sync(0xffffffffu, l1, 1);
      l0 += __shfl_xor_sync(0xffffffffu, l0, 2); l1 += __shfl_xor_sync(0xffffffffu, l1, 2);
      asm("rcp.approx.ftz.f32 %0, %0;" : "+f"(l0));
      asm("rcp.approx.ftz.f32 %0, %0;" : "+f"(l1));
      peek2();
      if (which == 0) mbar_wait(bar_addr(sb, B_QFULL + w), 0);
      wg_wait<0>();
      reg_fence(acc);
      reg_fence(pa);
      give(vs);
    }
    TS(12 + 5 * which);
    {
      const uint4* dst = at<uint4>(g_qc, (uint32_t)((g * 16 + t) * 2 + w) * 32768 + (fresh_tid() & 127) * 16);
#pragma unroll
      for (int i = 0; i < 16; i++) {
        const int c = (i & 1) ? (i >> 1) + 8 : i >> 1;
        pk[4 * c]     = pack_bf16(acc[8 * c] * l0, acc[8 * c + 1] * l0);
        pk[4 * c + 1] = pack_bf16(acc[8 * c + 2] * l1, acc[8 * c + 3] * l1);
        pk[4 * c + 2] = pack_bf16(acc[8 * c + 4] * l0, acc[8 * c + 5] * l0);
        pk[4 * c + 3] = pack_bf16(acc[8 * c + 6] * l1, acc[8 * c + 7] * l1);
        if (c < 8)
          asm volatile("{\n.reg .pred p;\nsetp.eq.b32 p, %5, 0;\n@p st.global.v4.u32 [%0], {%1, %2, %3, %4};\n}"
                       :: "l"(dst + c * 128), "r"(pk[4 * c]), "r"(pk[4 * c + 1]), "r"(pk[4 * c + 2]), "r"(pk[4 * c + 3]), "r"(which) : "memory");
      }
    }
    TS(13 + 5 * which);
  }

  {
    float oa[32], ob[32];
#pragma unroll
    for (int i = 0; i < 32; i++) { oa[i] = 0.f; ob[i] = 0.f; }
    uint32_t pk2[64];
    auto stage = [&](float (&o)[32], int ch) {
      reg_fence(o);
      uint32_t q[16];
#pragma unroll
      for (int i = 0; i < 16; i++) q[i] = pack_bf16(o[2 * i], o[2 * i + 1]);
      if (ch >= 4) mbar_wait(bar_addr(sb, B_S2_EMPTY + w * 4 + (ch & 3)), 0);
      store_block(qreg + (ch & 3) * 8192, lane_base16(), q);
    };
    auto hand_over = [&](int ch) {
      fence_async_smem();
      warp_arrive(bar_addr(sb, B_S2_FULL + w * 4 + (ch & 3)), lane);
    };
    uint32_t prev = 0;
    auto half = [&](int f, float (&o)[32], uint32_t (&a)[64], int accumulate) {
      const uint32_t sl = take(rdy0);
      const uint64_t d = desc_mn(sb + sl * SLOT);
      turn_begin();
      TS(40 + f);
      wg_fence();
#pragma unroll
      for (int kk = 0; kk < 16; kk++) {
        wgmma_rs_n64_tb(o, a[4 * kk], a[4 * kk + 1], a[4 * kk + 2], a[4 * kk + 3], desc_add(d, kk * 2048), accumulate | kk);
        if (kk == 12 && (f < 13 || w == 0)) turn_end();
      }
      wg_commit();
      if (f < 13) rdy0 = mbar_test(bar_addr(sb, B_FULL + r.slot), r.phase);
      wg_wait<1>();
      if (f >= 1 && f <= 9) give(prev);
      prev = sl;
    };
    auto load_ctx = [&](auto h0) {
      constexpr int I0 = decltype(h0)::value * 8, NL = 8;
      const uint4* src = at<const uint4>(g_qc, (uint32_t)((g * 16 + 15 - t) * 2 + (w ^ 1)) * 32768 + (fresh_tid() & 127) * 16);
#pragma unroll
      for (int i = I0; i < I0 + NL; i++) { const uint4 v = __ldcg(src + i * 128); pk2[4 * i] = v.x; pk2[4 * i + 1] = v.y; pk2[4 * i + 2] = v.z; pk2[4 * i + 3] = v.w; }
    };
    half(0, oa, pk, 0);
    mbar_wait(bar_addr(sb, B_CTXOK + w), 0);
    load_ctx(Int<0>());
    half(1, ob, pk, 0);
    load_ctx(Int<1>());
    half(2, oa, pk2, 1);
#pragma unroll 1
    for (int i = 0; i < 3; i++) {
      half(4 * i + 3, ob, pk2, 1);
      if (i == 0) stage(oa, 0);
      half(4 * i + 4, oa, pk, 0);
      if (i == 0) hand_over(0);
      stage(ob, 2 * i + 1);
      hand_over(2 * i + 1);
      half(4 * i + 5, oa, pk2, 1);
      if (i == 2) break;
      half(4 * i + 6, ob, pk, 0);
      stage(oa, 2 * i + 2);
      hand_over(2 * i + 2);
    }
    wg_wait<0>();
    reg_fence(pk);
    reg_fence(pk2);
    stage(oa, 6);
    fence_async_smem();
    named_sync(1 + w, 128);
    if (wq == 0 && lane == 0) {
      tma_red2(&p.o, qreg + 2 * 8192, DA + 6 * 64, (15 - t) * 128 + (w ^ 1) * 64);
      bulk_commit();
      bulk_wait_read();
    }
  }
  TS(19);
  TDUMP();
}

namespace ssm {
constexpr int NCH = DA / NCONV;
constexpr int NS = 8, NP = 6;
constexpr uint32_t X0 = 384;
constexpr uint32_t HO = X0 + 4096;
constexpr uint32_t HE = HO + HO_STRIDE + 64;
constexpr uint32_t SSLOT = HE + 4096 + 64;
constexpr uint32_t PART = 264 * 16;
constexpr uint32_t OFF_P = NS * SSLOT, OFF_D = OFF_P + NP * 4 * PART, END = OFF_D + NCH * 4;
static_assert(SSLOT % 128 == 0 && HO % 128 == 0 && END <= BARS, "smem");
enum : uint32_t { B_FULL = 0, B_EMPTY = NS, B_PFULL = 2 * NS, B_PEMPTY = 2 * NS + NP };
__device__ __forceinline__ int channel(int cidx, int i) { return (i >> 4) * 64 + cidx * 16 + (i & 15); }

__device__ __forceinline__ void producer(const Params& p, uint32_t sb, int cidx, unsigned epoch) {
#pragma unroll 1
  for (int i = 0; i < NCH; i++) {
    const int s = i % NS, ch = channel(cidx, i);
    const uint32_t full = bar_addr(sb, B_FULL + s), dst = sb + s * SSLOT;
    mbar_wait(bar_addr(sb, B_EMPTY + s), ((i / NS) & 1) ^ 1);
    mbar_expect_tx(full, 4096 + 4128 + 4096);
    bulk_ld(dst + HE, at<uint8_t>(p.a_ssmk, ch * 4096), 4096, full);
    if ((i & 15) == 0) { flag_wait<20>(flag_at(g_flags.x_ready, i >> 4), NMAIN, epoch); fence_async_global(); }
    bulk_ld(dst + HO, at<uint8_t>(g_ho, ch * HO_STRIDE), 4128, full);
    bulk_ld(dst + X0, at<uint8_t>(g_xs, ch * 4096), 4096, full);
  }
}

__device__ __forceinline__ void reducer(uint32_t sb, int cidx, int rw) {
  uint32_t n = 0;
#pragma unroll 1
  for (int i = rw; i < NCH; i += 3, n++) {
    const uint32_t b = rw + 3 * (n & 1), pb = sb + OFF_P + b * 4 * PART;
    uint8_t* dst = at<uint8_t>(g_xs, channel(cidx, i) * 4096);
    mbar_wait(bar_addr(sb, B_PFULL + b), (n >> 1) & 1);
    asm volatile("cp.async.bulk.global.shared::cta.bulk_group [%0], [%1], 4096;" :: "l"(dst), "r"(pb + 3 * PART) : "memory");
    bulk_commit();
    bulk_wait_all();
#pragma unroll
    for (int k = 2; k >= 0; k--)
      asm volatile("cp.reduce.async.bulk.global.shared::cta.bulk_group.add.noftz.bf16 [%0], [%1], 4096;" :: "l"(dst), "r"(pb + k * PART) : "memory");
    bulk_commit();
    bulk_wait_read();
    mbar_arrive(bar_addr(sb, B_PEMPTY + b));
    if (((i + 3) >> 4) != (i >> 4)) {
      bulk_wait_all();
      fence_async_global();
      flag_signal(flag_at(g_flags.z_ready, i >> 4));
    }
  }
}

__device__ __forceinline__ void mma_warpgroup(uint32_t sb, int w) {
  const int lane = threadIdx.x & 31, g = lane >> 2, c = lane & 3, wq = (threadIdx.x >> 5) & 3;
  const uint32_t aoff = ((g & 1) ? HO + 30 : HE) + (16 * wq - g + 2 * c) * 2;
  const uint32_t poff = OFF_P + wq * PART + (2 * wq + lane) * 16;
  const uint32_t dmask = (wq == 0 && c == (g >> 1)) ? ((g & 1) ? 0xffff0000u : 0xffffu) : 0u;
  float acc[8][16];
  uint32_t fa[16][4];
#pragma unroll
  for (int e = 0; e < 8; e++)
#pragma unroll
    for (int i = 0; i < 16; i++) acc[e][i] = 0.f;
  auto load_a = [&](int m, uint32_t ad) {
    fa[m][0] = lds4(ad + m * 256 + 16); fa[m][1] = lds4(ad + m * 256 + 144); fa[m][2] = lds4(ad + m * 256); fa[m][3] = lds4(ad + m * 256 + 128);
  };
  if (w == 1) named_arrive(PP_BAR, 256);
  mbar_wait(bar_addr(sb, B_FULL + w), 0);
#pragma unroll
  for (int m = 0; m < 16; m++) load_a(m, sb + w * SSLOT + aoff);
  uint32_t dd = lds4(sb + OFF_D + w * 4);
  if (threadIdx.x == 128) { GT(12); PT(10); }
  uint32_t pb = w, pphase = 1;
#pragma unroll 1
  for (int i = w; i < NCH; i += 2) {
    fa[0][2] = badd(fa[0][2], dd & dmask);
    const uint64_t db = (uint64_t)((((sb + (i % NS) * SSLOT + X0 - 16) & 0x3FFFF) >> 4) | (1u << 16)) | ((uint64_t)8 << 32);
    named_sync(PP_BAR + w, 256);
    wg_fence();
#pragma unroll
    for (int r = 0; r < 16; r++) {
      auto mm = [&](int e, int m) { wgmma_rs_n32(acc[e], fa[m][0], fa[m][1], fa[m][2], fa[m][3], db + (int64_t)(32 * e - 16 * m), m != 0); };
      mm(7, r);
      if (r < 14) mm(6, r); else mm(0, r - 14);
      if (r < 12) mm(5, r); else mm(1, r - 12);
      if (r < 10) mm(4, r); else mm(2, r - 10);
      if ((r & 1) == 0) mm(3, r >> 1);
      if (r == 13 && (i + 1 < NCH)) named_arrive(PP_BAR + (w ^ 1), 256);
    }
    wg_commit();
    const int nx = i + 2 < NCH ? i + 2 : i;
    mbar_wait(bar_addr(sb, B_FULL + nx % NS), (nx / NS) & 1);
    mbar_wait(bar_addr(sb, B_PEMPTY + pb), pphase);
    const uint32_t ad = sb + (nx % NS) * SSLOT + aoff, pa = sb + pb * 4 * PART + poff;
    wg_wait<0>();
#pragma unroll
    for (int e = 0; e < 8; e++) reg_fence(acc[e]);
#pragma unroll
    for (int m = 0; m < 16; m++) reg_fence(fa[m]);
    if (lane == 0) mbar_arrive(bar_addr(sb, B_EMPTY + i % NS));
#pragma unroll
    for (int e = 0; e < 8; e++) {
      load_a(e, ad);
      uint32_t u[4];
#pragma unroll
      for (int j = 0; j < 4; j++) {
        const int T = 4 * e + j, U = T - 1;
        float lo = acc[e][4 * j], hi = acc[e][4 * j + 1];
        if (T > 0) { lo += acc[U >> 2][4 * (U & 3) + 2]; hi += acc[U >> 2][4 * (U & 3) + 3]; }
        u[j] = pack_bf16(lo, hi);
      }
      asm volatile("stmatrix.sync.aligned.m8n8.x4.trans.shared.b16 [%0], {%1, %2, %3, %4};" :: "r"(pa + e * 512), "r"(u[0]), "r"(u[1]), "r"(u[2]), "r"(u[3]) : "memory");
    }
    dd = lds4(sb + OFF_D + nx * 4);
#pragma unroll
    for (int m = 8; m < 12; m++) load_a(m, ad);
    fence_async_smem();
    warp_arrive(bar_addr(sb, B_PFULL + pb), lane);
#pragma unroll
    for (int m = 12; m < 16; m++) load_a(m, ad);
    pb += 2;
    if (pb >= NP) { pb -= NP; pphase ^= 1; }
  }
  if (threadIdx.x == 128) { PT(9); GT(13); }
}

__device__ __forceinline__ void init(const Params& p, uint32_t sb, int cidx) {
  const uint32_t t = threadIdx.x;
  if (t < NCH) {
    const uint32_t d = (uint32_t)__ldg(reinterpret_cast<const unsigned short*>(p.a_D + channel(cidx, t))) * 0x10001u;
    asm volatile("st.shared.u32 [%0], %1;" :: "r"(sb + OFF_D + t * 4), "r"(d) : "memory");
  }
#pragma unroll 1
  for (uint32_t u = t; u < NS * 32; u += 128) {
    const uint32_t r = u & 31;
    if (r < 28) sts16(sb + (u >> 5) * SSLOT + (r < 24 ? r * 16 : HE - 64 + (r - 24) * 16), 0, 0, 0, 0);
    if (u < NP * 32) sts16(sb + OFF_P + (u >> 3) * PART + (u & 7) * 16, 0, 0, 0, 0);
  }
  if (t == 0) {
    for (int i = 0; i < NS; i++) { mbar_init(bar_addr(sb, B_FULL + i), 1); mbar_init(bar_addr(sb, B_EMPTY + i), 4); }
    for (int i = 0; i < NP; i++) { mbar_init(bar_addr(sb, B_PFULL + i), 4); mbar_init(bar_addr(sb, B_PEMPTY + i), 1); }
  }
  fence_async_smem();
}

__device__ __forceinline__ void side_prepare(const Params& p, int cta, int rd) {
  const int lane = threadIdx.x & 31, t0 = 16 * cta + 8 * (lane & 1);
#pragma unroll 1
  for (int ch = 64 * rd + (lane & ~1); ch < 64 * rd + 64; ch += 32) {
    const uint4 sv = __ldg(at<const uint4>(p.a_shift, ch * 8));
    const uint32_t* kp = at<const uint32_t>(p.a_k, (t0 * DA + ch) * 2);
    const uint32_t* vp = at<const uint32_t>(p.a_v, (t0 * DA + ch) * 2);
    uint32_t k0 = 0, k1 = 0, k2 = 0, kk[8], x[8];
    if (t0 > 0) { k0 = __ldg(kp - 3 * (DA / 2)); k1 = __ldg(kp - 2 * (DA / 2)); k2 = __ldg(kp - DA / 2); }
#pragma unroll
    for (int i = 0; i < 8; i++) { kk[i] = __ldg(kp + i * (DA / 2)); x[i] = __ldg(vp + i * (DA / 2)); }
    const uint32_t sh0 = __byte_perm(sv.x, sv.z, 0x5410), sh1 = __byte_perm(sv.x, sv.z, 0x7632);
    const uint32_t sh2 = __byte_perm(sv.y, sv.w, 0x5410), sh3 = __byte_perm(sv.y, sv.w, 0x7632);
#pragma unroll
    for (int i = 0; i < 8; i++) {
      uint32_t ks = bmul(k0, sh3);
      ks = badd(ks, bmul(k1, sh2)); ks = badd(ks, bmul(k2, sh1)); ks = badd(ks, bmul(kk[i], sh0));
      x[i] = bmul(ks, x[i]);
      k0 = k1; k1 = k2; k2 = kk[i];
    }
    uint4* dst = at<uint4>(g_xs, ch * 4096 + t0 * 2);
    dst[0]   = make_uint4(__byte_perm(x[7], x[6], 0x5410), __byte_perm(x[5], x[4], 0x5410), __byte_perm(x[3], x[2], 0x5410), __byte_perm(x[1], x[0], 0x5410));
    dst[256] = make_uint4(__byte_perm(x[7], x[6], 0x7632), __byte_perm(x[5], x[4], 0x7632), __byte_perm(x[3], x[2], 0x7632), __byte_perm(x[1], x[0], 0x7632));
  }
  {
    const int hc = 64 * rd + (cta >> 1), r0 = (cta & 1) * 128 + lane;
    const uint4* src = at<const uint4>(p.a_ssmk, hc * 4096 + r0 * 16);
    uint4* dst = at<uint4>(g_ho, hc * HO_STRIDE + r0 * 16);
    uint4 w[4];
    uint32_t nx[4];
#pragma unroll
    for (int i = 0; i < 4; i++) { w[i] = __ldg(src + 32 * i); nx[i] = r0 + 32 * i < 255 ? __ldg(reinterpret_cast<const uint32_t*>(src + 32 * i + 1)) : 0u; }
#pragma unroll
    for (int i = 0; i < 4; i++)
      dst[32 * i + 2] = make_uint4(__byte_perm(w[i].x, w[i].y, 0x5432), __byte_perm(w[i].y, w[i].z, 0x5432), __byte_perm(w[i].z, w[i].w, 0x5432), __byte_perm(w[i].w, nx[i], 0x5432));
    const uint32_t h0 = __shfl_sync(0xffffffffu, w[0].x, 0);
    if (r0 < 2) dst[0] = make_uint4(0, 0, 0, r0 ? h0 << 16 : 0u);
  }
  __syncwarp();
  if (lane == 0) flag_signal(flag_at(g_flags.x_ready, rd));
}
__device__ __forceinline__ void side_finish(const Params& p, int cta, int rd) {
  const int lane = threadIdx.x & 31, t0 = 16 * cta + 8 * (lane & 1);
#pragma unroll 1
  for (int ch = 64 * rd + (lane & ~1); ch < 64 * rd + 64; ch += 32) {
    const uint4* src = at<const uint4>(g_xs, ch * 4096 + t0 * 2);
    const uint32_t* qp = at<const uint32_t>(p.a_q, (t0 * DA + ch) * 2);
    uint32_t* op = at<uint32_t>(p.out, (t0 * OUTW + ch) * 2);
    const uint4 z0 = __ldcg(src), z1 = __ldcg(src + 256);
    uint32_t q[8];
#pragma unroll
    for (int i = 0; i < 8; i++) q[i] = __ldg(qp + i * (DA / 2));
    const uint32_t a[4] = {z0.w, z0.z, z0.y, z0.x}, b[4] = {z1.w, z1.z, z1.y, z1.x};
#pragma unroll
    for (int i = 0; i < 4; i++) {
      op[(2 * i) * (OUTW / 2)]     = bmul(q[2 * i], __byte_perm(a[i], b[i], 0x7632));
      op[(2 * i + 1) * (OUTW / 2)] = bmul(q[2 * i + 1], __byte_perm(a[i], b[i], 0x5410));
    }
  }
}
__device__ __forceinline__ void clear_rows(const Params& p, int qt, int part) {
  const int lane = threadIdx.x & 31;
  if (lane < 28) {
    uint4* z = at<uint4>(p.out, ((qt * 128 + part * 16) * OUTW + DA) * 2 + lane * 16);
#pragma unroll
    for (int i = 0; i < 32; i++) z[(i >> 1) * (OUTW / 8) + (i & 1) * 28] = make_uint4(0, 0, 0, 0);
  }
  __syncwarp();
  if (lane == 0) flag_signal(flag_at(g_flags.zero_ready, qt));
}
__device__ __forceinline__ void side_work(const Params& p, int cta, unsigned epoch) {
#pragma unroll 1
  for (int rd = -SIDE_AHEAD; rd < 7; rd++) {
    if (rd >= 0) {
      if ((threadIdx.x & 31) == 0) flag_wait<1000>(flag_at(g_flags.z_ready, rd), 3 * NCONV, epoch);
      __syncwarp();
    }
    if (rd + SIDE_AHEAD < 7) side_prepare(p, cta, rd + SIDE_AHEAD);
    if (rd >= 0) side_finish(p, cta, rd);
    if (rd == ZERO_RD) clear_rows(p, cta & 15, cta >> 4);
  }
}
}

__global__ void __cluster_dims__(2, 1, 1) __launch_bounds__(NTHREADS, 1)
concat_heads__ssm_conv_h3__compressed_kv_cla__prompt_kernel(const __grid_constant__ Params p) {
  extern __shared__ uint8_t smem_raw[];
  const uint32_t sb = (smem_u32(smem_raw) + 1023) & ~1023u;
  if (threadIdx.x == NTHREADS - 64) { prefetch_map(&p.wuk); prefetch_map(&p.ckv); }
  const int cta = blockIdx.x;
  const bool attn = cta < NMAIN;
  int g, t;
  {
    const int c = cta >> 1, u2 = ((c - 36) * 37) >> 8, i = c - 36 - 7 * u2;
    g = c < 4 ? 1 : c < 36 ? (c - 4) & 7 : i == 0 ? 0 : 1 + i;
    t = 2 * (c < 4 ? c : c < 36 ? 7 - ((c - 4) >> 3) : u2) + (cta & 1);
  }
  if (attn && threadIdx.x == NTHREADS - 32) {
    const uint32_t full = bar_addr(sb, B_FULL);
    mbar_init(full, 1);
    asm volatile("fence.mbarrier_init.release.cluster;" ::: "memory");
    mbar_expect_tx(full, 49152);
    load_w(p, g, t, 0, sb, full);
    load_a(p, g, t, 0, sb + QREG, full);
  }
  __syncwarp();
  const int lane = threadIdx.x & 31;
  const int warp = __shfl_sync(0xffffffffu, threadIdx.x >> 5, 0);
  const int wg = warp >> 2;
  if (wg != 0) {
    if (attn) {
      cluster_arrive();
      if (wg == 2) named_arrive(PP_BAR, 256);
    }
    asm volatile("setmaxnreg.inc.sync.aligned.u32 232;");
    if (!attn) {
      if (p.out != nullptr) { named_sync(0, NTHREADS); ssm::mma_warpgroup(sb, wg - 1); }
      return;
    }
    if (p.out != nullptr) consumer_main(p, sb, g, t, wg - 1, warp & 3);
  } else {
    asm volatile("setmaxnreg.dec.sync.aligned.u32 40;");
    if (!attn) {
      ssm::init(p, sb, cta - NMAIN);
      named_sync(0, NTHREADS);
      if (lane == 0) {
        if (warp == 0) { ssm::producer(p, sb, cta - NMAIN, load_epoch()); cta_done(32); }
        else ssm::reducer(sb, cta - NMAIN, warp - 1);
        if (warp == 1) GT(14);
      }
      return;
    }
    if (warp == 0) {
      if (lane == 0) {
        for (int i = 1; i < NSLOT; i++) mbar_init(bar_addr(sb, B_FULL + i), 1);
        asm volatile("fence.mbarrier_init.release.cluster;" ::: "memory");
      }
      __syncwarp();
      cluster_arrive();
      if (lane == 0) {
#pragma unroll 1
        for (int k = 1; k < EARLY_LD; k++) {
          const uint32_t full = bar_addr(sb, B_FULL + k);
          mbar_expect_tx(full, 49152);
          load_w(p, g, t, k & 15, sb + k * SLOT, full);
          load_a(p, g, t, k & 15, sb + QREG + k * 16384, full);
          __nanosleep(200);
        }
      }
      __syncwarp();
      cluster_wait();
      if (lane == 0) producer_main(p, sb, g, t);
      return;
    }
    if (lane == 0) {
      if (warp == 1) {
        for (int i = 0; i < NSLOT; i++) mbar_init(bar_addr(sb, B_EMPTY + i), 16);
        for (int i = 0; i < 2; i++) {
          mbar_init(bar_addr(sb, B_QFREE + i), 4); mbar_init(bar_addr(sb, B_QFULL + i), 1);
          mbar_init(bar_addr(sb, B_CTXOK + i), 1);
        }
      } else if (warp == 2) {
        for (int i = 0; i < 8; i++) { mbar_init(bar_addr(sb, B_S2_FULL + i), 4); mbar_init(bar_addr(sb, B_S2_EMPTY + i), 1); }
      } else {
        mbar_init(bar_addr(sb, B_DONE), 2);
        mbar_init(bar_addr(sb, B_KVOK), 1);
        for (int i = 0; i < 2; i++) {
          mbar_init(bar_addr(sb, B_ST_KV + i), 4); mbar_init(bar_addr(sb, B_ST_Q + i), 4); mbar_init(bar_addr(sb, B_ST_CTX + i), 4);
        }
      }
      asm volatile("fence.mbarrier_init.release.cluster;" ::: "memory");
    }
    __syncwarp();
    cluster_arrive();
    cluster_wait();
    if (warp < 3) {
      if (lane == 0) {
        if (warp == 1) { __nanosleep(2000); prefetch_map(&p.wuv); prefetch_map(&p.x); prefetch_map(&p.wq); prefetch_map(&p.o); prefetch_map(&p.wo); }
        helper_main(p, sb, g, t, warp - 1);
      }
    } else {
      ssm::side_work(p, g * 16 + t, load_epoch());
      if (lane == 0) { GT(57); mbar_wait(bar_addr(sb, B_DONE), 0); cta_done(1); }
    }
  }
}

typedef CUresult (*EncodeTiledFn)(CUtensorMap*, CUtensorMapDataType, cuuint32_t, void*, const cuuint64_t*, const cuuint64_t*,
                                  const cuuint32_t*, const cuuint32_t*, CUtensorMapInterleave, CUtensorMapSwizzle,
                                  CUtensorMapL2promotion, CUtensorMapFloatOOBfill);

void make_map(EncodeTiledFn enc, CUtensorMap* m, const void* ptr, int rank, const uint64_t* dims, const uint64_t* strides, const uint32_t* box) {
  cuuint64_t d[5], s[4]; cuuint32_t b[5], e[5] = {1, 1, 1, 1, 1};
  for (int i = 0; i < rank; i++) { d[i] = dims[i]; b[i] = box[i]; if (i) s[i - 1] = strides[i - 1]; }
  enc(m, CU_TENSOR_MAP_DATA_TYPE_BFLOAT16, rank, const_cast<void*>(ptr), d, s, b, e, CU_TENSOR_MAP_INTERLEAVE_NONE,
      CU_TENSOR_MAP_SWIZZLE_128B, CU_TENSOR_MAP_L2_PROMOTION_L2_256B, CU_TENSOR_MAP_FLOAT_OOB_FILL_NONE);
}
void map2(EncodeTiledFn enc, CUtensorMap* m, const void* ptr, uint64_t cols, uint64_t rows, uint32_t bc, uint32_t br) {
  const uint64_t dims[2] = {cols, rows}, st[1] = {cols * 2}; const uint32_t box[2] = {bc, br};
  make_map(enc, m, ptr, 2, dims, st, box);
}
void map3(EncodeTiledFn enc, CUtensorMap* m, const void* ptr, uint64_t rows, uint32_t nblk) {
  const uint64_t dims[3] = {64, rows, 64}, st[2] = {8192, 128}; const uint32_t box[3] = {64, 64, nblk};
  make_map(enc, m, ptr, 3, dims, st, box);
}

}

extern "C" void kernel_launch(void* const* d_in, const int* in_sizes, int n_in, void* d_out, int out_size) {
  (void)in_sizes; (void)n_in; (void)out_size;
  static EncodeTiledFn enc = nullptr;
  if (!enc) {
    void* fn = nullptr; cudaDriverEntryPointQueryResult qr;
    cudaGetDriverEntryPoint("cuTensorMapEncodeTiled", &fn, cudaEnableDefault, &qr);
    enc = (EncodeTiledFn)fn;
    cudaFuncSetAttribute(concat_heads__ssm_conv_h3__compressed_kv_cla__prompt_kernel, cudaFuncAttributeMaxDynamicSharedMemorySize, SMEM_BYTES);
  }
  Params p;
  p.a_q = (const bf16*)d_in[0]; p.a_k = (const bf16*)d_in[1]; p.a_v = (const bf16*)d_in[2];
  p.a_shift = (const bf16*)d_in[3]; p.a_ssmk = (const bf16*)d_in[4]; p.a_D = (const bf16*)d_in[5];
  p.out = (bf16*)d_out;
  map2(enc, &p.x, d_in[6], DM, SEQ, 64, 128);
  map2(enc, &p.ckv, d_in[7], DC, SEQ, 64, 128);
  map3(enc, &p.wq, d_in[8], DM, 4);
  map3(enc, &p.wuk, d_in[9], DC, 4);
  map3(enc, &p.wuv, d_in[10], DC, 4);
  {
    const uint64_t dims[5] = {DM, 2, 4, 4, NH * HD / 32}, st[4] = {DM * 2, 8 * DM * 2, 2 * DM * 2, 32 * DM * 2}; const uint32_t box[5] = {64, 2, 4, 4, 4};
    make_map(enc, &p.wo, d_in[11], 5, dims, st, box);
  }
  map2(enc, &p.o, d_out, OUTW, SEQ, 64, 64);
  concat_heads__ssm_conv_h3__compressed_kv_cla__prompt_kernel<<<NCTA, NTHREADS, SMEM_BYTES>>>(p);
}
```

```cpp
#include <cuda_runtime.h>
#include <cuda_bf16.h>
#include <cuda.h>
#include <stdint.h>

namespace {

typedef __nv_bfloat16 bf16;

constexpr int SEQ  = 2048;
constexpr int DA   = 448;
constexpr int NH   = 16;
constexpr int HD   = 256;
constexpr int DM   = 448;
constexpr int DC   = 1024;
constexpr int OUTW = DA + DM;
constexpr int NMAIN = 128;
constexpr int NCONV = 4;
constexpr int NCTA  = NMAIN + NCONV;
constexpr int LOG_DONE = 8;
constexpr int NTHREADS = 384;

__device__ __align__(1024) bf16 g_kv[2ull * SEQ * NH * HD];
__device__ __align__(1024) bf16 g_qc[(size_t)NMAIN * 128 * HD];
__device__ __align__(128) uint8_t g_xs[DA * SEQ * 2];
constexpr uint32_t HO_STRIDE = 4224;
__device__ __align__(128) uint8_t g_ho[DA * HO_STRIDE];
struct alignas(128) Flag { unsigned v; unsigned pad[31]; };
struct Flags {
  Flag kv_ready[8];
  Flag ctx_ready[NMAIN * 2];
  Flag x_ready[7];
  Flag z_ready[7];
  Flag zero_ready[16];
  alignas(128) unsigned long long done;
};
__device__ Flags g_flags;
#define TS(i)
#define TSC(i, cond)
#define TDUMP()
#define GT(i)
#define PT(i)

struct alignas(64) Params {
  CUtensorMap ckv;
  CUtensorMap wuk;
  CUtensorMap wuv;
  CUtensorMap x;
  CUtensorMap wq;
  CUtensorMap o;
  CUtensorMap wo;
  const bf16 *a_q, *a_k, *a_v, *a_shift, *a_ssmk, *a_D, *b_x;
  bf16* out;
};

constexpr uint32_t SLOT     = 32768;
constexpr int      NSLOT    = 5;
constexpr uint32_t QREG     = 163840;
constexpr uint32_t BARS     = 229376;
constexpr uint32_t SMEM_BYTES = BARS + 1024 + 1024;
enum : uint32_t {
  B_FULL = 0, B_EMPTY = 5, B_KVOK = 10, B_DONE = 11, B_ST_KV = 12, B_ST_Q = 14, B_ST_CTX = 16, B_CTXOK = 18, B_QFREE = 20, B_QFULL = 22,
  B_S2_FULL = 24, B_S2_EMPTY = 32, B_PF = 40
};
constexpr int P1_STEPS = 4 * 16 + 2 * 7, P1_XS = P1_STEPS - 2;

template <typename T> __device__ __forceinline__ T* at(const void* base, uint32_t off) {
  asm volatile("" : "+r"(off));
  return reinterpret_cast<T*>(const_cast<char*>(static_cast<const char*>(base)) + off);
}
__device__ __forceinline__ unsigned* flag_at(Flag* f, uint32_t i) { return at<unsigned>(f, i * (uint32_t)sizeof(Flag)); }
__device__ __forceinline__ uint32_t smem_u32(const void* p) { return (uint32_t)__cvta_generic_to_shared(p); }
__device__ __forceinline__ void mbar_init(uint32_t bar, uint32_t cnt) {
  asm volatile("mbarrier.init.shared::cta.b64 [%0], %1;" :: "r"(bar), "r"(cnt) : "memory");
}
__device__ __forceinline__ void mbar_expect_tx(uint32_t bar, uint32_t bytes) {
  asm volatile("mbarrier.arrive.expect_tx.shared::cta.b64 _, [%0], %1;" :: "r"(bar), "r"(bytes) : "memory");
}
__device__ __forceinline__ void mbar_arrive(uint32_t bar) {
  asm volatile("mbarrier.arrive.shared::cta.b64 _, [%0];" :: "r"(bar) : "memory");
}
__device__ __forceinline__ void mbar_arrive_remote(uint32_t bar, uint32_t cta) {
  asm volatile("{\n.reg .b32 ra;\nmapa.shared::cluster.u32 ra, %0, %1;\n"
               "mbarrier.arrive.shared::cluster.b64 _, [ra];\n}" :: "r"(bar), "r"(cta) : "memory");
}
__device__ __forceinline__ bool mbar_try(uint32_t bar, uint32_t parity) {
  uint32_t ok;
  asm volatile("{\n.reg .pred p;\nmbarrier.try_wait.parity.shared::cta.b64 p, [%1], %2;\nselp.u32 %0, 1, 0, p;\n}"
               : "=r"(ok) : "r"(bar), "r"(parity) : "memory");
  return ok;
}
__device__ __forceinline__ uint32_t mbar_test(uint32_t bar, uint32_t parity) {
  uint32_t ok;
  asm volatile("{\n.reg .pred p;\nmbarrier.test_wait.parity.shared::cta.b64 p, [%1], %2;\nselp.u32 %0, 1, 0, p;\n}"
               : "=r"(ok) : "r"(bar), "r"(parity) : "memory");
  return ok;
}
constexpr uint32_t SPIN_LIMIT = 1u << 24;
__device__ __forceinline__ void mbar_wait(uint32_t bar, uint32_t parity) {
  if (mbar_try(bar, parity)) return;
  uint32_t n = 0;
  while (!mbar_try(bar, parity)) { if (++n > SPIN_LIMIT) __trap(); }
}
__device__ __forceinline__ void mbar_wait_unless(uint32_t ready, uint32_t bar, uint32_t parity) {
  asm volatile("{\n.reg .pred p;\n.reg .b32 n;\nsetp.ne.u32 p, %0, 0;\nvote.sync.all.pred p, p, 0xffffffff;\n@p bra.uni WDONE;\nmov.u32 n, 0;\n"
               "WLOOP:\nmbarrier.try_wait.parity.shared::cta.b64 p, [%1], %2;\n@p bra.uni WDONE;\nadd.u32 n, n, 1;\nsetp.lt.u32 p, n, %3;\n@p bra.uni WLOOP;\ntrap;\nWDONE:\n}"
               :: "r"(ready), "r"(bar), "r"(parity), "n"(SPIN_LIMIT) : "memory");
}
__device__ __forceinline__ unsigned load_epoch() {
  unsigned long long d; asm volatile("ld.relaxed.gpu.global.u64 %0, [%1];" : "=l"(d) : "l"(&g_flags.done) : "memory");
  return (unsigned)(d >> LOG_DONE);
}
template <int SLEEP_NS>
__device__ __forceinline__ void flag_wait(const unsigned* f, unsigned count, unsigned epoch) {
  const unsigned target = (epoch + 1) * count;
  uint32_t n = 0;
  while (true) {
    unsigned v;
    asm volatile("ld.acquire.gpu.global.u32 %0, [%1];" : "=r"(v) : "l"(f) : "memory");
    if ((int)(v - target) >= 0) break;
    if (++n > SPIN_LIMIT / 4) __trap();
    __nanosleep(SLEEP_NS);
  }
}
__device__ __forceinline__ void flag_signal(unsigned* f) { asm volatile("red.release.gpu.global.add.u32 [%0], 1;" :: "l"(f) : "memory"); }
__device__ __forceinline__ void cta_done(unsigned long long n) { asm volatile("red.relaxed.gpu.global.add.u64 [%0], %1;" :: "l"(&g_flags.done), "l"(n) : "memory"); }
__device__ __forceinline__ void fence_async_global() { asm volatile("fence.proxy.async.global;" ::: "memory"); }
__device__ __forceinline__ void fence_async_smem() { asm volatile("fence.proxy.async.shared::cta;" ::: "memory"); }
__device__ __forceinline__ void tma_ld2(uint32_t dst, const CUtensorMap* m, uint32_t bar, int c0, int c1) {
  asm volatile("cp.async.bulk.tensor.2d.shared::cluster.global.mbarrier::complete_tx::bytes [%0], [%1, {%3, %4}], [%2];"
               :: "r"(dst), "l"(m), "r"(bar), "r"(c0), "r"(c1) : "memory");
}
__device__ __forceinline__ void tma_ld3(uint32_t dst, const CUtensorMap* m, uint32_t bar, int c0, int c1, int c2) {
  asm volatile("cp.async.bulk.tensor.3d.shared::cluster.global.mbarrier::complete_tx::bytes [%0], [%1, {%3, %4, %5}], [%2];"
               :: "r"(dst), "l"(m), "r"(bar), "r"(c0), "r"(c1), "r"(c2) : "memory");
}
__device__ __forceinline__ void tma_ld5_mc(uint32_t dst, const CUtensorMap* m, uint32_t bar, int c0, int c4) {
  asm volatile("cp.async.bulk.tensor.5d.shared::cluster.global.mbarrier::complete_tx::bytes.multicast::cluster [%0], [%1, {%3, %6, %6, %6, %4}], [%2], %5;"
               :: "r"(dst), "l"(m), "r"(bar), "r"(c0), "r"(c4), "h"((uint16_t)3), "r"(0) : "memory");
}
__device__ __forceinline__ void bulk_ld(uint32_t dst, const void* src, uint32_t bytes, uint32_t bar) {
  asm volatile("cp.async.bulk.shared::cluster.global.mbarrier::complete_tx::bytes [%0], [%1], %2, [%3];"
               :: "r"(dst), "l"(src), "r"(bytes), "r"(bar) : "memory");
}
__device__ __forceinline__ void bulk_ld_p(uint32_t dst, const void* src, uint32_t bytes, uint32_t bar, uint64_t pl) {
  asm volatile("cp.async.bulk.shared::cluster.global.mbarrier::complete_tx::bytes.L2::cache_hint [%0], [%1], %2, [%3], %4;"
               :: "r"(dst), "l"(src), "r"(bytes), "r"(bar), "l"(pl) : "memory");
}
__device__ __forceinline__ void bulk_ld_mc(uint32_t dst, const void* src, uint32_t bytes, uint32_t bar, uint64_t pl) {
  asm volatile("cp.async.bulk.shared::cluster.global.mbarrier::complete_tx::bytes.multicast::cluster.L2::cache_hint [%0], [%1], %2, [%3], %4, %5;"
               :: "r"(dst), "l"(src), "r"(bytes), "r"(bar), "h"((uint16_t)3), "l"(pl) : "memory");
}
__device__ __forceinline__ void tma_red2(const CUtensorMap* m, uint32_t src, int c0, int c1) {
  asm volatile("cp.reduce.async.bulk.tensor.2d.global.shared::cta.add.bulk_group [%0, {%2, %3}], [%1];"
               :: "l"(m), "r"(src), "r"(c0), "r"(c1) : "memory");
}
__device__ __forceinline__ void bulk_commit() { asm volatile("cp.async.bulk.commit_group;" ::: "memory"); }
__device__ __forceinline__ void bulk_wait_read() { asm volatile("cp.async.bulk.wait_group.read 0;" ::: "memory"); }
__device__ __forceinline__ void bulk_wait_all() { asm volatile("cp.async.bulk.wait_group 0;" ::: "memory"); }
__device__ __forceinline__ void prefetch_map(const CUtensorMap* m) { asm volatile("prefetch.tensormap [%0];" :: "l"(m) : "memory"); }
__device__ __forceinline__ void wg_fence() { asm volatile("wgmma.fence.sync.aligned;" ::: "memory"); }
__device__ __forceinline__ void wg_commit() { asm volatile("wgmma.commit_group.sync.aligned;" ::: "memory"); }
template <int N> __device__ __forceinline__ void wg_wait() { asm volatile("wgmma.wait_group.sync.aligned %0;" :: "n"(N) : "memory"); }
template <int N> __device__ __forceinline__ void reg_fence(float (&d)[N]) {
#pragma unroll
  for (int i = 0; i < N; i++) asm volatile("" : "+f"(d[i]) :: "memory");
}
template <int N> __device__ __forceinline__ void reg_fence(uint32_t (&d)[N]) {
#pragma unroll
  for (int i = 0; i < N; i++) asm volatile("" : "+r"(d[i]) :: "memory");
}
__device__ __forceinline__ uint32_t fresh_tid() { uint32_t t; asm volatile("mov.u32 %0, %%tid.x;" : "=r"(t)); return t; }
__device__ __forceinline__ uint32_t lane_base16() {
  const uint32_t t = fresh_tid(), lane = t & 31, wq = (t >> 5) & 3;
  return (16 * wq + (lane & 7) + 8 * ((lane >> 3) & 1)) * 128 + (((lane >> 4) ^ (lane & 7)) << 4);
}
__device__ __forceinline__ void cluster_arrive() { asm volatile("barrier.cluster.arrive.relaxed.aligned;" ::: "memory"); }
__device__ __forceinline__ void cluster_wait() { asm volatile("barrier.cluster.wait.acquire.aligned;" ::: "memory"); }
__device__ __forceinline__ void named_sync(int id, int n) { asm volatile("bar.sync %0, %1;" :: "r"(id), "r"(n) : "memory"); }
__device__ __forceinline__ void named_arrive(int id, int n) { asm volatile("bar.arrive %0, %1;" :: "r"(id), "r"(n) : "memory"); }
__device__ __forceinline__ uint32_t pack_bf16(float lo, float hi) {
  uint32_t r; asm("cvt.rn.bf16x2.f32 %0, %1, %2;" : "=r"(r) : "f"(hi), "f"(lo)); return r;
}
__device__ __forceinline__ float ex2(float x) { float y; asm("ex2.approx.ftz.f32 %0, %1;" : "=f"(y) : "f"(x)); return y; }
__device__ __forceinline__ void stsm4(uint32_t addr, uint32_t a, uint32_t b, uint32_t c, uint32_t d) {
  asm volatile("stmatrix.sync.aligned.m8n8.x4.shared.b16 [%0], {%1, %2, %3, %4};" :: "r"(addr), "r"(a), "r"(b), "r"(c), "r"(d) : "memory");
}
__device__ __forceinline__ uint64_t mk_desc(uint32_t addr, uint32_t lbo, uint32_t sbo) {
  return (uint64_t)(((addr & 0x3FFFF) >> 4) | ((lbo >> 4) << 16)) | ((uint64_t)((sbo >> 4) | (1u << 30)) << 32);
}
__device__ __forceinline__ uint64_t desc_k(uint32_t addr)  { return mk_desc(addr, 16, 1024); }
__device__ __forceinline__ uint64_t desc_mn(uint32_t addr) { return mk_desc(addr, 8192, 1024); }
__device__ __forceinline__ uint64_t desc_64(uint32_t addr) { return (uint64_t)(((addr & 0x3FFFF) >> 4) | ((4096u >> 4) << 16)) | ((uint64_t)((512u >> 4) | (2u << 30)) << 32); }
__device__ __forceinline__ uint64_t desc_add(uint64_t d, uint32_t bytes) { return d + (bytes >> 4); }

__device__ __forceinline__ void wgmma_ss_n256_tb(float (&d)[128], uint64_t da, uint64_t db, int sd) {
  asm volatile("{\n.reg .pred p;\nsetp.ne.b32 p, %130, 0;\n"
    "wgmma.mma_async.sync.aligned.m64n256k16.f32.bf16.bf16 "
    "{%0, %1, %2, %3, %4, %5, %6, %7, %8, %9, %10, %11, %12, %13, %14, %15, "
    "%16, %17, %18, %19, %20, %21, %22, %23, %24, %25, %26, %27, %28, %29, %30, %31, "
    "%32, %33, %34, %35, %36, %37, %38, %39, %40, %41, %42, %43, %44, %45, %46, %47, "
    "%48, %49, %50, %51, %52, %53, %54, %55, %56, %57, %58, %59, %60, %61, %62, %63, "
    "%64, %65, %66, %67, %68, %69, %70, %71, %72, %73, %74, %75, %76, %77, %78, %79, "
    "%80, %81, %82, %83, %84, %85, %86, %87, %88, %89, %90, %91, %92, %93, %94, %95, "
    "%96, %97, %98, %99, %100, %101, %102, %103, %104, %105, %106, %107, %108, %109, %110, %111, "
    "%112, %113, %114, %115, %116, %117, %118, %119, %120, %121, %122, %123, %124, %125, %126, %127}, "
    "%128, %129, p, 1, 1, 0, 1;\n}"
    : "+f"(d[0]), "+f"(d[1]), "+f"(d[2]), "+f"(d[3]), "+f"(d[4]), "+f"(d[5]), "+f"(d[6]), "+f"(d[7]),
      "+f"(d[8]), "+f"(d[9]), "+f"(d[10]), "+f"(d[11]), "+f"(d[12]), "+f"(d[13]), "+f"(d[14]), "+f"(d[15]),
      "+f"(d[16]), "+f"(d[17]), "+f"(d[18]), "+f"(d[19]), "+f"(d[20]), "+f"(d[21]), "+f"(d[22]), "+f"(d[23]),
      "+f"(d[24]), "+f"(d[25]), "+f"(d[26]), "+f"(d[27]), "+f"(d[28]), "+f"(d[29]), "+f"(d[30]), "+f"(d[31]),
      "+f"(d[32]), "+f"(d[33]), "+f"(d[34]), "+f"(d[35]), "+f"(d[36]), "+f"(d[37]), "+f"(d[38]), "+f"(d[39]),
      "+f"(d[40]), "+f"(d[41]), "+f"(d[42]), "+f"(d[43]), "+f"(d[44]), "+f"(d[45]), "+f"(d[46]), "+f"(d[47]),
      "+f"(d[48]), "+f"(d[49]), "+f"(d[50]), "+f"(d[51]), "+f"(d[52]), "+f"(d[53]), "+f"(d[54]), "+f"(d[55]),
      "+f"(d[56]), "+f"(d[57]), "+f"(d[58]), "+f"(d[59]), "+f"(d[60]), "+f"(d[61]), "+f"(d[62]), "+f"(d[63]),
      "+f"(d[64]), "+f"(d[65]), "+f"(d[66]), "+f"(d[67]), "+f"(d[68]), "+f"(d[69]), "+f"(d[70]), "+f"(d[71]),
      "+f"(d[72]), "+f"(d[73]), "+f"(d[74]), "+f"(d[75]), "+f"(d[76]), "+f"(d[77]), "+f"(d[78]), "+f"(d[79]),
      "+f"(d[80]), "+f"(d[81]), "+f"(d[82]), "+f"(d[83]), "+f"(d[84]), "+f"(d[85]), "+f"(d[86]), "+f"(d[87]),
      "+f"(d[88]), "+f"(d[89]), "+f"(d[90]), "+f"(d[91]), "+f"(d[92]), "+f"(d[93]), "+f"(d[94]), "+f"(d[95]),
      "+f"(d[96]), "+f"(d[97]), "+f"(d[98]), "+f"(d[99]), "+f"(d[100]), "+f"(d[101]), "+f"(d[102]), "+f"(d[103]),
      "+f"(d[104]), "+f"(d[105]), "+f"(d[106]), "+f"(d[107]), "+f"(d[108]), "+f"(d[109]), "+f"(d[110]), "+f"(d[111]),
      "+f"(d[112]), "+f"(d[113]), "+f"(d[114]), "+f"(d[115]), "+f"(d[116]), "+f"(d[117]), "+f"(d[118]), "+f"(d[119]),
      "+f"(d[120]), "+f"(d[121]), "+f"(d[122]), "+f"(d[123]), "+f"(d[124]), "+f"(d[125]), "+f"(d[126]), "+f"(d[127])
    : "l"(da), "l"(db), "r"(sd));
}
__device__ __forceinline__ void wgmma_ss_n64(float (&d)[32], uint64_t da, uint64_t db, int sd) {
  asm volatile("{\n.reg .pred p;\nsetp.ne.b32 p, %34, 0;\n"
    "wgmma.mma_async.sync.aligned.m64n64k16.f32.bf16.bf16 "
    "{%0, %1, %2, %3, %4, %5, %6, %7, %8, %9, %10, %11, %12, %13, %14, %15, "
    "%16, %17, %18, %19, %20, %21, %22, %23, %24, %25, %26, %27, %28, %29, %30, %31}, "
    "%32, %33, p, 1, 1, 0, 0;\n}"
    : "+f"(d[0]), "+f"(d[1]), "+f"(d[2]), "+f"(d[3]), "+f"(d[4]), "+f"(d[5]), "+f"(d[6]), "+f"(d[7]),
      "+f"(d[8]), "+f"(d[9]), "+f"(d[10]), "+f"(d[11]), "+f"(d[12]), "+f"(d[13]), "+f"(d[14]), "+f"(d[15]),
      "+f"(d[16]), "+f"(d[17]), "+f"(d[18]), "+f"(d[19]), "+f"(d[20]), "+f"(d[21]), "+f"(d[22]), "+f"(d[23]),
      "+f"(d[24]), "+f"(d[25]), "+f"(d[26]), "+f"(d[27]), "+f"(d[28]), "+f"(d[29]), "+f"(d[30]), "+f"(d[31])
    : "l"(da), "l"(db), "r"(sd));
}
__device__ __forceinline__ void wgmma_rs_n256_tb(float (&d)[128], uint32_t a0, uint32_t a1, uint32_t a2, uint32_t a3, uint64_t db, int sd) {
  asm volatile("{\n.reg .pred p;\nsetp.ne.b32 p, %133, 0;\n"
    "wgmma.mma_async.sync.aligned.m64n256k16.f32.bf16.bf16 "
    "{%0, %1, %2, %3, %4, %5, %6, %7, %8, %9, %10, %11, %12, %13, %14, %15, "
    "%16, %17, %18, %19, %20, %21, %22, %23, %24, %25, %26, %27, %28, %29, %30, %31, "
    "%32, %33, %34, %35, %36, %37, %38, %39, %40, %41, %42, %43, %44, %45, %46, %47, "
    "%48, %49, %50, %51, %52, %53, %54, %55, %56, %57, %58, %59, %60, %61, %62, %63, "
    "%64, %65, %66, %67, %68, %69, %70, %71, %72, %73, %74, %75, %76, %77, %78, %79, "
    "%80, %81, %82, %83, %84, %85, %86, %87, %88, %89, %90, %91, %92, %93, %94, %95, "
    "%96, %97, %98, %99, %100, %101, %102, %103, %104, %105, %106, %107, %108, %109, %110, %111, "
    "%112, %113, %114, %115, %116, %117, %118, %119, %120, %121, %122, %123, %124, %125, %126, %127}, "
    "{%128, %129, %130, %131}, %132, p, 1, 1, 1;\n}"
    : "+f"(d[0]), "+f"(d[1]), "+f"(d[2]), "+f"(d[3]), "+f"(d[4]), "+f"(d[5]), "+f"(d[6]), "+f"(d[7]),
      "+f"(d[8]), "+f"(d[9]), "+f"(d[10]), "+f"(d[11]), "+f"(d[12]), "+f"(d[13]), "+f"(d[14]), "+f"(d[15]),
      "+f"(d[16]), "+f"(d[17]), "+f"(d[18]), "+f"(d[19]), "+f"(d[20]), "+f"(d[21]), "+f"(d[22]), "+f"(d[23]),
      "+f"(d[24]), "+f"(d[25]), "+f"(d[26]), "+f"(d[27]), "+f"(d[28]), "+f"(d[29]), "+f"(d[30]), "+f"(d[31]),
      "+f"(d[32]), "+f"(d[33]), "+f"(d[34]), "+f"(d[35]), "+f"(d[36]), "+f"(d[37]), "+f"(d[38]), "+f"(d[39]),
      "+f"(d[40]), "+f"(d[41]), "+f"(d[42]), "+f"(d[43]), "+f"(d[44]), "+f"(d[45]), "+f"(d[46]), "+f"(d[47]),
      "+f"(d[48]), "+f"(d[49]), "+f"(d[50]), "+f"(d[51]), "+f"(d[52]), "+f"(d[53]), "+f"(d[54]), "+f"(d[55]),
      "+f"(d[56]), "+f"(d[57]), "+f"(d[58]), "+f"(d[59]), "+f"(d[60]), "+f"(d[61]), "+f"(d[62]), "+f"(d[63]),
      "+f"(d[64]), "+f"(d[65]), "+f"(d[66]), "+f"(d[67]), "+f"(d[68]), "+f"(d[69]), "+f"(d[70]), "+f"(d[71]),
      "+f"(d[72]), "+f"(d[73]), "+f"(d[74]), "+f"(d[75]), "+f"(d[76]), "+f"(d[77]), "+f"(d[78]), "+f"(d[79]),
      "+f"(d[80]), "+f"(d[81]), "+f"(d[82]), "+f"(d[83]), "+f"(d[84]), "+f"(d[85]), "+f"(d[86]), "+f"(d[87]),
      "+f"(d[88]), "+f"(d[89]), "+f"(d[90]), "+f"(d[91]), "+f"(d[92]), "+f"(d[93]), "+f"(d[94]), "+f"(d[95]),
      "+f"(d[96]), "+f"(d[97]), "+f"(d[98]), "+f"(d[99]), "+f"(d[100]), "+f"(d[101]), "+f"(d[102]), "+f"(d[103]),
      "+f"(d[104]), "+f"(d[105]), "+f"(d[106]), "+f"(d[107]), "+f"(d[108]), "+f"(d[109]), "+f"(d[110]), "+f"(d[111]),
      "+f"(d[112]), "+f"(d[113]), "+f"(d[114]), "+f"(d[115]), "+f"(d[116]), "+f"(d[117]), "+f"(d[118]), "+f"(d[119]),
      "+f"(d[120]), "+f"(d[121]), "+f"(d[122]), "+f"(d[123]), "+f"(d[124]), "+f"(d[125]), "+f"(d[126]), "+f"(d[127])
    : "r"(a0), "r"(a1), "r"(a2), "r"(a3), "l"(db), "r"(sd));
}
__device__ __forceinline__ void wgmma_rs_n64_tb(float (&d)[32], uint32_t a0, uint32_t a1, uint32_t a2, uint32_t a3, uint64_t db, int sd) {
  asm volatile("{\n.reg .pred p;\nsetp.ne.b32 p, %37, 0;\n"
    "wgmma.mma_async.sync.aligned.m64n64k16.f32.bf16.bf16 "
    "{%0, %1, %2, %3, %4, %5, %6, %7, %8, %9, %10, %11, %12, %13, %14, %15, "
    "%16, %17, %18, %19, %20, %21, %22, %23, %24, %25, %26, %27, %28, %29, %30, %31}, "
    "{%32, %33, %34, %35}, %36, p, 1, 1, 1;\n}"
    : "+f"(d[0]), "+f"(d[1]), "+f"(d[2]), "+f"(d[3]), "+f"(d[4]), "+f"(d[5]), "+f"(d[6]), "+f"(d[7]),
      "+f"(d[8]), "+f"(d[9]), "+f"(d[10]), "+f"(d[11]), "+f"(d[12]), "+f"(d[13]), "+f"(d[14]), "+f"(d[15]),
      "+f"(d[16]), "+f"(d[17]), "+f"(d[18]), "+f"(d[19]), "+f"(d[20]), "+f"(d[21]), "+f"(d[22]), "+f"(d[23]),
      "+f"(d[24]), "+f"(d[25]), "+f"(d[26]), "+f"(d[27]), "+f"(d[28]), "+f"(d[29]), "+f"(d[30]), "+f"(d[31])
    : "r"(a0), "r"(a1), "r"(a2), "r"(a3), "l"(db), "r"(sd));
}
__device__ __forceinline__ void wgmma_rs_n32(float (&d)[16], uint32_t a0, uint32_t a1, uint32_t a2, uint32_t a3, uint64_t db, int sd) {
  asm volatile("{\n.reg .pred p;\nsetp.ne.b32 p, %21, 0;\n"
    "wgmma.mma_async.sync.aligned.m64n32k16.f32.bf16.bf16 "
    "{%0, %1, %2, %3, %4, %5, %6, %7, %8, %9, %10, %11, %12, %13, %14, %15}, "
    "{%16, %17, %18, %19}, %20, p, 1, 1, 0;\n}"
    : "+f"(d[0]), "+f"(d[1]), "+f"(d[2]), "+f"(d[3]), "+f"(d[4]), "+f"(d[5]), "+f"(d[6]), "+f"(d[7]),
      "+f"(d[8]), "+f"(d[9]), "+f"(d[10]), "+f"(d[11]), "+f"(d[12]), "+f"(d[13]), "+f"(d[14]), "+f"(d[15])
    : "r"(a0), "r"(a1), "r"(a2), "r"(a3), "l"(db), "r"(sd));
}

__device__ __forceinline__ void sts16(uint32_t a, uint32_t x, uint32_t y, uint32_t z, uint32_t w) {
  asm volatile("st.shared.v4.u32 [%0], {%1, %2, %3, %4};" :: "r"(a), "r"(x), "r"(y), "r"(z), "r"(w) : "memory");
}
__device__ __forceinline__ uint32_t lds4(uint32_t a) { uint32_t v; asm volatile("ld.shared.u32 %0, [%1];" : "=r"(v) : "r"(a) : "memory"); return v; }
__device__ __forceinline__ uint32_t bmul(uint32_t a, uint32_t b) { uint32_t r; asm("mul.rn.bf16x2 %0, %1, %2;" : "=r"(r) : "r"(a), "r"(b)); return r; }
__device__ __forceinline__ uint32_t badd(uint32_t a, uint32_t b) { uint32_t r; asm("add.rn.bf16x2 %0, %1, %2;" : "=r"(r) : "r"(a), "r"(b)); return r; }

#define SIDE_AHEAD 3
#define ZERO_RD 4
#define STAGE1_NS 0
constexpr int EARLY_LD = 4;
constexpr int PP_BAR = 3;
template <int V> struct Int { static constexpr int value = V; };
struct Ring {
  uint32_t slot, phase;
  __device__ __forceinline__ void next() { if (++slot == NSLOT) { slot = 0; phase ^= 1; } }
};
__device__ __forceinline__ uint32_t bar_addr(uint32_t sb, uint32_t i) { return sb + BARS + 8 * i; }

__device__ __forceinline__ int kv_group(int g, int t) { return (g & 6) | (t & 1); }
__device__ __forceinline__ int kv_rows(int g, int t) { return (t & 14) | (g & 1); }
__device__ __forceinline__ void load_w(const Params& p, int g, int t, int it, uint32_t dst, uint32_t full) {
  if (it < 64) tma_ld3(dst, (it & 16) ? &p.wuv : &p.wuk, full, 0, (it & 15) * 64, (kv_group(g, t) + (it < 32 ? 8 : 0)) * 4);
  else tma_ld3(dst, &p.wq, full, 0, (it < 71 ? it - 64 : it - 71) * 64, (it < 71 ? g + 8 : g) * 4);
}
__device__ __forceinline__ void load_a(const Params& p, int g, int t, int it, uint32_t dst, uint32_t full) {
  if (it < 64) tma_ld2(dst, &p.ckv, full, (it & 15) * 64, kv_rows(g, t) * 128);
  else tma_ld2(dst, &p.x, full, (it < 71 ? it - 64 : it - 71) * 64, (it < 71 ? 15 - t : t) * 128);
}

__device__ __forceinline__ void producer_main(const Params& p, uint32_t sb, int g, int t) {
  const int rank = t & 1;
  Ring r{EARLY_LD, 0};
  auto wait_slot = [&]() { mbar_wait(bar_addr(sb, B_EMPTY + r.slot), r.phase ^ 1); };
  uint32_t prev = 0;
#pragma unroll 1
  for (int it = EARLY_LD; it < P1_STEPS; it++) {
    wait_slot();
    if (it > EARLY_LD && it <= P1_XS) load_a(p, g, t, it - 1, sb + QREG + ((it - 1) & 3) * 16384, prev);
    const uint32_t full = bar_addr(sb, B_FULL + r.slot);
    mbar_expect_tx(full, it < P1_XS ? 49152 : 32768);
    load_w(p, g, t, it, sb + r.slot * SLOT, full);
    prev = full;
    r.next();
    if (it == 50) mbar_arrive(bar_addr(sb, B_PF));
    if (it == P1_XS) {
      wait_slot();
      const uint32_t f2 = bar_addr(sb, B_FULL + r.slot);
      mbar_expect_tx(f2, 32768);
      load_a(p, g, t, P1_XS, sb + r.slot * SLOT, f2);
      load_a(p, g, t, P1_XS + 1, sb + r.slot * SLOT + 16384, f2);
      r.next();
    }
  }
  uint64_t once;
  asm volatile("createpolicy.fractional.L2::evict_first.b64 %0, 1.0;" : "=l"(once));
  const int na = 2 * t + 2, own = 2 * (t & ~1) + 2;
  mbar_wait(bar_addr(sb, B_KVOK), 0);
#pragma unroll 1
  for (int f = 0; f < 68; f++) {
    const bool isK = (f == 0) || ((f & 1) && f < 67);
    const int i = isK ? (f + 1) >> 1 : (f - 1) >> 1;
    wait_slot();
    const uint32_t full = bar_addr(sb, B_FULL + r.slot);
    mbar_expect_tx(full, 32768);
    const uint32_t src = (uint32_t)(((isK ? 0 : NH) + g) * 32 + (i >= na ? 8 * 32 + 33 - i : i)) * 32768;
    if ((i & ~1) != own) bulk_ld_mc(sb + r.slot * SLOT + rank * 16384, at<uint8_t>(g_kv, src + rank * 16384), 16384, full, once);
    else bulk_ld_p(sb + r.slot * SLOT, at<uint8_t>(g_kv, src), 32768, full, once);
    r.next();
  }
#pragma unroll 1
  for (int f = 0; f < 14; f++) {
    const int ch = f < 4 ? f & 1 : f >> 1, par = f < 4 ? f >> 1 : f & 1;
    wait_slot();
    const uint32_t full = bar_addr(sb, B_FULL + r.slot);
    mbar_expect_tx(full, 32768);
    tma_ld5_mc(sb + r.slot * SLOT + rank * 16384, &p.wo, full, ch * 64, (par ? g : g + 8) * 8 + rank * 4);
    r.next();
  }
}

__device__ __forceinline__ void helper_main(const Params& p, uint32_t sb, int g, int t, int w) {
  const unsigned epoch = load_epoch();
  const uint32_t qreg = sb + QREG + w * 32768, qfull = bar_addr(sb, B_QFULL + w);
  mbar_wait(bar_addr(sb, B_ST_KV + w), 0);
  flag_signal(flag_at(g_flags.kv_ready, kv_group(g, t)));
  if (w == 0) {
    flag_wait<20>(flag_at(g_flags.kv_ready, g), 32, epoch);
    fence_async_global();
    mbar_arrive(bar_addr(sb, B_KVOK));
  }
  mbar_wait(bar_addr(sb, B_ST_Q + w), 0);
  asm volatile("fence.release.gpu;" ::: "memory");
  fence_async_global();
  mbar_wait(bar_addr(sb, B_QFREE + w), 0);
  mbar_expect_tx(qfull, 32768);
  bulk_ld(qreg, at<uint8_t>(g_qc, ((g * 16 + t) * 2 + w) * 32768), 32768, qfull);
  auto publish = [&]() { mbar_wait(bar_addr(sb, B_ST_CTX + w), 0); flag_signal(flag_at(g_flags.ctx_ready, (g * 16 + t) * 2 + w)); };
  if (t < 8) publish();
  flag_wait<20>(flag_at(g_flags.ctx_ready, (g * 16 + 15 - t) * 2 + (w ^ 1)), 1, epoch);
  mbar_arrive(bar_addr(sb, B_CTXOK + w));
  mbar_arrive(bar_addr(sb, B_DONE));
  if (t >= 8) publish();
  flag_wait<20>(flag_at(g_flags.zero_ready, 15 - t), 8, epoch);
  fence_async_global();
#pragma unroll 1
  for (int ch = 0; ch < 6; ch++) {
    mbar_wait(bar_addr(sb, B_S2_FULL + w * 4 + (ch & 3)), ch >> 2);
    tma_red2(&p.o, qreg + (ch & 3) * 8192, DA + ch * 64, (15 - t) * 128 + (w ^ 1) * 64);
    bulk_commit();
    if (ch < 3) { bulk_wait_read(); mbar_arrive(bar_addr(sb, B_S2_EMPTY + w * 4 + ch)); }
  }
  bulk_wait_read();
  GT(48 + w);
}

__device__ __forceinline__ void store_block(uint32_t base, uint32_t lanebase, const uint32_t (&pk)[16]) {
#pragma unroll
  for (int J = 0; J < 8; J += 2) stsm4(base + (lanebase ^ (J << 4)), pk[2 * J], pk[2 * J + 1], pk[2 * J + 2], pk[2 * J + 3]);
}
__device__ __forceinline__ void pack_chunks(uint32_t (&pk)[64], const float (&acc)[128]) {
#pragma unroll
  for (int i = 0; i < 64; i++) { const int e = 16 * (i >> 3) + 4 * (i & 3) + 2 * ((i >> 2) & 1); pk[i] = pack_bf16(acc[e], acc[e + 1]); }
}
__device__ __forceinline__ uint32_t chunk_off() { const uint32_t t = fresh_tid(); return (t & 96) * 32 + (t & 28) * 16 + (((t ^ (t >> 3)) & 3) << 4); }
__device__ __forceinline__ void warp_arrive(uint32_t bar, int lane) { __syncwarp(); if (lane == 0) mbar_arrive(bar); }

__device__ __forceinline__ void consumer_main(const Params& p, uint32_t sb, int g, int t, int w, int wq) {
  const int lane = threadIdx.x & 31;
  const int rank = t & 1;

  auto turn_begin = [&]() { named_sync(PP_BAR + w, 256); };
  auto turn_end = [&]() { named_arrive(PP_BAR + (w ^ 1), 256); };
  Ring r{0, 0};
  auto take = [&](uint32_t ready = 0) { const uint32_t sl = r.slot; mbar_wait_unless(ready, bar_addr(sb, B_FULL + sl), r.phase); r.next(); return sl; };
  uint32_t rdy0 = 0, rdy1 = 0;
  auto peek2 = [&]() { Ring q = r; rdy0 = mbar_test(bar_addr(sb, B_FULL + q.slot), q.phase); q.next(); rdy1 = mbar_test(bar_addr(sb, B_FULL + q.slot), q.phase); };
  auto give = [&](uint32_t sl) { if (lane < 2) mbar_arrive_remote(bar_addr(sb, B_EMPTY + sl), rank ^ lane); };
  float acc[128];
#pragma unroll
  for (int i = 0; i < 128; i++) acc[i] = 0.f;
  uint32_t pk[64];
#pragma unroll
  for (int i = 0; i < 64; i++) pk[i] = 0;
  reg_fence(acc);
  reg_fence(pk);
  cluster_wait();
  TS(0);
  const uint32_t qreg = sb + QREG + w * 32768;
  {
    uint32_t xs = 0;
    uint4* row = nullptr;
    int it = 0;
#pragma unroll 1
    for (int tile = 0; tile < 6; tile++) {
      const bool isq = tile >= 4;
      const uint32_t abase = sb + QREG + (w ^ (tile == 4)) * 8192;
#pragma unroll 1
      for (int u = 0; u < (isq ? 4 : 8); u++) {
        const bool two = !(isq && u == 1), last = it == P1_XS;
        const uint32_t w0 = take(rdy0);
        TSC(1, it == 0);
        if (last) { xs = take(rdy1); rdy1 = 0; }
        const uint32_t xb = sb + xs * SLOT + w * 8192;
        const uint64_t da = desc_k(last ? xb : abase + (it & 3) * 16384), db = desc_mn(sb + w0 * SLOT);
        turn_begin();
        wg_fence();
#pragma unroll
        for (int kk = 0; kk < 4; kk++) wgmma_ss_n256_tb(acc, desc_add(da, kk * 32), desc_add(db, kk * 2048), (u | kk) != 0);
        wg_commit();
        uint32_t w1 = w0;
        if (two) {
          w1 = take(rdy1);
          const uint64_t da1 = desc_k(last ? xb + 16384 : abase + ((it + 1) & 3) * 16384), db1 = desc_mn(sb + w1 * SLOT);
          wg_fence();
#pragma unroll
          for (int kk = 0; kk < 4; kk++) wgmma_ss_n256_tb(acc, desc_add(da1, kk * 32), desc_add(db1, kk * 2048), 1);
          wg_commit();
          turn_end();
          wg_wait<1>();
          give(w0);
        } else {
          turn_end();
        }
        if (tile > 0) {
          uint32_t m = isq ? 0xC0380403u >> (8 * u) : 1u << u;
          asm volatile("" : "+r"(m));
#pragma unroll
          for (int i = 0; i < 16; i++)
            if (m & (1u << (i >> 1))) row[(i >> 1) * 256 + (i & 1) * 32] = make_uint4(pk[4 * i], pk[4 * i + 1], pk[4 * i + 2], pk[4 * i + 3]);
        }
        peek2();
        wg_wait<0>();
        give(w1);
        it += 1 + two;
      }
      reg_fence(acc);
      if (isq) warp_arrive(bar_addr(sb, (tile == 4 ? B_ST_KV : B_ST_Q) + w), lane);
      pack_chunks(pk, acc);
      row = at<uint4>(isq ? (const void*)g_qc : (const void*)g_kv, chunk_off() +
                      (uint32_t)(isq ? (g * 16 + t) * 2 + w : ((tile & 1) * NH + kv_group(g, t) + (tile < 2 ? 8 : 0)) * 32 + kv_rows(g, t) * 2 + w) * 32768);
      TS(2 + tile);
    }
    give(xs);
    const uint32_t qa = qreg + chunk_off();
#pragma unroll
    for (int i = 0; i < 16; i++) sts16(qa + (i >> 1) * 4096 + (i & 1) * 512, pk[4 * i], pk[4 * i + 1], pk[4 * i + 2], pk[4 * i + 3]);
    fence_async_smem();
  }
  TS(8);

  constexpr float SC = 0.0625f * 1.4426950408889634f;
#pragma unroll 1
  for (int which = 0; which < 2; which++) {
    float s[32];
#pragma unroll
    for (int i = 0; i < 32; i++) s[i] = 0.f;
    uint32_t pa[16], pb[16];
    float m0 = 0.f, m1 = 0.f, l0 = 0.f, l1 = 0.f;
    const uint64_t dq = desc_64(qreg);
    uint64_t dk = 0, dqq = 0, dv = 0;
    auto prep_qk = [&](uint32_t kaddr) { dk = desc_64(kaddr); dqq = dq + (kaddr >> 31); asm volatile("" : "+l"(dk), "+l"(dqq)); };
    auto prep_pv = [&](uint32_t vaddr) { dv = desc_64(vaddr); asm volatile("" : "+l"(dv)); };
    auto issue_qk = [&]() {
#pragma unroll
      for (int kk = 0; kk < 16; kk++)
        wgmma_ss_n64(s, desc_add(dqq, (kk >> 1) * 4096 + (kk & 1) * 32), desc_add(dk, (kk >> 1) * 4096 + (kk & 1) * 32), kk != 0);
    };
    auto issue_pv = [&](int accumulate) {
#pragma unroll
      for (int kk = 0; kk < 4; kk++)
        wgmma_rs_n256_tb(acc, pa[4 * kk], pa[4 * kk + 1], pa[4 * kk + 2], pa[4 * kk + 3], desc_add(dv, kk * 1024), accumulate | kk);
    };
    auto mask_diag = [&]() {
      const int d = 16 * wq + (lane >> 2) - 2 * (lane & 3);
#pragma unroll
      for (int jj = 0; jj < 8; jj++) {
        if (8 * jj > d)     { s[4 * jj] = -INFINITY;     if (jj < 7) s[4 * jj + 6] = -INFINITY; }
        if (8 * jj + 1 > d) { s[4 * jj + 1] = -INFINITY; if (jj < 7) s[4 * jj + 7] = -INFINITY; }
      }
    };
    float a0, a1;
    auto softmax = [&]() -> bool {
      float x0 = fmaxf(s[0], s[1]), x1 = fmaxf(s[2], s[3]);
#pragma unroll
      for (int jj = 1; jj < 8; jj++) {
        x0 = fmaxf(x0, fmaxf(s[4 * jj], s[4 * jj + 1]));
        x1 = fmaxf(x1, fmaxf(s[4 * jj + 2], s[4 * jj + 3]));
      }
      x0 = fmaxf(x0, __shfl_xor_sync(0xffffffffu, x0, 1));
      x1 = fmaxf(x1, __shfl_xor_sync(0xffffffffu, x1, 1));
      x0 = fmaxf(x0, __shfl_xor_sync(0xffffffffu, x0, 2));
      x1 = fmaxf(x1, __shfl_xor_sync(0xffffffffu, x1, 2));
      const bool grow = __any_sync(0xffffffffu, fmaxf(x0 - m0, x1 - m1) * SC > 8.f);
      if (grow) {
        x0 = fmaxf(x0, m0); x1 = fmaxf(x1, m1);
        a0 = ex2((m0 - x0) * SC); a1 = ex2((m1 - x1) * SC);
        m0 = x0; m1 = x1;
        l0 *= a0; l1 *= a1;
      }
      const float b0 = -m0 * SC, b1 = -m1 * SC;
      float t0 = 0.f, t1 = 0.f, t2 = 0.f, t3 = 0.f;
#pragma unroll
      for (int jj = 0; jj < 8; jj++) {
        s[4 * jj]     = ex2(fmaf(s[4 * jj], SC, b0));
        s[4 * jj + 1] = ex2(fmaf(s[4 * jj + 1], SC, b0));
        s[4 * jj + 2] = ex2(fmaf(s[4 * jj + 2], SC, b1));
        s[4 * jj + 3] = ex2(fmaf(s[4 * jj + 3], SC, b1));
        t0 += s[4 * jj]; t1 += s[4 * jj + 1]; t2 += s[4 * jj + 2]; t3 += s[4 * jj + 3];
      }
      l0 += t0 + t1; l1 += t2 + t3;
      return grow;
    };
    auto softmax_fast = [&](uint32_t (&pp)[16], auto first, auto hook) -> bool {
      const float b0 = -m0 * SC, b1 = -m1 * SC;
      float t0 = 0.f, t1 = 0.f, t2 = 0.f, t3 = 0.f;
#pragma unroll
      for (int jj = 0; jj < 8; jj++) {
        const float e0 = ex2(fmaf(s[4 * jj], SC, b0)), e1 = ex2(fmaf(s[4 * jj + 1], SC, b0));
        const float e2 = ex2(fmaf(s[4 * jj + 2], SC, b1)), e3 = ex2(fmaf(s[4 * jj + 3], SC, b1));
        hook(jj, e0);
        pp[2 * jj] = pack_bf16(e0, e1); pp[2 * jj + 1] = pack_bf16(e2, e3);
        if (jj == 0) { t0 = e0; t1 = e1; t2 = e2; t3 = e3; } else { t0 += e0; t1 += e1; t2 += e2; t3 += e3; }
      }
      t0 += t1; t2 += t3;
      bool redo = __any_sync(0xffffffffu, !(t0 + t2 <= 16777216.f));
      if (decltype(first)::value) {
        uint32_t u0 = __ballot_sync(0xffffffffu, t0 >= 1.52587890625e-05f), u1 = __ballot_sync(0xffffffffu, t2 >= 1.52587890625e-05f);
        u0 |= u0 >> 1; u1 |= u1 >> 1;
        redo |= (((u0 | (u0 >> 2)) & (u1 | (u1 >> 2))) & 0x11111111u) != 0x11111111u;
      }
      if (!redo) { l0 += t0; l1 += t2; }
      return redo;
    };
    auto rescale = [&]() {
#pragma unroll
      for (int i = 0; i < 32; i++) { acc[4 * i] *= a0; acc[4 * i + 1] *= a0; acc[4 * i + 2] *= a1; acc[4 * i + 3] *= a1; }
    };
    auto to_p = [&](uint32_t (&pp)[16]) {
#pragma unroll
      for (int i = 0; i < 16; i++) pp[i] = pack_bf16(s[2 * i], s[2 * i + 1]);
    };
    auto q_free = [&]() { if (lane == 0) mbar_arrive(bar_addr(sb, B_QFREE + w)); };

    const int n = 2 * (which ? 15 - t : t) + 1 + (w ^ which);
    uint32_t ks = take(rdy0);
    TS(9 + 5 * which);
    prep_qk(sb + ks * SLOT);
    turn_begin();
    TS(20 + 10 * which);
    wg_fence();
    issue_qk();
    wg_commit();
    turn_end();
    if (which == 1) give(take(rdy1));
    TS(22 + 10 * which);
    wg_wait<0>();
    TS(21 + 10 * which);
    reg_fence(s);
    give(ks);
    if (which == 0 && n == 1) q_free();
    if (which == 1 || n == 1) mask_diag();
    {
      const uint4* dst = at<uint4>(g_qc, (uint32_t)((g * 16 + t) * 2 + w) * 32768 + (fresh_tid() & 127) * 16);
      const bool redo = softmax_fast(pa, Int<1>(), [&](int jj, float e) {
        if (jj == 7) peek2();
        const int i = 8 + jj;
        asm volatile("{\n.reg .pred p, q;\nsetp.ne.b32 q, %6, 0;\nsetp.geu.and.f32 p, %5, 0fBF800000, q;\n@p st.global.v4.u32 [%0], {%1, %2, %3, %4};\n}"
                       :: "l"(dst + i * 128), "r"(pk[4 * i]), "r"(pk[4 * i + 1]), "r"(pk[4 * i + 2]), "r"(pk[4 * i + 3]), "f"(e), "r"(which) : "memory");
      });
      if (redo) {
        m0 = -INFINITY; m1 = -INFINITY;
        softmax();
        to_p(pa);
      }
    }
    if (which == 1) warp_arrive(bar_addr(sb, B_ST_CTX + w), lane);
    TS(10 + 5 * which);
#pragma unroll 1
    for (int jj = 1; jj < n; jj++) {
      ks = take(rdy0);
      const uint32_t vs = take(rdy1);
      prep_qk(sb + ks * SLOT);
      prep_pv(sb + vs * SLOT);
      TSC(23 + 10 * which, jj == 1);
      turn_begin();
      TSC(24 + 10 * which, jj == 1);
      TSC(26 + 10 * which, jj == n - 1);
      wg_fence();
      issue_qk();
      wg_commit();
      issue_pv(jj > 1);
      wg_commit();
      turn_end();
      wg_wait<1>();
      TSC(25 + 10 * which, jj == 1);
      reg_fence(s);
      give(ks);
      if (jj == n - 1 && which == 0) { q_free(); mask_diag(); }
      if (softmax_fast(pb, Int<0>(), [](int, float) {})) {
        wg_wait<0>();
        reg_fence(acc);
        if (softmax()) rescale();
        to_p(pb);
      }
      peek2();
      wg_wait<0>();
      reg_fence(acc);
      reg_fence(pa);
      give(vs);
#pragma unroll
      for (int i = 0; i < 16; i++) pa[i] = pb[i] | (vs >> 8);
    }
    TS(11 + 5 * which);
    if (which == 0) { give(take(rdy0)); rdy0 = rdy1; }
    {
      const uint32_t vs = take(rdy0);
      prep_pv(sb + vs * SLOT);
      TS(27 + 10 * which);
      turn_begin();
      TS(28 + 10 * which);
      wg_fence();
      issue_pv(n > 1);
      wg_commit();
      turn_end();
      l0 += __shfl_xor_sync(0xffffffffu, l0, 1); l1 += __shfl_xor_sync(0xffffffffu, l1, 1);
      l0 += __shfl_xor_sync(0xffffffffu, l0, 2); l1 += __shfl_xor_sync(0xffffffffu, l1, 2);
      asm("rcp.approx.ftz.f32 %0, %0;" : "+f"(l0));
      asm("rcp.approx.ftz.f32 %0, %0;" : "+f"(l1));
      peek2();
      if (which == 0) mbar_wait(bar_addr(sb, B_QFULL + w), 0);
      wg_wait<0>();
      reg_fence(acc);
      reg_fence(pa);
      give(vs);
    }
    TS(12 + 5 * which);
    {
      const uint4* dst = at<uint4>(g_qc, (uint32_t)((g * 16 + t) * 2 + w) * 32768 + (fresh_tid() & 127) * 16);
#pragma unroll
      for (int i = 0; i < 16; i++) {
        const int c = (i & 1) ? (i >> 1) + 8 : i >> 1;
        pk[4 * c]     = pack_bf16(acc[8 * c] * l0, acc[8 * c + 1] * l0);
        pk[4 * c + 1] = pack_bf16(acc[8 * c + 2] * l1, acc[8 * c + 3] * l1);
        pk[4 * c + 2] = pack_bf16(acc[8 * c + 4] * l0, acc[8 * c + 5] * l0);
        pk[4 * c + 3] = pack_bf16(acc[8 * c + 6] * l1, acc[8 * c + 7] * l1);
        if (c < 8)
          asm volatile("{\n.reg .pred p;\nsetp.eq.b32 p, %5, 0;\n@p st.global.v4.u32 [%0], {%1, %2, %3, %4};\n}"
                       :: "l"(dst + c * 128), "r"(pk[4 * c]), "r"(pk[4 * c + 1]), "r"(pk[4 * c + 2]), "r"(pk[4 * c + 3]), "r"(which) : "memory");
      }
    }
    TS(13 + 5 * which);
  }

  {
    float oa[32], ob[32];
#pragma unroll
    for (int i = 0; i < 32; i++) { oa[i] = 0.f; ob[i] = 0.f; }
    uint32_t pk2[64];
    auto stage = [&](float (&o)[32], int ch) {
      reg_fence(o);
      uint32_t q[16];
#pragma unroll
      for (int i = 0; i < 16; i++) q[i] = pack_bf16(o[2 * i], o[2 * i + 1]);
      if (ch >= 4) mbar_wait(bar_addr(sb, B_S2_EMPTY + w * 4 + (ch & 3)), 0);
      store_block(qreg + (ch & 3) * 8192, lane_base16(), q);
    };
    auto hand_over = [&](int ch) {
      fence_async_smem();
      warp_arrive(bar_addr(sb, B_S2_FULL + w * 4 + (ch & 3)), lane);
    };
    uint32_t prev = 0;
    auto half = [&](int f, float (&o)[32], uint32_t (&a)[64], int accumulate) {
      const uint32_t sl = take(rdy0);
      const uint64_t d = desc_mn(sb + sl * SLOT);
      turn_begin();
      TS(40 + f);
      wg_fence();
#pragma unroll
      for (int kk = 0; kk < 16; kk++) {
        wgmma_rs_n64_tb(o, a[4 * kk], a[4 * kk + 1], a[4 * kk + 2], a[4 * kk + 3], desc_add(d, kk * 2048), accumulate | kk);
        if (kk == 12 && (f < 13 || w == 0)) turn_end();
      }
      wg_commit();
      if (f < 13) rdy0 = mbar_test(bar_addr(sb, B_FULL + r.slot), r.phase);
      wg_wait<1>();
      if (f >= 1 && f <= 9) give(prev);
      prev = sl;
    };
    auto load_ctx = [&](auto h0) {
      constexpr int I0 = decltype(h0)::value * 8, NL = 8;
      const uint4* src = at<const uint4>(g_qc, (uint32_t)((g * 16 + 15 - t) * 2 + (w ^ 1)) * 32768 + (fresh_tid() & 127) * 16);
#pragma unroll
      for (int i = I0; i < I0 + NL; i++) { const uint4 v = __ldcg(src + i * 128); pk2[4 * i] = v.x; pk2[4 * i + 1] = v.y; pk2[4 * i + 2] = v.z; pk2[4 * i + 3] = v.w; }
    };
    half(0, oa, pk, 0);
    mbar_wait(bar_addr(sb, B_CTXOK + w), 0);
    load_ctx(Int<0>());
    half(1, ob, pk, 0);
    load_ctx(Int<1>());
    half(2, oa, pk2, 1);
#pragma unroll 1
    for (int i = 0; i < 3; i++) {
      half(4 * i + 3, ob, pk2, 1);
      if (i == 0) stage(oa, 0);
      half(4 * i + 4, oa, pk, 0);
      if (i == 0) hand_over(0);
      stage(ob, 2 * i + 1);
      hand_over(2 * i + 1);
      half(4 * i + 5, oa, pk2, 1);
      if (i == 2) break;
      half(4 * i + 6, ob, pk, 0);
      stage(oa, 2 * i + 2);
      hand_over(2 * i + 2);
    }
    wg_wait<0>();
    reg_fence(pk);
    reg_fence(pk2);
    stage(oa, 6);
    fence_async_smem();
    named_sync(1 + w, 128);
    if (wq == 0 && lane == 0) {
      tma_red2(&p.o, qreg + 2 * 8192, DA + 6 * 64, (15 - t) * 128 + (w ^ 1) * 64);
      bulk_commit();
      bulk_wait_read();
    }
  }
  TS(19);
  TDUMP();
}

namespace ssm {
constexpr int NCH = DA / NCONV;
constexpr int NS = 8, NP = 6;
constexpr uint32_t X0 = 384;
constexpr uint32_t HO = X0 + 4096;
constexpr uint32_t HE = HO + HO_STRIDE + 64;
constexpr uint32_t SSLOT = HE + 4096 + 64;
constexpr uint32_t PART = 264 * 16;
constexpr uint32_t OFF_P = NS * SSLOT, OFF_D = OFF_P + NP * 4 * PART, END = OFF_D + NCH * 4;
static_assert(SSLOT % 128 == 0 && HO % 128 == 0 && END <= BARS, "smem");
enum : uint32_t { B_FULL = 0, B_EMPTY = NS, B_PFULL = 2 * NS, B_PEMPTY = 2 * NS + NP };
__device__ __forceinline__ int channel(int cidx, int i) { return (i >> 4) * 64 + cidx * 16 + (i & 15); }

__device__ __forceinline__ void producer(const Params& p, uint32_t sb, int cidx, unsigned epoch) {
#pragma unroll 1
  for (int i = 0; i < NCH; i++) {
    const int s = i % NS, ch = channel(cidx, i);
    const uint32_t full = bar_addr(sb, B_FULL + s), dst = sb + s * SSLOT;
    mbar_wait(bar_addr(sb, B_EMPTY + s), ((i / NS) & 1) ^ 1);
    mbar_expect_tx(full, 4096 + 4128 + 4096);
    bulk_ld(dst + HE, at<uint8_t>(p.a_ssmk, ch * 4096), 4096, full);
    if ((i & 15) == 0) { flag_wait<20>(flag_at(g_flags.x_ready, i >> 4), NMAIN, epoch); fence_async_global(); }
    bulk_ld(dst + HO, at<uint8_t>(g_ho, ch * HO_STRIDE), 4128, full);
    bulk_ld(dst + X0, at<uint8_t>(g_xs, ch * 4096), 4096, full);
  }
}

__device__ __forceinline__ void reducer(uint32_t sb, int cidx, int rw) {
  uint32_t n = 0;
#pragma unroll 1
  for (int i = rw; i < NCH; i += 3, n++) {
    const uint32_t b = rw + 3 * (n & 1), pb = sb + OFF_P + b * 4 * PART;
    uint8_t* dst = at<uint8_t>(g_xs, channel(cidx, i) * 4096);
    mbar_wait(bar_addr(sb, B_PFULL + b), (n >> 1) & 1);
    asm volatile("cp.async.bulk.global.shared::cta.bulk_group [%0], [%1], 4096;" :: "l"(dst), "r"(pb + 3 * PART) : "memory");
    bulk_commit();
    bulk_wait_all();
#pragma unroll
    for (int k = 2; k >= 0; k--)
      asm volatile("cp.reduce.async.bulk.global.shared::cta.bulk_group.add.noftz.bf16 [%0], [%1], 4096;" :: "l"(dst), "r"(pb + k * PART) : "memory");
    bulk_commit();
    bulk_wait_read();
    mbar_arrive(bar_addr(sb, B_PEMPTY + b));
    if (((i + 3) >> 4) != (i >> 4)) {
      bulk_wait_all();
      fence_async_global();
      flag_signal(flag_at(g_flags.z_ready, i >> 4));
    }
  }
}

__device__ __forceinline__ void mma_warpgroup(uint32_t sb, int w) {
  const int lane = threadIdx.x & 31, g = lane >> 2, c = lane & 3, wq = (threadIdx.x >> 5) & 3;
  const uint32_t aoff = ((g & 1) ? HO + 30 : HE) + (16 * wq - g + 2 * c) * 2;
  const uint32_t poff = OFF_P + wq * PART + (2 * wq + lane) * 16;
  const uint32_t dmask = (wq == 0 && c == (g >> 1)) ? ((g & 1) ? 0xffff0000u : 0xffffu) : 0u;
  float acc[8][16];
  uint32_t fa[16][4];
#pragma unroll
  for (int e = 0; e < 8; e++)
#pragma unroll
    for (int i = 0; i < 16; i++) acc[e][i] = 0.f;
  auto load_a = [&](int m, uint32_t ad) {
    fa[m][0] = lds4(ad + m * 256 + 16); fa[m][1] = lds4(ad + m * 256 + 144); fa[m][2] = lds4(ad + m * 256); fa[m][3] = lds4(ad + m * 256 + 128);
  };
  if (w == 1) named_arrive(PP_BAR, 256);
  mbar_wait(bar_addr(sb, B_FULL + w), 0);
#pragma unroll
  for (int m = 0; m < 16; m++) load_a(m, sb + w * SSLOT + aoff);
  uint32_t dd = lds4(sb + OFF_D + w * 4);
  if (threadIdx.x == 128) { GT(12); PT(10); }
  uint32_t pb = w, pphase = 1;
#pragma unroll 1
  for (int i = w; i < NCH; i += 2) {
    fa[0][2] = badd(fa[0][2], dd & dmask);
    const uint64_t db = (uint64_t)((((sb + (i % NS) * SSLOT + X0 - 16) & 0x3FFFF) >> 4) | (1u << 16)) | ((uint64_t)8 << 32);
    named_sync(PP_BAR + w, 256);
    wg_fence();
#pragma unroll
    for (int r = 0; r < 16; r++) {
      auto mm = [&](int e, int m) { wgmma_rs_n32(acc[e], fa[m][0], fa[m][1], fa[m][2], fa[m][3], db + (int64_t)(32 * e - 16 * m), m != 0); };
      mm(7, r);
      if (r < 14) mm(6, r); else mm(0, r - 14);
      if (r < 12) mm(5, r); else mm(1, r - 12);
      if (r < 10) mm(4, r); else mm(2, r - 10);
      if ((r & 1) == 0) mm(3, r >> 1);
      if (r == 13 && (i + 1 < NCH)) named_arrive(PP_BAR + (w ^ 1), 256);
    }
    wg_commit();
    const int nx = i + 2 < NCH ? i + 2 : i;
    mbar_wait(bar_addr(sb, B_FULL + nx % NS), (nx / NS) & 1);
    mbar_wait(bar_addr(sb, B_PEMPTY + pb), pphase);
    const uint32_t ad = sb + (nx % NS) * SSLOT + aoff, pa = sb + pb * 4 * PART + poff;
    wg_wait<0>();
#pragma unroll
    for (int e = 0; e < 8; e++) reg_fence(acc[e]);
#pragma unroll
    for (int m = 0; m < 16; m++) reg_fence(fa[m]);
    if (lane == 0) mbar_arrive(bar_addr(sb, B_EMPTY + i % NS));
#pragma unroll
    for (int e = 0; e < 8; e++) {
      load_a(e, ad);
      uint32_t u[4];
#pragma unroll
      for (int j = 0; j < 4; j++) {
        const int T = 4 * e + j, U = T - 1;
        float lo = acc[e][4 * j], hi = acc[e][4 * j + 1];
        if (T > 0) { lo += acc[U >> 2][4 * (U & 3) + 2]; hi += acc[U >> 2][4 * (U & 3) + 3]; }
        u[j] = pack_bf16(lo, hi);
      }
      asm volatile("stmatrix.sync.aligned.m8n8.x4.trans.shared.b16 [%0], {%1, %2, %3, %4};" :: "r"(pa + e * 512), "r"(u[0]), "r"(u[1]), "r"(u[2]), "r"(u[3]) : "memory");
    }
    dd = lds4(sb + OFF_D + nx * 4);
#pragma unroll
    for (int m = 8; m < 12; m++) load_a(m, ad);
    fence_async_smem();
    warp_arrive(bar_addr(sb, B_PFULL + pb), lane);
#pragma unroll
    for (int m = 12; m < 16; m++) load_a(m, ad);
    pb += 2;
    if (pb >= NP) { pb -= NP; pphase ^= 1; }
  }
  if (threadIdx.x == 128) { PT(9); GT(13); }
}

__device__ __forceinline__ void init(const Params& p, uint32_t sb, int cidx) {
  const uint32_t t = threadIdx.x;
  if (t < NCH) {
    const uint32_t d = (uint32_t)__ldg(reinterpret_cast<const unsigned short*>(p.a_D + channel(cidx, t))) * 0x10001u;
    asm volatile("st.shared.u32 [%0], %1;" :: "r"(sb + OFF_D + t * 4), "r"(d) : "memory");
  }
#pragma unroll 1
  for (uint32_t u = t; u < NS * 32; u += 128) {
    const uint32_t r = u & 31;
    if (r < 28) sts16(sb + (u >> 5) * SSLOT + (r < 24 ? r * 16 : HE - 64 + (r - 24) * 16), 0, 0, 0, 0);
    if (u < NP * 32) sts16(sb + OFF_P + (u >> 3) * PART + (u & 7) * 16, 0, 0, 0, 0);
  }
  if (t == 0) {
    for (int i = 0; i < NS; i++) { mbar_init(bar_addr(sb, B_FULL + i), 1); mbar_init(bar_addr(sb, B_EMPTY + i), 4); }
    for (int i = 0; i < NP; i++) { mbar_init(bar_addr(sb, B_PFULL + i), 4); mbar_init(bar_addr(sb, B_PEMPTY + i), 1); }
  }
  fence_async_smem();
}

__device__ __forceinline__ void side_prepare(const Params& p, int cta, int rd) {
  const int lane = threadIdx.x & 31, t0 = 16 * cta + 8 * (lane & 1);
#pragma unroll 1
  for (int ch = 64 * rd + (lane & ~1); ch < 64 * rd + 64; ch += 32) {
    const uint4 sv = __ldg(at<const uint4>(p.a_shift, ch * 8));
    const uint32_t* kp = at<const uint32_t>(p.a_k, (t0 * DA + ch) * 2);
    const uint32_t* vp = at<const uint32_t>(p.a_v, (t0 * DA + ch) * 2);
    uint32_t k0 = 0, k1 = 0, k2 = 0, kk[8], x[8];
    if (t0 > 0) { k0 = __ldg(kp - 3 * (DA / 2)); k1 = __ldg(kp - 2 * (DA / 2)); k2 = __ldg(kp - DA / 2); }
#pragma unroll
    for (int i = 0; i < 8; i++) { kk[i] = __ldg(kp + i * (DA / 2)); x[i] = __ldg(vp + i * (DA / 2)); }
    const uint32_t sh0 = __byte_perm(sv.x, sv.z, 0x5410), sh1 = __byte_perm(sv.x, sv.z, 0x7632);
    const uint32_t sh2 = __byte_perm(sv.y, sv.w, 0x5410), sh3 = __byte_perm(sv.y, sv.w, 0x7632);
#pragma unroll
    for (int i = 0; i < 8; i++) {
      uint32_t ks = bmul(k0, sh3);
      ks = badd(ks, bmul(k1, sh2)); ks = badd(ks, bmul(k2, sh1)); ks = badd(ks, bmul(kk[i], sh0));
      x[i] = bmul(ks, x[i]);
      k0 = k1; k1 = k2; k2 = kk[i];
    }
    uint4* dst = at<uint4>(g_xs, ch * 4096 + t0 * 2);
    dst[0]   = make_uint4(__byte_perm(x[7], x[6], 0x5410), __byte_perm(x[5], x[4], 0x5410), __byte_perm(x[3], x[2], 0x5410), __byte_perm(x[1], x[0], 0x5410));
    dst[256] = make_uint4(__byte_perm(x[7], x[6], 0x7632), __byte_perm(x[5], x[4], 0x7632), __byte_perm(x[3], x[2], 0x7632), __byte_perm(x[1], x[0], 0x7632));
  }
  {
    const int hc = 64 * rd + (cta >> 1), r0 = (cta & 1) * 128 + lane;
    const uint4* src = at<const uint4>(p.a_ssmk, hc * 4096 + r0 * 16);
    uint4* dst = at<uint4>(g_ho, hc * HO_STRIDE + r0 * 16);
    uint4 w[4];
    uint32_t nx[4];
#pragma unroll
    for (int i = 0; i < 4; i++) { w[i] = __ldg(src + 32 * i); nx[i] = r0 + 32 * i < 255 ? __ldg(reinterpret_cast<const uint32_t*>(src + 32 * i + 1)) : 0u; }
#pragma unroll
    for (int i = 0; i < 4; i++)
      dst[32 * i + 2] = make_uint4(__byte_perm(w[i].x, w[i].y, 0x5432), __byte_perm(w[i].y, w[i].z, 0x5432), __byte_perm(w[i].z, w[i].w, 0x5432), __byte_perm(w[i].w, nx[i], 0x5432));
    const uint32_t h0 = __shfl_sync(0xffffffffu, w[0].x, 0);
    if (r0 < 2) dst[0] = make_uint4(0, 0, 0, r0 ? h0 << 16 : 0u);
  }
  __syncwarp();
  if (lane == 0) flag_signal(flag_at(g_flags.x_ready, rd));
}
__device__ __forceinline__ void side_finish(const Params& p, int cta, int rd) {
  const int lane = threadIdx.x & 31, t0 = 16 * cta + 8 * (lane & 1);
#pragma unroll 1
  for (int ch = 64 * rd + (lane & ~1); ch < 64 * rd + 64; ch += 32) {
    const uint4* src = at<const uint4>(g_xs, ch * 4096 + t0 * 2);
    const uint32_t* qp = at<const uint32_t>(p.a_q, (t0 * DA + ch) * 2);
    uint32_t* op = at<uint32_t>(p.out, (t0 * OUTW + ch) * 2);
    const uint4 z0 = __ldcg(src), z1 = __ldcg(src + 256);
    uint32_t q[8];
#pragma unroll
    for (int i = 0; i < 8; i++) q[i] = __ldg(qp + i * (DA / 2));
    const uint32_t a[4] = {z0.w, z0.z, z0.y, z0.x}, b[4] = {z1.w, z1.z, z1.y, z1.x};
#pragma unroll
    for (int i = 0; i < 4; i++) {
      op[(2 * i) * (OUTW / 2)]     = bmul(q[2 * i], __byte_perm(a[i], b[i], 0x7632));
      op[(2 * i + 1) * (OUTW / 2)] = bmul(q[2 * i + 1], __byte_perm(a[i], b[i], 0x5410));
    }
  }
}
__device__ __forceinline__ void clear_rows(const Params& p, int qt, int part) {
  const int lane = threadIdx.x & 31;
  if (lane < 28) {
    uint4* z = at<uint4>(p.out, ((qt * 128 + part * 16) * OUTW + DA) * 2 + lane * 16);
#pragma unroll
    for (int i = 0; i < 32; i++) z[(i >> 1) * (OUTW / 8) + (i & 1) * 28] = make_uint4(0, 0, 0, 0);
  }
  __syncwarp();
  if (lane == 0) flag_signal(flag_at(g_flags.zero_ready, qt));
}
__device__ __forceinline__ void side_work(const Params& p, int cta, unsigned epoch) {
#pragma unroll 1
  for (int rd = -SIDE_AHEAD; rd < 7; rd++) {
    if (rd >= 0) {
      if ((threadIdx.x & 31) == 0) flag_wait<1000>(flag_at(g_flags.z_ready, rd), 3 * NCONV, epoch);
      __syncwarp();
    }
    if (rd + SIDE_AHEAD < 7) side_prepare(p, cta, rd + SIDE_AHEAD);
    if (rd >= 0) side_finish(p, cta, rd);
    if (rd == ZERO_RD) clear_rows(p, cta & 15, cta >> 4);
  }
}
}

__global__ void __cluster_dims__(2, 1, 1) __launch_bounds__(NTHREADS, 1)
concat_heads__ssm_conv_h3__compressed_kv_cla__prompt_kernel(const __grid_constant__ Params p) {
  extern __shared__ uint8_t smem_raw[];
  const uint32_t sb = (smem_u32(smem_raw) + 1023) & ~1023u;
  if (threadIdx.x == NTHREADS - 64) { prefetch_map(&p.wuk); prefetch_map(&p.ckv); }
  const int cta = blockIdx.x;
  const bool attn = cta < NMAIN;
  int g, t;
  {
    const int c = cta >> 1, u2 = ((c - 36) * 37) >> 8, i = c - 36 - 7 * u2;
    g = c < 4 ? 1 : c < 36 ? (c - 4) & 7 : i == 0 ? 0 : 1 + i;
    t = 2 * (c < 4 ? c : c < 36 ? 7 - ((c - 4) >> 3) : u2) + (cta & 1);
  }
  if (attn && threadIdx.x == NTHREADS - 32) {
    const uint32_t full = bar_addr(sb, B_FULL);
    mbar_init(full, 1);
    asm volatile("fence.mbarrier_init.release.cluster;" ::: "memory");
    mbar_expect_tx(full, 49152);
    load_w(p, g, t, 0, sb, full);
    load_a(p, g, t, 0, sb + QREG, full);
  }
  if (STAGE1_NS && attn && threadIdx.x == NTHREADS - 64) {
    const uint32_t full = bar_addr(sb, B_FULL + 1);
    mbar_init(full, 1);
    asm volatile("fence.mbarrier_init.release.cluster;" ::: "memory");
    mbar_expect_tx(full, 49152);
    __nanosleep(STAGE1_NS);
    load_w(p, g, t, 1, sb + SLOT, full);
    load_a(p, g, t, 1, sb + QREG + 16384, full);
  }
  __syncwarp();
  const int lane = threadIdx.x & 31;
  const int warp = __shfl_sync(0xffffffffu, threadIdx.x >> 5, 0);
  const int wg = warp >> 2;
  if (wg != 0) {
    if (attn) {
      cluster_arrive();
      if (wg == 2) named_arrive(PP_BAR, 256);
    }
    asm volatile("setmaxnreg.inc.sync.aligned.u32 232;");
    if (!attn) {
      if (p.out != nullptr) { named_sync(0, NTHREADS); ssm::mma_warpgroup(sb, wg - 1); }
      return;
    }
    if (p.out != nullptr) consumer_main(p, sb, g, t, wg - 1, warp & 3);
  } else {
    asm volatile("setmaxnreg.dec.sync.aligned.u32 40;");
    if (!attn) {
      ssm::init(p, sb, cta - NMAIN);
      named_sync(0, NTHREADS);
      if (lane == 0) {
        if (warp == 0) { ssm::producer(p, sb, cta - NMAIN, load_epoch()); cta_done(32); }
        else ssm::reducer(sb, cta - NMAIN, warp - 1);
        if (warp == 1) GT(14);
      }
      return;
    }
    if (warp == 0) {
      if (lane == 0) {
        for (int i = STAGE1_NS ? 2 : 1; i < NSLOT; i++) mbar_init(bar_addr(sb, B_FULL + i), 1);
        asm volatile("fence.mbarrier_init.release.cluster;" ::: "memory");
      }
      __syncwarp();
      cluster_arrive();
      if (lane == 0) {
#pragma unroll 1
        for (int k = STAGE1_NS ? 2 : 1; k < EARLY_LD; k++) {
          const uint32_t full = bar_addr(sb, B_FULL + k);
          mbar_expect_tx(full, 49152);
          load_w(p, g, t, k & 15, sb + k * SLOT, full);
          load_a(p, g, t, k & 15, sb + QREG + k * 16384, full);
          __nanosleep(200);
        }
      }
      __syncwarp();
      cluster_wait();
      if (lane == 0) producer_main(p, sb, g, t);
      return;
    }
    if (lane == 0) {
      if (warp == 1) {
        for (int i = 0; i < NSLOT; i++) mbar_init(bar_addr(sb, B_EMPTY + i), 16);
        for (int i = 0; i < 2; i++) {
          mbar_init(bar_addr(sb, B_QFREE + i), 4); mbar_init(bar_addr(sb, B_QFULL + i), 1);
          mbar_init(bar_addr(sb, B_CTXOK + i), 1);
        }
      } else if (warp == 2) {
        for (int i = 0; i < 8; i++) { mbar_init(bar_addr(sb, B_S2_FULL + i), 4); mbar_init(bar_addr(sb, B_S2_EMPTY + i), 1); }
      } else {
        mbar_init(bar_addr(sb, B_DONE), 2);
        mbar_init(bar_addr(sb, B_KVOK), 1); mbar_init(bar_addr(sb, B_PF), 1);
        for (int i = 0; i < 2; i++) {
          mbar_init(bar_addr(sb, B_ST_KV + i), 4); mbar_init(bar_addr(sb, B_ST_Q + i), 4); mbar_init(bar_addr(sb, B_ST_CTX + i), 4);
        }
      }
      asm volatile("fence.mbarrier_init.release.cluster;" ::: "memory");
    }
    __syncwarp();
    cluster_arrive();
    cluster_wait();
    if (warp < 3) {
      if (warp == 2) {
        mbar_wait(bar_addr(sb, B_PF), 0);
        const uint8_t* a = at<const uint8_t>(p.b_x, (g * 16 + t) * 16 * DM * 2 + lane * 128);
#pragma unroll 1
        for (int i = 0; i < 4; i++) {
          if (i < 3 || lane < 16) asm volatile("prefetch.global.L2 [%0];" :: "l"(a + i * 4096));
          __nanosleep(1000);
        }
      }
      if (lane == 0) {
        if (warp == 1) { __nanosleep(2000); prefetch_map(&p.wuv); prefetch_map(&p.x); prefetch_map(&p.wq); prefetch_map(&p.o); prefetch_map(&p.wo); }
        helper_main(p, sb, g, t, warp - 1);
      }
    } else {
      ssm::side_work(p, g * 16 + t, load_epoch());
      if (lane == 0) { GT(57); mbar_wait(bar_addr(sb, B_DONE), 0); cta_done(1); }
    }
  }
}

typedef CUresult (*EncodeTiledFn)(CUtensorMap*, CUtensorMapDataType, cuuint32_t, void*, const cuuint64_t*, const cuuint64_t*,
                                  const cuuint32_t*, const cuuint32_t*, CUtensorMapInterleave, CUtensorMapSwizzle,
                                  CUtensorMapL2promotion, CUtensorMapFloatOOBfill);

void make_map(EncodeTiledFn enc, CUtensorMap* m, const void* ptr, int rank, const uint64_t* dims, const uint64_t* strides, const uint32_t* box) {
  cuuint64_t d[5], s[4]; cuuint32_t b[5], e[5] = {1, 1, 1, 1, 1};
  for (int i = 0; i < rank; i++) { d[i] = dims[i]; b[i] = box[i]; if (i) s[i - 1] = strides[i - 1]; }
  enc(m, CU_TENSOR_MAP_DATA_TYPE_BFLOAT16, rank, const_cast<void*>(ptr), d, s, b, e, CU_TENSOR_MAP_INTERLEAVE_NONE,
      CU_TENSOR_MAP_SWIZZLE_128B, CU_TENSOR_MAP_L2_PROMOTION_L2_256B, CU_TENSOR_MAP_FLOAT_OOB_FILL_NONE);
}
void map2(EncodeTiledFn enc, CUtensorMap* m, const void* ptr, uint64_t cols, uint64_t rows, uint32_t bc, uint32_t br) {
  const uint64_t dims[2] = {cols, rows}, st[1] = {cols * 2}; const uint32_t box[2] = {bc, br};
  make_map(enc, m, ptr, 2, dims, st, box);
}
void map3(EncodeTiledFn enc, CUtensorMap* m, const void* ptr, uint64_t rows, uint32_t nblk) {
  const uint64_t dims[3] = {64, rows, 64}, st[2] = {8192, 128}; const uint32_t box[3] = {64, 64, nblk};
  make_map(enc, m, ptr, 3, dims, st, box);
}

}

extern "C" void kernel_launch(void* const* d_in, const int* in_sizes, int n_in, void* d_out, int out_size) {
  (void)in_sizes; (void)n_in; (void)out_size;
  static EncodeTiledFn enc = nullptr;
  if (!enc) {
    void* fn = nullptr; cudaDriverEntryPointQueryResult qr;
    cudaGetDriverEntryPoint("cuTensorMapEncodeTiled", &fn, cudaEnableDefault, &qr);
    enc = (EncodeTiledFn)fn;
    cudaFuncSetAttribute(concat_heads__ssm_conv_h3__compressed_kv_cla__prompt_kernel, cudaFuncAttributeMaxDynamicSharedMemorySize, SMEM_BYTES);
  }
  Params p;
  p.a_q = (const bf16*)d_in[0]; p.a_k = (const bf16*)d_in[1]; p.a_v = (const bf16*)d_in[2];
  p.a_shift = (const bf16*)d_in[3]; p.a_ssmk = (const bf16*)d_in[4]; p.a_D = (const bf16*)d_in[5];
  p.out = (bf16*)d_out;
  p.b_x = (const bf16*)d_in[6];
  map2(enc, &p.x, d_in[6], DM, SEQ, 64, 128);
  map2(enc, &p.ckv, d_in[7], DC, SEQ, 64, 128);
  map3(enc, &p.wq, d_in[8], DM, 4);
  map3(enc, &p.wuk, d_in[9], DC, 4);
  map3(enc, &p.wuv, d_in[10], DC, 4);
  {
    const uint64_t dims[5] = {DM, 2, 4, 4, NH * HD / 32}, st[4] = {DM * 2, 8 * DM * 2, 2 * DM * 2, 32 * DM * 2}; const uint32_t box[5] = {64, 2, 4, 4, 4};
    make_map(enc, &p.wo, d_in[11], 5, dims, st, box);
  }
  map2(enc, &p.o, d_out, OUTW, SEQ, 64, 64);
  concat_heads__ssm_conv_h3__compressed_kv_cla__prompt_kernel<<<NCTA, NTHREADS, SMEM_BYTES>>>(p);
}
```

```cpp
#include <cuda_runtime.h>
#include <cuda_bf16.h>
#include <cuda.h>
#include <stdint.h>

namespace {

typedef __nv_bfloat16 bf16;

constexpr int SEQ  = 2048;
constexpr int DA   = 448;
constexpr int NH   = 16;
constexpr int HD   = 256;
constexpr int DM   = 448;
constexpr int DC   = 1024;
constexpr int OUTW = DA + DM;
constexpr int NMAIN = 128;
constexpr int NCONV = 4;
constexpr int NCTA  = NMAIN + NCONV;
constexpr int LOG_DONE = 8;
constexpr int NTHREADS = 384;

__device__ __align__(1024) bf16 g_kv[2ull * SEQ * NH * HD];
__device__ __align__(1024) bf16 g_qc[(size_t)NMAIN * 128 * HD];
__device__ __align__(128) uint8_t g_xs[DA * SEQ * 2];
constexpr uint32_t HO_STRIDE = 4224;
__device__ __align__(128) uint8_t g_ho[DA * HO_STRIDE];
struct alignas(128) Flag { unsigned v; unsigned pad[31]; };
struct Flags {
  Flag kv_ready[8];
  Flag ctx_ready[NMAIN * 2];
  Flag x_ready[7];
  Flag z_ready[7];
  Flag zero_ready[16];
  alignas(128) unsigned long long done;
};
__device__ Flags g_flags;
#define TS(i)
#define TSC(i, cond)
#define TDUMP()
#define GT(i)
#define PT(i)

struct alignas(64) Params {
  CUtensorMap ckv;
  CUtensorMap wuk;
  CUtensorMap wuv;
  CUtensorMap x;
  CUtensorMap wq;
  CUtensorMap o;
  CUtensorMap wo;
  const bf16 *a_q, *a_k, *a_v, *a_shift, *a_ssmk, *a_D, *b_x;
  bf16* out;
};

constexpr uint32_t SLOT     = 32768;
constexpr int      NSLOT    = 5;
constexpr uint32_t QREG     = 163840;
constexpr uint32_t BARS     = 229376;
constexpr uint32_t SMEM_BYTES = BARS + 1024 + 1024;
enum : uint32_t {
  B_FULL = 0, B_EMPTY = 5, B_KVOK = 10, B_DONE = 11, B_ST_KV = 12, B_ST_Q = 14, B_ST_CTX = 16, B_CTXOK = 18, B_QFREE = 20, B_QFULL = 22,
  B_S2_FULL = 24, B_S2_EMPTY = 32, B_PF = 40
};
constexpr int P1_STEPS = 4 * 16 + 2 * 7, P1_XS = P1_STEPS - 2;

template <typename T> __device__ __forceinline__ T* at(const void* base, uint32_t off) {
  asm volatile("" : "+r"(off));
  return reinterpret_cast<T*>(const_cast<char*>(static_cast<const char*>(base)) + off);
}
__device__ __forceinline__ unsigned* flag_at(Flag* f, uint32_t i) { return at<unsigned>(f, i * (uint32_t)sizeof(Flag)); }
__device__ __forceinline__ uint32_t smem_u32(const void* p) { return (uint32_t)__cvta_generic_to_shared(p); }
__device__ __forceinline__ void mbar_init(uint32_t bar, uint32_t cnt) {
  asm volatile("mbarrier.init.shared::cta.b64 [%0], %1;" :: "r"(bar), "r"(cnt) : "memory");
}
__device__ __forceinline__ void mbar_expect_tx(uint32_t bar, uint32_t bytes) {
  asm volatile("mbarrier.arrive.expect_tx.shared::cta.b64 _, [%0], %1;" :: "r"(bar), "r"(bytes) : "memory");
}
__device__ __forceinline__ void mbar_arrive(uint32_t bar) {
  asm volatile("mbarrier.arrive.shared::cta.b64 _, [%0];" :: "r"(bar) : "memory");
}
__device__ __forceinline__ void mbar_arrive_remote(uint32_t bar, uint32_t cta) {
  asm volatile("{\n.reg .b32 ra;\nmapa.shared::cluster.u32 ra, %0, %1;\n"
               "mbarrier.arrive.shared::cluster.b64 _, [ra];\n}" :: "r"(bar), "r"(cta) : "memory");
}
__device__ __forceinline__ bool mbar_try(uint32_t bar, uint32_t parity) {
  uint32_t ok;
  asm volatile("{\n.reg .pred p;\nmbarrier.try_wait.parity.shared::cta.b64 p, [%1], %2;\nselp.u32 %0, 1, 0, p;\n}"
               : "=r"(ok) : "r"(bar), "r"(parity) : "memory");
  return ok;
}
__device__ __forceinline__ uint32_t mbar_test(uint32_t bar, uint32_t parity) {
  uint32_t ok;
  asm volatile("{\n.reg .pred p;\nmbarrier.test_wait.parity.shared::cta.b64 p, [%1], %2;\nselp.u32 %0, 1, 0, p;\n}"
               : "=r"(ok) : "r"(bar), "r"(parity) : "memory");
  return ok;
}
constexpr uint32_t SPIN_LIMIT = 1u << 24;
__device__ __forceinline__ void mbar_wait(uint32_t bar, uint32_t parity) {
  if (mbar_try(bar, parity)) return;
  uint32_t n = 0;
  while (!mbar_try(bar, parity)) { if (++n > SPIN_LIMIT) __trap(); }
}
__device__ __forceinline__ void mbar_wait_unless(uint32_t ready, uint32_t bar, uint32_t parity) {
  asm volatile("{\n.reg .pred p;\n.reg .b32 n;\nsetp.ne.u32 p, %0, 0;\nvote.sync.all.pred p, p, 0xffffffff;\n@p bra.uni WDONE;\nmov.u32 n, 0;\n"
               "WLOOP:\nmbarrier.try_wait.parity.shared::cta.b64 p, [%1], %2;\n@p bra.uni WDONE;\nadd.u32 n, n, 1;\nsetp.lt.u32 p, n, %3;\n@p bra.uni WLOOP;\ntrap;\nWDONE:\n}"
               :: "r"(ready), "r"(bar), "r"(parity), "n"(SPIN_LIMIT) : "memory");
}
__device__ __forceinline__ unsigned load_epoch() {
  unsigned long long d; asm volatile("ld.relaxed.gpu.global.u64 %0, [%1];" : "=l"(d) : "l"(&g_flags.done) : "memory");
  return (unsigned)(d >> LOG_DONE);
}
template <int SLEEP_NS>
__device__ __forceinline__ void flag_wait(const unsigned* f, unsigned count, unsigned epoch) {
  const unsigned target = (epoch + 1) * count;
  uint32_t n = 0;
  while (true) {
    unsigned v;
    asm volatile("ld.acquire.gpu.global.u32 %0, [%1];" : "=r"(v) : "l"(f) : "memory");
    if ((int)(v - target) >= 0) break;
    if (++n > SPIN_LIMIT / 4) __trap();
    __nanosleep(SLEEP_NS);
  }
}
__device__ __forceinline__ void flag_signal(unsigned* f) { asm volatile("red.release.gpu.global.add.u32 [%0], 1;" :: "l"(f) : "memory"); }
__device__ __forceinline__ void cta_done(unsigned long long n) { asm volatile("red.relaxed.gpu.global.add.u64 [%0], %1;" :: "l"(&g_flags.done), "l"(n) : "memory"); }
__device__ __forceinline__ void fence_async_global() { asm volatile("fence.proxy.async.global;" ::: "memory"); }
__device__ __forceinline__ void fence_async_smem() { asm volatile("fence.proxy.async.shared::cta;" ::: "memory"); }
__device__ __forceinline__ void tma_ld2(uint32_t dst, const CUtensorMap* m, uint32_t bar, int c0, int c1) {
  asm volatile("cp.async.bulk.tensor.2d.shared::cluster.global.mbarrier::complete_tx::bytes [%0], [%1, {%3, %4}], [%2];"
               :: "r"(dst), "l"(m), "r"(bar), "r"(c0), "r"(c1) : "memory");
}
__device__ __forceinline__ void tma_ld3(uint32_t dst, const CUtensorMap* m, uint32_t bar, int c0, int c1, int c2) {
  asm volatile("cp.async.bulk.tensor.3d.shared::cluster.global.mbarrier::complete_tx::bytes [%0], [%1, {%3, %4, %5}], [%2];"
               :: "r"(dst), "l"(m), "r"(bar), "r"(c0), "r"(c1), "r"(c2) : "memory");
}
__device__ __forceinline__ void tma_ld5_mc(uint32_t dst, const CUtensorMap* m, uint32_t bar, int c0, int c4) {
  asm volatile("cp.async.bulk.tensor.5d.shared::cluster.global.mbarrier::complete_tx::bytes.multicast::cluster [%0], [%1, {%3, %6, %6, %6, %4}], [%2], %5;"
               :: "r"(dst), "l"(m), "r"(bar), "r"(c0), "r"(c4), "h"((uint16_t)3), "r"(0) : "memory");
}
__device__ __forceinline__ void bulk_ld(uint32_t dst, const void* src, uint32_t bytes, uint32_t bar) {
  asm volatile("cp.async.bulk.shared::cluster.global.mbarrier::complete_tx::bytes [%0], [%1], %2, [%3];"
               :: "r"(dst), "l"(src), "r"(bytes), "r"(bar) : "memory");
}
__device__ __forceinline__ void bulk_ld_p(uint32_t dst, const void* src, uint32_t bytes, uint32_t bar, uint64_t pl) {
  asm volatile("cp.async.bulk.shared::cluster.global.mbarrier::complete_tx::bytes.L2::cache_hint [%0], [%1], %2, [%3], %4;"
               :: "r"(dst), "l"(src), "r"(bytes), "r"(bar), "l"(pl) : "memory");
}
__device__ __forceinline__ void bulk_ld_mc(uint32_t dst, const void* src, uint32_t bytes, uint32_t bar, uint64_t pl) {
  asm volatile("cp.async.bulk.shared::cluster.global.mbarrier::complete_tx::bytes.multicast::cluster.L2::cache_hint [%0], [%1], %2, [%3], %4, %5;"
               :: "r"(dst), "l"(src), "r"(bytes), "r"(bar), "h"((uint16_t)3), "l"(pl) : "memory");
}
__device__ __forceinline__ void tma_red2(const CUtensorMap* m, uint32_t src, int c0, int c1) {
  asm volatile("cp.reduce.async.bulk.tensor.2d.global.shared::cta.add.bulk_group [%0, {%2, %3}], [%1];"
               :: "l"(m), "r"(src), "r"(c0), "r"(c1) : "memory");
}
__device__ __forceinline__ void bulk_commit() { asm volatile("cp.async.bulk.commit_group;" ::: "memory"); }
__device__ __forceinline__ void bulk_wait_read() { asm volatile("cp.async.bulk.wait_group.read 0;" ::: "memory"); }
__device__ __forceinline__ void bulk_wait_all() { asm volatile("cp.async.bulk.wait_group 0;" ::: "memory"); }
__device__ __forceinline__ void prefetch_map(const CUtensorMap* m) { asm volatile("prefetch.tensormap [%0];" :: "l"(m) : "memory"); }
__device__ __forceinline__ void wg_fence() { asm volatile("wgmma.fence.sync.aligned;" ::: "memory"); }
__device__ __forceinline__ void wg_commit() { asm volatile("wgmma.commit_group.sync.aligned;" ::: "memory"); }
template <int N> __device__ __forceinline__ void wg_wait() { asm volatile("wgmma.wait_group.sync.aligned %0;" :: "n"(N) : "memory"); }
template <int N> __device__ __forceinline__ void reg_fence(float (&d)[N]) {
#pragma unroll
  for (int i = 0; i < N; i++) asm volatile("" : "+f"(d[i]) :: "memory");
}
template <int N> __device__ __forceinline__ void reg_fence(uint32_t (&d)[N]) {
#pragma unroll
  for (int i = 0; i < N; i++) asm volatile("" : "+r"(d[i]) :: "memory");
}
__device__ __forceinline__ uint32_t fresh_tid() { uint32_t t; asm volatile("mov.u32 %0, %%tid.x;" : "=r"(t)); return t; }
__device__ __forceinline__ uint32_t lane_base16() {
  const uint32_t t = fresh_tid(), lane = t & 31, wq = (t >> 5) & 3;
  return (16 * wq + (lane & 7) + 8 * ((lane >> 3) & 1)) * 128 + (((lane >> 4) ^ (lane & 7)) << 4);
}
__device__ __forceinline__ void cluster_arrive() { asm volatile("barrier.cluster.arrive.relaxed.aligned;" ::: "memory"); }
__device__ __forceinline__ void cluster_wait() { asm volatile("barrier.cluster.wait.acquire.aligned;" ::: "memory"); }
__device__ __forceinline__ void named_sync(int id, int n) { asm volatile("bar.sync %0, %1;" :: "r"(id), "r"(n) : "memory"); }
__device__ __forceinline__ void named_arrive(int id, int n) { asm volatile("bar.arrive %0, %1;" :: "r"(id), "r"(n) : "memory"); }
__device__ __forceinline__ uint32_t pack_bf16(float lo, float hi) {
  uint32_t r; asm("cvt.rn.bf16x2.f32 %0, %1, %2;" : "=r"(r) : "f"(hi), "f"(lo)); return r;
}
__device__ __forceinline__ float ex2(float x) { float y; asm("ex2.approx.ftz.f32 %0, %1;" : "=f"(y) : "f"(x)); return y; }
__device__ __forceinline__ void stsm4(uint32_t addr, uint32_t a, uint32_t b, uint32_t c, uint32_t d) {
  asm volatile("stmatrix.sync.aligned.m8n8.x4.shared.b16 [%0], {%1, %2, %3, %4};" :: "r"(addr), "r"(a), "r"(b), "r"(c), "r"(d) : "memory");
}
__device__ __forceinline__ uint64_t mk_desc(uint32_t addr, uint32_t lbo, uint32_t sbo) {
  return (uint64_t)(((addr & 0x3FFFF) >> 4) | ((lbo >> 4) << 16)) | ((uint64_t)((sbo >> 4) | (1u << 30)) << 32);
}
__device__ __forceinline__ uint64_t desc_k(uint32_t addr)  { return mk_desc(addr, 16, 1024); }
__device__ __forceinline__ uint64_t desc_mn(uint32_t addr) { return mk_desc(addr, 8192, 1024); }
__device__ __forceinline__ uint64_t desc_64(uint32_t addr) { return (uint64_t)(((addr & 0x3FFFF) >> 4) | ((4096u >> 4) << 16)) | ((uint64_t)((512u >> 4) | (2u << 30)) << 32); }
__device__ __forceinline__ uint64_t desc_add(uint64_t d, uint32_t bytes) { return d + (bytes >> 4); }

__device__ __forceinline__ void wgmma_ss_n256_tb(float (&d)[128], uint64_t da, uint64_t db, int sd) {
  asm volatile("{\n.reg .pred p;\nsetp.ne.b32 p, %130, 0;\n"
    "wgmma.mma_async.sync.aligned.m64n256k16.f32.bf16.bf16 "
    "{%0, %1, %2, %3, %4, %5, %6, %7, %8, %9, %10, %11, %12, %13, %14, %15, "
    "%16, %17, %18, %19, %20, %21, %22, %23, %24, %25, %26, %27, %28, %29, %30, %31, "
    "%32, %33, %34, %35, %36, %37, %38, %39, %40, %41, %42, %43, %44, %45, %46, %47, "
    "%48, %49, %50, %51, %52, %53, %54, %55, %56, %57, %58, %59, %60, %61, %62, %63, "
    "%64, %65, %66, %67, %68, %69, %70, %71, %72, %73, %74, %75, %76, %77, %78, %79, "
    "%80, %81, %82, %83, %84, %85, %86, %87, %88, %89, %90, %91, %92, %93, %94, %95, "
    "%96, %97, %98, %99, %100, %101, %102, %103, %104, %105, %106, %107, %108, %109, %110, %111, "
    "%112, %113, %114, %115, %116, %117, %118, %119, %120, %121, %122, %123, %124, %125, %126, %127}, "
    "%128, %129, p, 1, 1, 0, 1;\n}"
    : "+f"(d[0]), "+f"(d[1]), "+f"(d[2]), "+f"(d[3]), "+f"(d[4]), "+f"(d[5]), "+f"(d[6]), "+f"(d[7]),
      "+f"(d[8]), "+f"(d[9]), "+f"(d[10]), "+f"(d[11]), "+f"(d[12]), "+f"(d[13]), "+f"(d[14]), "+f"(d[15]),
      "+f"(d[16]), "+f"(d[17]), "+f"(d[18]), "+f"(d[19]), "+f"(d[20]), "+f"(d[21]), "+f"(d[22]), "+f"(d[23]),
      "+f"(d[24]), "+f"(d[25]), "+f"(d[26]), "+f"(d[27]), "+f"(d[28]), "+f"(d[29]), "+f"(d[30]), "+f"(d[31]),
      "+f"(d[32]), "+f"(d[33]), "+f"(d[34]), "+f"(d[35]), "+f"(d[36]), "+f"(d[37]), "+f"(d[38]), "+f"(d[39]),
      "+f"(d[40]), "+f"(d[41]), "+f"(d[42]), "+f"(d[43]), "+f"(d[44]), "+f"(d[45]), "+f"(d[46]), "+f"(d[47]),
      "+f"(d[48]), "+f"(d[49]), "+f"(d[50]), "+f"(d[51]), "+f"(d[52]), "+f"(d[53]), "+f"(d[54]), "+f"(d[55]),
      "+f"(d[56]), "+f"(d[57]), "+f"(d[58]), "+f"(d[59]), "+f"(d[60]), "+f"(d[61]), "+f"(d[62]), "+f"(d[63]),
      "+f"(d[64]), "+f"(d[65]), "+f"(d[66]), "+f"(d[67]), "+f"(d[68]), "+f"(d[69]), "+f"(d[70]), "+f"(d[71]),
      "+f"(d[72]), "+f"(d[73]), "+f"(d[74]), "+f"(d[75]), "+f"(d[76]), "+f"(d[77]), "+f"(d[78]), "+f"(d[79]),
      "+f"(d[80]), "+f"(d[81]), "+f"(d[82]), "+f"(d[83]), "+f"(d[84]), "+f"(d[85]), "+f"(d[86]), "+f"(d[87]),
      "+f"(d[88]), "+f"(d[89]), "+f"(d[90]), "+f"(d[91]), "+f"(d[92]), "+f"(d[93]), "+f"(d[94]), "+f"(d[95]),
      "+f"(d[96]), "+f"(d[97]), "+f"(d[98]), "+f"(d[99]), "+f"(d[100]), "+f"(d[101]), "+f"(d[102]), "+f"(d[103]),
      "+f"(d[104]), "+f"(d[105]), "+f"(d[106]), "+f"(d[107]), "+f"(d[108]), "+f"(d[109]), "+f"(d[110]), "+f"(d[111]),
      "+f"(d[112]), "+f"(d[113]), "+f"(d[114]), "+f"(d[115]), "+f"(d[116]), "+f"(d[117]), "+f"(d[118]), "+f"(d[119]),
      "+f"(d[120]), "+f"(d[121]), "+f"(d[122]), "+f"(d[123]), "+f"(d[124]), "+f"(d[125]), "+f"(d[126]), "+f"(d[127])
    : "l"(da), "l"(db), "r"(sd));
}
__device__ __forceinline__ void wgmma_ss_n64(float (&d)[32], uint64_t da, uint64_t db, int sd) {
  asm volatile("{\n.reg .pred p;\nsetp.ne.b32 p, %34, 0;\n"
    "wgmma.mma_async.sync.aligned.m64n64k16.f32.bf16.bf16 "
    "{%0, %1, %2, %3, %4, %5, %6, %7, %8, %9, %10, %11, %12, %13, %14, %15, "
    "%16, %17, %18, %19, %20, %21, %22, %23, %24, %25, %26, %27, %28, %29, %30, %31}, "
    "%32, %33, p, 1, 1, 0, 0;\n}"
    : "+f"(d[0]), "+f"(d[1]), "+f"(d[2]), "+f"(d[3]), "+f"(d[4]), "+f"(d[5]), "+f"(d[6]), "+f"(d[7]),
      "+f"(d[8]), "+f"(d[9]), "+f"(d[10]), "+f"(d[11]), "+f"(d[12]), "+f"(d[13]), "+f"(d[14]), "+f"(d[15]),
      "+f"(d[16]), "+f"(d[17]), "+f"(d[18]), "+f"(d[19]), "+f"(d[20]), "+f"(d[21]), "+f"(d[22]), "+f"(d[23]),
      "+f"(d[24]), "+f"(d[25]), "+f"(d[26]), "+f"(d[27]), "+f"(d[28]), "+f"(d[29]), "+f"(d[30]), "+f"(d[31])
    : "l"(da), "l"(db), "r"(sd));
}
__device__ __forceinline__ void wgmma_rs_n256_tb(float (&d)[128], uint32_t a0, uint32_t a1, uint32_t a2, uint32_t a3, uint64_t db, int sd) {
  asm volatile("{\n.reg .pred p;\nsetp.ne.b32 p, %133, 0;\n"
    "wgmma.mma_async.sync.aligned.m64n256k16.f32.bf16.bf16 "
    "{%0, %1, %2, %3, %4, %5, %6, %7, %8, %9, %10, %11, %12, %13, %14, %15, "
    "%16, %17, %18, %19, %20, %21, %22, %23, %24, %25, %26, %27, %28, %29, %30, %31, "
    "%32, %33, %34, %35, %36, %37, %38, %39, %40, %41, %42, %43, %44, %45, %46, %47, "
    "%48, %49, %50, %51, %52, %53, %54, %55, %56, %57, %58, %59, %60, %61, %62, %63, "
    "%64, %65, %66, %67, %68, %69, %70, %71, %72, %73, %74, %75, %76, %77, %78, %79, "
    "%80, %81, %82, %83, %84, %85, %86, %87, %88, %89, %90, %91, %92, %93, %94, %95, "
    "%96, %97, %98, %99, %100, %101, %102, %103, %104, %105, %106, %107, %108, %109, %110, %111, "
    "%112, %113, %114, %115, %116, %117, %118, %119, %120, %121, %122, %123, %124, %125, %126, %127}, "
    "{%128, %129, %130, %131}, %132, p, 1, 1, 1;\n}"
    : "+f"(d[0]), "+f"(d[1]), "+f"(d[2]), "+f"(d[3]), "+f"(d[4]), "+f"(d[5]), "+f"(d[6]), "+f"(d[7]),
      "+f"(d[8]), "+f"(d[9]), "+f"(d[10]), "+f"(d[11]), "+f"(d[12]), "+f"(d[13]), "+f"(d[14]), "+f"(d[15]),
      "+f"(d[16]), "+f"(d[17]), "+f"(d[18]), "+f"(d[19]), "+f"(d[20]), "+f"(d[21]), "+f"(d[22]), "+f"(d[23]),
      "+f"(d[24]), "+f"(d[25]), "+f"(d[26]), "+f"(d[27]), "+f"(d[28]), "+f"(d[29]), "+f"(d[30]), "+f"(d[31]),
      "+f"(d[32]), "+f"(d[33]), "+f"(d[34]), "+f"(d[35]), "+f"(d[36]), "+f"(d[37]), "+f"(d[38]), "+f"(d[39]),
      "+f"(d[40]), "+f"(d[41]), "+f"(d[42]), "+f"(d[43]), "+f"(d[44]), "+f"(d[45]), "+f"(d[46]), "+f"(d[47]),
      "+f"(d[48]), "+f"(d[49]), "+f"(d[50]), "+f"(d[51]), "+f"(d[52]), "+f"(d[53]), "+f"(d[54]), "+f"(d[55]),
      "+f"(d[56]), "+f"(d[57]), "+f"(d[58]), "+f"(d[59]), "+f"(d[60]), "+f"(d[61]), "+f"(d[62]), "+f"(d[63]),
      "+f"(d[64]), "+f"(d[65]), "+f"(d[66]), "+f"(d[67]), "+f"(d[68]), "+f"(d[69]), "+f"(d[70]), "+f"(d[71]),
      "+f"(d[72]), "+f"(d[73]), "+f"(d[74]), "+f"(d[75]), "+f"(d[76]), "+f"(d[77]), "+f"(d[78]), "+f"(d[79]),
      "+f"(d[80]), "+f"(d[81]), "+f"(d[82]), "+f"(d[83]), "+f"(d[84]), "+f"(d[85]), "+f"(d[86]), "+f"(d[87]),
      "+f"(d[88]), "+f"(d[89]), "+f"(d[90]), "+f"(d[91]), "+f"(d[92]), "+f"(d[93]), "+f"(d[94]), "+f"(d[95]),
      "+f"(d[96]), "+f"(d[97]), "+f"(d[98]), "+f"(d[99]), "+f"(d[100]), "+f"(d[101]), "+f"(d[102]), "+f"(d[103]),
      "+f"(d[104]), "+f"(d[105]), "+f"(d[106]), "+f"(d[107]), "+f"(d[108]), "+f"(d[109]), "+f"(d[110]), "+f"(d[111]),
      "+f"(d[112]), "+f"(d[113]), "+f"(d[114]), "+f"(d[115]), "+f"(d[116]), "+f"(d[117]), "+f"(d[118]), "+f"(d[119]),
      "+f"(d[120]), "+f"(d[121]), "+f"(d[122]), "+f"(d[123]), "+f"(d[124]), "+f"(d[125]), "+f"(d[126]), "+f"(d[127])
    : "r"(a0), "r"(a1), "r"(a2), "r"(a3), "l"(db), "r"(sd));
}
__device__ __forceinline__ void wgmma_rs_n64_tb(float (&d)[32], uint32_t a0, uint32_t a1, uint32_t a2, uint32_t a3, uint64_t db, int sd) {
  asm volatile("{\n.reg .pred p;\nsetp.ne.b32 p, %37, 0;\n"
    "wgmma.mma_async.sync.aligned.m64n64k16.f32.bf16.bf16 "
    "{%0, %1, %2, %3, %4, %5, %6, %7, %8, %9, %10, %11, %12, %13, %14, %15, "
    "%16, %17, %18, %19, %20, %21, %22, %23, %24, %25, %26, %27, %28, %29, %30, %31}, "
    "{%32, %33, %34, %35}, %36, p, 1, 1, 1;\n}"
    : "+f"(d[0]), "+f"(d[1]), "+f"(d[2]), "+f"(d[3]), "+f"(d[4]), "+f"(d[5]), "+f"(d[6]), "+f"(d[7]),
      "+f"(d[8]), "+f"(d[9]), "+f"(d[10]), "+f"(d[11]), "+f"(d[12]), "+f"(d[13]), "+f"(d[14]), "+f"(d[15]),
      "+f"(d[16]), "+f"(d[17]), "+f"(d[18]), "+f"(d[19]), "+f"(d[20]), "+f"(d[21]), "+f"(d[22]), "+f"(d[23]),
      "+f"(d[24]), "+f"(d[25]), "+f"(d[26]), "+f"(d[27]), "+f"(d[28]), "+f"(d[29]), "+f"(d[30]), "+f"(d[31])
    : "r"(a0), "r"(a1), "r"(a2), "r"(a3), "l"(db), "r"(sd));
}
__device__ __forceinline__ void wgmma_rs_n32(float (&d)[16], uint32_t a0, uint32_t a1, uint32_t a2, uint32_t a3, uint64_t db, int sd) {
  asm volatile("{\n.reg .pred p;\nsetp.ne.b32 p, %21, 0;\n"
    "wgmma.mma_async.sync.aligned.m64n32k16.f32.bf16.bf16 "
    "{%0, %1, %2, %3, %4, %5, %6, %7, %8, %9, %10, %11, %12, %13, %14, %15}, "
    "{%16, %17, %18, %19}, %20, p, 1, 1, 0;\n}"
    : "+f"(d[0]), "+f"(d[1]), "+f"(d[2]), "+f"(d[3]), "+f"(d[4]), "+f"(d[5]), "+f"(d[6]), "+f"(d[7]),
      "+f"(d[8]), "+f"(d[9]), "+f"(d[10]), "+f"(d[11]), "+f"(d[12]), "+f"(d[13]), "+f"(d[14]), "+f"(d[15])
    : "r"(a0), "r"(a1), "r"(a2), "r"(a3), "l"(db), "r"(sd));
}

__device__ __forceinline__ void sts16(uint32_t a, uint32_t x, uint32_t y, uint32_t z, uint32_t w) {
  asm volatile("st.shared.v4.u32 [%0], {%1, %2, %3, %4};" :: "r"(a), "r"(x), "r"(y), "r"(z), "r"(w) : "memory");
}
__device__ __forceinline__ uint32_t lds4(uint32_t a) { uint32_t v; asm volatile("ld.shared.u32 %0, [%1];" : "=r"(v) : "r"(a) : "memory"); return v; }
__device__ __forceinline__ uint32_t bmul(uint32_t a, uint32_t b) { uint32_t r; asm("mul.rn.bf16x2 %0, %1, %2;" : "=r"(r) : "r"(a), "r"(b)); return r; }
__device__ __forceinline__ uint32_t badd(uint32_t a, uint32_t b) { uint32_t r; asm("add.rn.bf16x2 %0, %1, %2;" : "=r"(r) : "r"(a), "r"(b)); return r; }

#define SIDE_AHEAD 3
#define ZERO_RD 4
#define EXP_LASTRD 7
#define NB 8
constexpr int EARLY_LD = 4;
constexpr int PP_BAR = 3;
template <int V> struct Int { static constexpr int value = V; };
struct Ring {
  uint32_t slot, phase;
  __device__ __forceinline__ void next() { if (++slot == NSLOT) { slot = 0; phase ^= 1; } }
};
__device__ __forceinline__ uint32_t bar_addr(uint32_t sb, uint32_t i) { return sb + BARS + 8 * i; }

__device__ __forceinline__ int kv_group(int g, int t) { return (g & 6) | (t & 1); }
__device__ __forceinline__ int kv_rows(int g, int t) { return (t & 14) | (g & 1); }
__device__ __forceinline__ void load_w(const Params& p, int g, int t, int it, uint32_t dst, uint32_t full) {
  if (it < 64) tma_ld3(dst, (it & 16) ? &p.wuv : &p.wuk, full, 0, (it & 15) * 64, (kv_group(g, t) + (it < 32 ? 8 : 0)) * 4);
  else tma_ld3(dst, &p.wq, full, 0, (it < 71 ? it - 64 : it - 71) * 64, (it < 71 ? g + 8 : g) * 4);
}
__device__ __forceinline__ void load_a(const Params& p, int g, int t, int it, uint32_t dst, uint32_t full) {
  if (it < 64) tma_ld2(dst, &p.ckv, full, (it & 15) * 64, kv_rows(g, t) * 128);
  else tma_ld2(dst, &p.x, full, (it < 71 ? it - 64 : it - 71) * 64, (it < 71 ? 15 - t : t) * 128);
}

__device__ __forceinline__ void producer_main(const Params& p, uint32_t sb, int g, int t) {
  const int rank = t & 1;
  Ring r{EARLY_LD, 0};
  auto wait_slot = [&]() { mbar_wait(bar_addr(sb, B_EMPTY + r.slot), r.phase ^ 1); };
  uint32_t prev = 0;
#pragma unroll 1
  for (int it = EARLY_LD; it < P1_STEPS; it++) {
    wait_slot();
    if (it > EARLY_LD && it <= P1_XS) load_a(p, g, t, it - 1, sb + QREG + ((it - 1) & 3) * 16384, prev);
    const uint32_t full = bar_addr(sb, B_FULL + r.slot);
    mbar_expect_tx(full, it < P1_XS ? 49152 : 32768);
    load_w(p, g, t, it, sb + r.slot * SLOT, full);
    prev = full;
    r.next();
    if (it == 50) mbar_arrive(bar_addr(sb, B_PF));
    if (it == P1_XS) {
      wait_slot();
      const uint32_t f2 = bar_addr(sb, B_FULL + r.slot);
      mbar_expect_tx(f2, 32768);
      load_a(p, g, t, P1_XS, sb + r.slot * SLOT, f2);
      load_a(p, g, t, P1_XS + 1, sb + r.slot * SLOT + 16384, f2);
      r.next();
    }
  }
  uint64_t once;
  asm volatile("createpolicy.fractional.L2::evict_first.b64 %0, 1.0;" : "=l"(once));
  const int na = 2 * t + 2, own = 2 * (t & ~1) + 2;
  mbar_wait(bar_addr(sb, B_KVOK), 0);
#pragma unroll 1
  for (int f = 0; f < 68; f++) {
    const bool isK = (f == 0) || ((f & 1) && f < 67);
    const int i = isK ? (f + 1) >> 1 : (f - 1) >> 1;
    wait_slot();
    const uint32_t full = bar_addr(sb, B_FULL + r.slot);
    mbar_expect_tx(full, 32768);
    const uint32_t src = (uint32_t)(((isK ? 0 : NH) + g) * 32 + (i >= na ? 8 * 32 + 33 - i : i)) * 32768;
    if ((i & ~1) != own) bulk_ld_mc(sb + r.slot * SLOT + rank * 16384, at<uint8_t>(g_kv, src + rank * 16384), 16384, full, once);
    else bulk_ld_p(sb + r.slot * SLOT, at<uint8_t>(g_kv, src), 32768, full, once);
    r.next();
  }
#pragma unroll 1
  for (int f = 0; f < 14; f++) {
    const int ch = f < 4 ? f & 1 : f >> 1, par = f < 4 ? f >> 1 : f & 1;
    wait_slot();
    const uint32_t full = bar_addr(sb, B_FULL + r.slot);
    mbar_expect_tx(full, 32768);
    tma_ld5_mc(sb + r.slot * SLOT + rank * 16384, &p.wo, full, ch * 64, (par ? g : g + 8) * 8 + rank * 4);
    r.next();
  }
}

__device__ __forceinline__ void helper_main(const Params& p, uint32_t sb, int g, int t, int w) {
  const unsigned epoch = load_epoch();
  const uint32_t qreg = sb + QREG + w * 32768, qfull = bar_addr(sb, B_QFULL + w);
  mbar_wait(bar_addr(sb, B_ST_KV + w), 0);
  flag_signal(flag_at(g_flags.kv_ready, kv_group(g, t)));
  if (w == 0) {
    flag_wait<20>(flag_at(g_flags.kv_ready, g), 32, epoch);
    fence_async_global();
    mbar_arrive(bar_addr(sb, B_KVOK));
  }
  mbar_wait(bar_addr(sb, B_ST_Q + w), 0);
  asm volatile("fence.release.gpu;" ::: "memory");
  fence_async_global();
  mbar_wait(bar_addr(sb, B_QFREE + w), 0);
  mbar_expect_tx(qfull, 32768);
  bulk_ld(qreg, at<uint8_t>(g_qc, ((g * 16 + t) * 2 + w) * 32768), 32768, qfull);
  auto publish = [&]() { mbar_wait(bar_addr(sb, B_ST_CTX + w), 0); flag_signal(flag_at(g_flags.ctx_ready, (g * 16 + t) * 2 + w)); };
  if (t < 8) publish();
  flag_wait<20>(flag_at(g_flags.ctx_ready, (g * 16 + 15 - t) * 2 + (w ^ 1)), 1, epoch);
  mbar_arrive(bar_addr(sb, B_CTXOK + w));
  mbar_arrive(bar_addr(sb, B_DONE));
  if (t >= 8) publish();
  flag_wait<20>(flag_at(g_flags.zero_ready, 15 - t), 8, epoch);
  fence_async_global();
#pragma unroll 1
  for (int ch = 0; ch < 6; ch++) {
    mbar_wait(bar_addr(sb, B_S2_FULL + w * 4 + (ch & 3)), ch >> 2);
    tma_red2(&p.o, qreg + (ch & 3) * 8192, DA + ch * 64, (15 - t) * 128 + (w ^ 1) * 64);
    bulk_commit();
    if (ch < 3) { bulk_wait_read(); mbar_arrive(bar_addr(sb, B_S2_EMPTY + w * 4 + ch)); }
  }
  bulk_wait_read();
  GT(48 + w);
}

__device__ __forceinline__ void store_block(uint32_t base, uint32_t lanebase, const uint32_t (&pk)[16]) {
#pragma unroll
  for (int J = 0; J < 8; J += 2) stsm4(base + (lanebase ^ (J << 4)), pk[2 * J], pk[2 * J + 1], pk[2 * J + 2], pk[2 * J + 3]);
}
__device__ __forceinline__ void pack_chunks(uint32_t (&pk)[64], const float (&acc)[128]) {
#pragma unroll
  for (int i = 0; i < 64; i++) { const int e = 16 * (i >> 3) + 4 * (i & 3) + 2 * ((i >> 2) & 1); pk[i] = pack_bf16(acc[e], acc[e + 1]); }
}
__device__ __forceinline__ uint32_t chunk_off() { const uint32_t t = fresh_tid(); return (t & 96) * 32 + (t & 28) * 16 + (((t ^ (t >> 3)) & 3) << 4); }
__device__ __forceinline__ void warp_arrive(uint32_t bar, int lane) { __syncwarp(); if (lane == 0) mbar_arrive(bar); }

__device__ __forceinline__ void consumer_main(const Params& p, uint32_t sb, int g, int t, int w, int wq) {
  const int lane = threadIdx.x & 31;
  const int rank = t & 1;

  auto turn_begin = [&]() { named_sync(PP_BAR + w, 256); };
  auto turn_end = [&]() { named_arrive(PP_BAR + (w ^ 1), 256); };
  Ring r{0, 0};
  auto take = [&](uint32_t ready = 0) { const uint32_t sl = r.slot; mbar_wait_unless(ready, bar_addr(sb, B_FULL + sl), r.phase); r.next(); return sl; };
  uint32_t rdy0 = 0, rdy1 = 0;
  auto peek2 = [&]() { Ring q = r; rdy0 = mbar_test(bar_addr(sb, B_FULL + q.slot), q.phase); q.next(); rdy1 = mbar_test(bar_addr(sb, B_FULL + q.slot), q.phase); };
  auto give = [&](uint32_t sl) { if (lane < 2) mbar_arrive_remote(bar_addr(sb, B_EMPTY + sl), rank ^ lane); };
  float acc[128];
#pragma unroll
  for (int i = 0; i < 128; i++) acc[i] = 0.f;
  uint32_t pk[64];
#pragma unroll
  for (int i = 0; i < 64; i++) pk[i] = 0;
  reg_fence(acc);
  reg_fence(pk);
  cluster_wait();
  TS(0);
  const uint32_t qreg = sb + QREG + w * 32768;
  {
    uint32_t xs = 0;
    uint4* row = nullptr;
    int it = 0;
#pragma unroll 1
    for (int tile = 0; tile < 6; tile++) {
      const bool isq = tile >= 4;
      const uint32_t abase = sb + QREG + (w ^ (tile == 4)) * 8192;
#pragma unroll 1
      for (int u = 0; u < (isq ? 4 : 8); u++) {
        const bool two = !(isq && u == 1), last = it == P1_XS;
        const uint32_t w0 = take(rdy0);
        TSC(1, it == 0);
        if (last) { xs = take(rdy1); rdy1 = 0; }
        const uint32_t xb = sb + xs * SLOT + w * 8192;
        const uint64_t da = desc_k(last ? xb : abase + (it & 3) * 16384), db = desc_mn(sb + w0 * SLOT);
        turn_begin();
        wg_fence();
#pragma unroll
        for (int kk = 0; kk < 4; kk++) wgmma_ss_n256_tb(acc, desc_add(da, kk * 32), desc_add(db, kk * 2048), (u | kk) != 0);
        wg_commit();
        uint32_t w1 = w0;
        if (two) {
          w1 = take(rdy1);
          const uint64_t da1 = desc_k(last ? xb + 16384 : abase + ((it + 1) & 3) * 16384), db1 = desc_mn(sb + w1 * SLOT);
          wg_fence();
#pragma unroll
          for (int kk = 0; kk < 4; kk++) wgmma_ss_n256_tb(acc, desc_add(da1, kk * 32), desc_add(db1, kk * 2048), 1);
          wg_commit();
          turn_end();
          wg_wait<1>();
          give(w0);
        } else {
          turn_end();
        }
        if (tile > 0) {
          uint32_t m = isq ? 0xC0380403u >> (8 * u) : 1u << u;
          asm volatile("" : "+r"(m));
#pragma unroll
          for (int i = 0; i < 16; i++)
            if (m & (1u << (i >> 1))) row[(i >> 1) * 256 + (i & 1) * 32] = make_uint4(pk[4 * i], pk[4 * i + 1], pk[4 * i + 2], pk[4 * i + 3]);
        }
        peek2();
        wg_wait<0>();
        give(w1);
        it += 1 + two;
      }
      reg_fence(acc);
      if (isq) warp_arrive(bar_addr(sb, (tile == 4 ? B_ST_KV : B_ST_Q) + w), lane);
      if (tile == 5) break;
      pack_chunks(pk, acc);
      row = at<uint4>(isq ? (const void*)g_qc : (const void*)g_kv, chunk_off() +
                      (uint32_t)(isq ? (g * 16 + t) * 2 + w : ((tile & 1) * NH + kv_group(g, t) + (tile < 2 ? 8 : 0)) * 32 + kv_rows(g, t) * 2 + w) * 32768);
      TS(2 + tile);
    }
    give(xs);
    const uint32_t qa = qreg + chunk_off();
    TS(7);
    pack_chunks(pk, acc);
#pragma unroll
    for (int i = 0; i < 16; i++) sts16(qa + (i >> 1) * 4096 + (i & 1) * 512, pk[4 * i], pk[4 * i + 1], pk[4 * i + 2], pk[4 * i + 3]);
    rdy0 = mbar_test(bar_addr(sb, B_FULL + r.slot), r.phase);
    fence_async_smem();
  }
  TS(8);

  auto normalise = [&](int c, float i0, float i1) {
    pk[4 * c]     = pack_bf16(acc[8 * c] * i0, acc[8 * c + 1] * i0);
    pk[4 * c + 1] = pack_bf16(acc[8 * c + 2] * i1, acc[8 * c + 3] * i1);
    pk[4 * c + 2] = pack_bf16(acc[8 * c + 4] * i0, acc[8 * c + 5] * i0);
    pk[4 * c + 3] = pack_bf16(acc[8 * c + 6] * i1, acc[8 * c + 7] * i1);
  };
  float il0 = 0.f, il1 = 0.f;
  constexpr float SC = 0.0625f * 1.4426950408889634f;
#pragma unroll 1
  for (int which = 0; which < 2; which++) {
    float s[32];
#pragma unroll
    for (int i = 0; i < 32; i++) s[i] = 0.f;
    uint32_t pa[16], pb[16];
    float m0 = 0.f, m1 = 0.f, l0 = 0.f, l1 = 0.f;
    const uint64_t dq = desc_64(qreg);
    uint64_t dk = 0, dqq = 0, dv = 0;
    auto prep_qk = [&](uint32_t kaddr) { dk = desc_64(kaddr); dqq = dq + (kaddr >> 31); asm volatile("" : "+l"(dk), "+l"(dqq)); };
    auto prep_pv = [&](uint32_t vaddr) { dv = desc_64(vaddr); asm volatile("" : "+l"(dv)); };
    auto issue_qk = [&]() {
#pragma unroll
      for (int kk = 0; kk < 16; kk++)
        wgmma_ss_n64(s, desc_add(dqq, (kk >> 1) * 4096 + (kk & 1) * 32), desc_add(dk, (kk >> 1) * 4096 + (kk & 1) * 32), kk != 0);
    };
    auto issue_pv = [&](int accumulate) {
#pragma unroll
      for (int kk = 0; kk < 4; kk++)
        wgmma_rs_n256_tb(acc, pa[4 * kk], pa[4 * kk + 1], pa[4 * kk + 2], pa[4 * kk + 3], desc_add(dv, kk * 1024), accumulate | kk);
    };
    auto mask_diag = [&]() {
      const int d = 16 * wq + (lane >> 2) - 2 * (lane & 3);
#pragma unroll
      for (int jj = 0; jj < 8; jj++) {
        if (8 * jj > d)     { s[4 * jj] = -INFINITY;     if (jj < 7) s[4 * jj + 6] = -INFINITY; }
        if (8 * jj + 1 > d) { s[4 * jj + 1] = -INFINITY; if (jj < 7) s[4 * jj + 7] = -INFINITY; }
      }
    };
    float a0, a1;
    auto softmax = [&]() -> bool {
      float x0 = fmaxf(s[0], s[1]), x1 = fmaxf(s[2], s[3]);
#pragma unroll
      for (int jj = 1; jj < 8; jj++) {
        x0 = fmaxf(x0, fmaxf(s[4 * jj], s[4 * jj + 1]));
        x1 = fmaxf(x1, fmaxf(s[4 * jj + 2], s[4 * jj + 3]));
      }
      x0 = fmaxf(x0, __shfl_xor_sync(0xffffffffu, x0, 1));
      x1 = fmaxf(x1, __shfl_xor_sync(0xffffffffu, x1, 1));
      x0 = fmaxf(x0, __shfl_xor_sync(0xffffffffu, x0, 2));
      x1 = fmaxf(x1, __shfl_xor_sync(0xffffffffu, x1, 2));
      const bool grow = __any_sync(0xffffffffu, fmaxf(x0 - m0, x1 - m1) * SC > 8.f);
      if (grow) {
        x0 = fmaxf(x0, m0); x1 = fmaxf(x1, m1);
        a0 = ex2((m0 - x0) * SC); a1 = ex2((m1 - x1) * SC);
        m0 = x0; m1 = x1;
        l0 *= a0; l1 *= a1;
      }
      const float b0 = -m0 * SC, b1 = -m1 * SC;
      float t0 = 0.f, t1 = 0.f, t2 = 0.f, t3 = 0.f;
#pragma unroll
      for (int jj = 0; jj < 8; jj++) {
        s[4 * jj]     = ex2(fmaf(s[4 * jj], SC, b0));
        s[4 * jj + 1] = ex2(fmaf(s[4 * jj + 1], SC, b0));
        s[4 * jj + 2] = ex2(fmaf(s[4 * jj + 2], SC, b1));
        s[4 * jj + 3] = ex2(fmaf(s[4 * jj + 3], SC, b1));
        t0 += s[4 * jj]; t1 += s[4 * jj + 1]; t2 += s[4 * jj + 2]; t3 += s[4 * jj + 3];
      }
      l0 += t0 + t1; l1 += t2 + t3;
      return grow;
    };
    auto softmax_fast = [&](uint32_t (&pp)[16], auto first, auto hook) -> bool {
      const float b0 = -m0 * SC, b1 = -m1 * SC;
      float t0 = 0.f, t1 = 0.f, t2 = 0.f, t3 = 0.f;
#pragma unroll
      for (int jj = 0; jj < 8; jj++) {
        const float e0 = ex2(fmaf(s[4 * jj], SC, b0)), e1 = ex2(fmaf(s[4 * jj + 1], SC, b0));
        const float e2 = ex2(fmaf(s[4 * jj + 2], SC, b1)), e3 = ex2(fmaf(s[4 * jj + 3], SC, b1));
        hook(jj, e0);
        pp[2 * jj] = pack_bf16(e0, e1); pp[2 * jj + 1] = pack_bf16(e2, e3);
        if (jj == 0) { t0 = e0; t1 = e1; t2 = e2; t3 = e3; } else { t0 += e0; t1 += e1; t2 += e2; t3 += e3; }
      }
      t0 += t1; t2 += t3;
      bool redo = __any_sync(0xffffffffu, !(t0 + t2 <= 16777216.f));
      if (decltype(first)::value) {
        uint32_t u0 = __ballot_sync(0xffffffffu, t0 >= 1.52587890625e-05f), u1 = __ballot_sync(0xffffffffu, t2 >= 1.52587890625e-05f);
        u0 |= u0 >> 1; u1 |= u1 >> 1;
        redo |= (((u0 | (u0 >> 2)) & (u1 | (u1 >> 2))) & 0x11111111u) != 0x11111111u;
      }
      if (!redo) { l0 += t0; l1 += t2; }
      return redo;
    };
    auto rescale = [&]() {
#pragma unroll
      for (int i = 0; i < 32; i++) { acc[4 * i] *= a0; acc[4 * i + 1] *= a0; acc[4 * i + 2] *= a1; acc[4 * i + 3] *= a1; }
    };
    auto to_p = [&](uint32_t (&pp)[16]) {
#pragma unroll
      for (int i = 0; i < 16; i++) pp[i] = pack_bf16(s[2 * i], s[2 * i + 1]);
    };
    auto q_free = [&]() { if (lane == 0) mbar_arrive(bar_addr(sb, B_QFREE + w)); };

    const int n = 2 * (which ? 15 - t : t) + 1 + (w ^ which);
    uint32_t ks = take(rdy0);
    TS(9 + 5 * which);
    prep_qk(sb + ks * SLOT);
    turn_begin();
    TS(20 + 10 * which);
    wg_fence();
    issue_qk();
    wg_commit();
    turn_end();
    if (which == 1) give(take(rdy1));
    TS(22 + 10 * which);
    wg_wait<0>();
    TS(21 + 10 * which);
    reg_fence(s);
    give(ks);
    if (which == 0 && n == 1) q_free();
    if (which == 1 || n == 1) mask_diag();
    {
      const uint4* dst = at<uint4>(g_qc, (uint32_t)((g * 16 + t) * 2 + w) * 32768 + (fresh_tid() & 127) * 16);
      const bool redo = softmax_fast(pa, Int<1>(), [&](int jj, float e) {
        if (jj == 7) peek2();
        const int i = 8 + jj;
        asm volatile("{\n.reg .pred p, q;\nsetp.ne.b32 q, %6, 0;\nsetp.geu.and.f32 p, %5, 0fBF800000, q;\n@p st.global.v4.u32 [%0], {%1, %2, %3, %4};\n}"
                       :: "l"(dst + i * 128), "r"(pk[4 * i]), "r"(pk[4 * i + 1]), "r"(pk[4 * i + 2]), "r"(pk[4 * i + 3]), "f"(e), "r"(which) : "memory");
      });
      if (redo) {
        m0 = -INFINITY; m1 = -INFINITY;
        softmax();
        to_p(pa);
      }
    }
    if (which == 1) warp_arrive(bar_addr(sb, B_ST_CTX + w), lane);
    TS(10 + 5 * which);
#pragma unroll 1
    for (int jj = 1; jj < n; jj++) {
      ks = take(rdy0);
      const uint32_t vs = take(rdy1);
      prep_qk(sb + ks * SLOT);
      prep_pv(sb + vs * SLOT);
      TSC(23 + 10 * which, jj == 1);
      turn_begin();
      TSC(24 + 10 * which, jj == 1);
      TSC(26 + 10 * which, jj == n - 1);
      wg_fence();
      issue_qk();
      wg_commit();
      issue_pv(jj > 1);
      wg_commit();
      turn_end();
      wg_wait<1>();
      TSC(25 + 10 * which, jj == 1);
      reg_fence(s);
      give(ks);
      if (jj == n - 1 && which == 0) { q_free(); mask_diag(); }
      if (softmax_fast(pb, Int<0>(), [](int, float) {})) {
        wg_wait<0>();
        reg_fence(acc);
        if (softmax()) rescale();
        to_p(pb);
      }
      peek2();
      wg_wait<0>();
      reg_fence(acc);
      reg_fence(pa);
      give(vs);
#pragma unroll
      for (int i = 0; i < 16; i++) pa[i] = pb[i] | (vs >> 8);
    }
    TS(11 + 5 * which);
    if (which == 0) { give(take(rdy0)); rdy0 = rdy1; }
    {
      const uint32_t vs = take(rdy0);
      prep_pv(sb + vs * SLOT);
      TS(27 + 10 * which);
      turn_begin();
      TS(28 + 10 * which);
      wg_fence();
      issue_pv(n > 1);
      wg_commit();
      turn_end();
      l0 += __shfl_xor_sync(0xffffffffu, l0, 1); l1 += __shfl_xor_sync(0xffffffffu, l1, 1);
      l0 += __shfl_xor_sync(0xffffffffu, l0, 2); l1 += __shfl_xor_sync(0xffffffffu, l1, 2);
      asm("rcp.approx.ftz.f32 %0, %0;" : "+f"(l0));
      asm("rcp.approx.ftz.f32 %0, %0;" : "+f"(l1));
      peek2();
      if (which == 0) mbar_wait(bar_addr(sb, B_QFULL + w), 0);
      wg_wait<0>();
      reg_fence(acc);
      reg_fence(pa);
      give(vs);
    }
    TS(12 + 5 * which);
    if (which == 1) { il0 = l0; il1 = l1; break; }
    {
      const uint4* dst = at<uint4>(g_qc, (uint32_t)((g * 16 + t) * 2 + w) * 32768 + (fresh_tid() & 127) * 16);
#pragma unroll
      for (int i = 0; i < 16; i++) {
        const int c = (i & 1) ? (i >> 1) + 8 : i >> 1;
        normalise(c, l0, l1);
        if (c < 8)
          asm volatile("st.global.v4.u32 [%0], {%1, %2, %3, %4};"
                       :: "l"(dst + c * 128), "r"(pk[4 * c]), "r"(pk[4 * c + 1]), "r"(pk[4 * c + 2]), "r"(pk[4 * c + 3]) : "memory");
      }
    }
    TS(13 + 5 * which);
  }

  {
    float oa[32], ob[32];
#pragma unroll
    for (int i = 0; i < 32; i++) { oa[i] = 0.f; ob[i] = 0.f; }
    uint32_t pk2[64];
    auto stage = [&](float (&o)[32], int ch) {
      reg_fence(o);
      uint32_t q[16];
#pragma unroll
      for (int i = 0; i < 16; i++) q[i] = pack_bf16(o[2 * i], o[2 * i + 1]);
      if (ch >= 4) mbar_wait(bar_addr(sb, B_S2_EMPTY + w * 4 + (ch & 3)), 0);
      store_block(qreg + (ch & 3) * 8192, lane_base16(), q);
    };
    auto hand_over = [&](int ch) {
      fence_async_smem();
      warp_arrive(bar_addr(sb, B_S2_FULL + w * 4 + (ch & 3)), lane);
    };
    uint32_t prev = 0;
    auto half = [&](int f, float (&o)[32], uint32_t (&a)[64], int accumulate) {
      if (f == 0) {
#pragma unroll
        for (int c = 0; c < NB; c++) normalise(c, il0, il1);
        TS(18);
      }
      const uint32_t sl = take(rdy0);
      const uint64_t d = desc_mn(sb + sl * SLOT);
      turn_begin();
      TS(40 + f);
      if (f == 0) {
#pragma unroll
        for (int c = NB; c < 16; c++) normalise(c, il0, il1);
      }
      wg_fence();
#pragma unroll
      for (int kk = 0; kk < 16; kk++) {
        wgmma_rs_n64_tb(o, a[4 * kk], a[4 * kk + 1], a[4 * kk + 2], a[4 * kk + 3], desc_add(d, kk * 2048), accumulate | kk);
        if (kk == 12 && (f < 13 || w == 0)) turn_end();
      }
      wg_commit();
      if (f < 13) rdy0 = mbar_test(bar_addr(sb, B_FULL + r.slot), r.phase);
      wg_wait<1>();
      if (f >= 1 && f <= 9) give(prev);
      prev = sl;
    };
    auto load_ctx = [&](auto h0) {
      constexpr int I0 = decltype(h0)::value * 8, NL = 8;
      const uint4* src = at<const uint4>(g_qc, (uint32_t)((g * 16 + 15 - t) * 2 + (w ^ 1)) * 32768 + (fresh_tid() & 127) * 16);
#pragma unroll
      for (int i = I0; i < I0 + NL; i++) { const uint4 v = __ldcg(src + i * 128); pk2[4 * i] = v.x; pk2[4 * i + 1] = v.y; pk2[4 * i + 2] = v.z; pk2[4 * i + 3] = v.w; }
    };
    half(0, oa, pk, 0);
    mbar_wait(bar_addr(sb, B_CTXOK + w), 0);
    load_ctx(Int<0>());
    half(1, ob, pk, 0);
    load_ctx(Int<1>());
    half(2, oa, pk2, 1);
#pragma unroll 1
    for (int i = 0; i < 3; i++) {
      half(4 * i + 3, ob, pk2, 1);
      if (i == 0) stage(oa, 0);
      half(4 * i + 4, oa, pk, 0);
      if (i == 0) hand_over(0);
      stage(ob, 2 * i + 1);
      hand_over(2 * i + 1);
      half(4 * i + 5, oa, pk2, 1);
      if (i == 2) break;
      half(4 * i + 6, ob, pk, 0);
      stage(oa, 2 * i + 2);
      hand_over(2 * i + 2);
    }
    mbar_wait(bar_addr(sb, B_S2_EMPTY + w * 4 + 2), 0);
    const uint32_t lb = lane_base16();
    wg_wait<0>();
    reg_fence(pk);
    reg_fence(pk2);
    reg_fence(oa);
    uint32_t q[16];
#pragma unroll
    for (int i = 0; i < 16; i++) q[i] = pack_bf16(oa[2 * i], oa[2 * i + 1]);
    store_block(qreg + 2 * 8192, lb, q);
    fence_async_smem();
    named_sync(1 + w, 128);
    if (wq == 0 && lane == 0) {
      tma_red2(&p.o, qreg + 2 * 8192, DA + 6 * 64, (15 - t) * 128 + (w ^ 1) * 64);
      bulk_commit();
      bulk_wait_read();
    }
  }
  TS(19);
  TDUMP();
}

namespace ssm {
constexpr int NCH = DA / NCONV;
constexpr int NS = 8, NP = 6;
constexpr uint32_t X0 = 384;
constexpr uint32_t HO = X0 + 4096;
constexpr uint32_t HE = HO + HO_STRIDE + 64;
constexpr uint32_t SSLOT = HE + 4096 + 64;
constexpr uint32_t PART = 264 * 16;
constexpr uint32_t OFF_P = NS * SSLOT, OFF_D = OFF_P + NP * 4 * PART, END = OFF_D + NCH * 4;
static_assert(SSLOT % 128 == 0 && HO % 128 == 0 && END <= BARS, "smem");
enum : uint32_t { B_FULL = 0, B_EMPTY = NS, B_PFULL = 2 * NS, B_PEMPTY = 2 * NS + NP };
__device__ __forceinline__ int channel(int cidx, int i) { return (i >> 4) * 64 + cidx * 16 + (i & 15); }

__device__ __forceinline__ void producer(const Params& p, uint32_t sb, int cidx, unsigned epoch) {
#pragma unroll 1
  for (int i = 0; i < NCH; i++) {
    const int s = i % NS, ch = channel(cidx, i);
    const uint32_t full = bar_addr(sb, B_FULL + s), dst = sb + s * SSLOT;
    mbar_wait(bar_addr(sb, B_EMPTY + s), ((i / NS) & 1) ^ 1);
    mbar_expect_tx(full, 4096 + 4128 + 4096);
    bulk_ld(dst + HE, at<uint8_t>(p.a_ssmk, ch * 4096), 4096, full);
    if ((i & 15) == 0) { flag_wait<20>(flag_at(g_flags.x_ready, i >> 4), NMAIN, epoch); fence_async_global(); }
    bulk_ld(dst + HO, at<uint8_t>(g_ho, ch * HO_STRIDE), 4128, full);
    bulk_ld(dst + X0, at<uint8_t>(g_xs, ch * 4096), 4096, full);
  }
}

__device__ __forceinline__ void reducer(uint32_t sb, int cidx, int rw) {
  uint32_t n = 0;
#pragma unroll 1
  for (int i = rw; i < NCH; i += 3, n++) {
    const uint32_t b = rw + 3 * (n & 1), pb = sb + OFF_P + b * 4 * PART;
    uint8_t* dst = at<uint8_t>(g_xs, channel(cidx, i) * 4096);
    mbar_wait(bar_addr(sb, B_PFULL + b), (n >> 1) & 1);
    asm volatile("cp.async.bulk.global.shared::cta.bulk_group [%0], [%1], 4096;" :: "l"(dst), "r"(pb + 3 * PART) : "memory");
    bulk_commit();
    bulk_wait_all();
#pragma unroll
    for (int k = 2; k >= 0; k--)
      asm volatile("cp.reduce.async.bulk.global.shared::cta.bulk_group.add.noftz.bf16 [%0], [%1], 4096;" :: "l"(dst), "r"(pb + k * PART) : "memory");
    bulk_commit();
    bulk_wait_read();
    mbar_arrive(bar_addr(sb, B_PEMPTY + b));
    if (((i + 3) >> 4) != (i >> 4)) {
      bulk_wait_all();
      fence_async_global();
      flag_signal(flag_at(g_flags.z_ready, i >> 4));
    }
  }
}

__device__ __forceinline__ void mma_warpgroup(uint32_t sb, int w) {
  const int lane = threadIdx.x & 31, g = lane >> 2, c = lane & 3, wq = (threadIdx.x >> 5) & 3;
  const uint32_t aoff = ((g & 1) ? HO + 30 : HE) + (16 * wq - g + 2 * c) * 2;
  const uint32_t poff = OFF_P + wq * PART + (2 * wq + lane) * 16;
  const uint32_t dmask = (wq == 0 && c == (g >> 1)) ? ((g & 1) ? 0xffff0000u : 0xffffu) : 0u;
  float acc[8][16];
  uint32_t fa[16][4];
#pragma unroll
  for (int e = 0; e < 8; e++)
#pragma unroll
    for (int i = 0; i < 16; i++) acc[e][i] = 0.f;
  auto load_a = [&](int m, uint32_t ad) {
    fa[m][0] = lds4(ad + m * 256 + 16); fa[m][1] = lds4(ad + m * 256 + 144); fa[m][2] = lds4(ad + m * 256); fa[m][3] = lds4(ad + m * 256 + 128);
  };
  if (w == 1) named_arrive(PP_BAR, 256);
  mbar_wait(bar_addr(sb, B_FULL + w), 0);
#pragma unroll
  for (int m = 0; m < 16; m++) load_a(m, sb + w * SSLOT + aoff);
  uint32_t dd = lds4(sb + OFF_D + w * 4);
  if (threadIdx.x == 128) { GT(12); PT(10); }
  uint32_t pb = w, pphase = 1;
#pragma unroll 1
  for (int i = w; i < NCH; i += 2) {
    fa[0][2] = badd(fa[0][2], dd & dmask);
    const uint64_t db = (uint64_t)((((sb + (i % NS) * SSLOT + X0 - 16) & 0x3FFFF) >> 4) | (1u << 16)) | ((uint64_t)8 << 32);
    named_sync(PP_BAR + w, 256);
    wg_fence();
#pragma unroll
    for (int r = 0; r < 16; r++) {
      auto mm = [&](int e, int m) { wgmma_rs_n32(acc[e], fa[m][0], fa[m][1], fa[m][2], fa[m][3], db + (int64_t)(32 * e - 16 * m), m != 0); };
      mm(7, r);
      if (r < 14) mm(6, r); else mm(0, r - 14);
      if (r < 12) mm(5, r); else mm(1, r - 12);
      if (r < 10) mm(4, r); else mm(2, r - 10);
      if ((r & 1) == 0) mm(3, r >> 1);
      if (r == 13 && (i + 1 < NCH)) named_arrive(PP_BAR + (w ^ 1), 256);
    }
    wg_commit();
    const int nx = i + 2 < NCH ? i + 2 : i;
    mbar_wait(bar_addr(sb, B_FULL + nx % NS), (nx / NS) & 1);
    mbar_wait(bar_addr(sb, B_PEMPTY + pb), pphase);
    const uint32_t ad = sb + (nx % NS) * SSLOT + aoff, pa = sb + pb * 4 * PART + poff;
    wg_wait<0>();
#pragma unroll
    for (int e = 0; e < 8; e++) reg_fence(acc[e]);
#pragma unroll
    for (int m = 0; m < 16; m++) reg_fence(fa[m]);
    if (lane == 0) mbar_arrive(bar_addr(sb, B_EMPTY + i % NS));
#pragma unroll
    for (int e = 0; e < 8; e++) {
      load_a(e, ad);
      uint32_t u[4];
#pragma unroll
      for (int j = 0; j < 4; j++) {
        const int T = 4 * e + j, U = T - 1;
        float lo = acc[e][4 * j], hi = acc[e][4 * j + 1];
        if (T > 0) { lo += acc[U >> 2][4 * (U & 3) + 2]; hi += acc[U >> 2][4 * (U & 3) + 3]; }
        u[j] = pack_bf16(lo, hi);
      }
      asm volatile("stmatrix.sync.aligned.m8n8.x4.trans.shared.b16 [%0], {%1, %2, %3, %4};" :: "r"(pa + e * 512), "r"(u[0]), "r"(u[1]), "r"(u[2]), "r"(u[3]) : "memory");
    }
    dd = lds4(sb + OFF_D + nx * 4);
#pragma unroll
    for (int m = 8; m < 12; m++) load_a(m, ad);
    fence_async_smem();
    warp_arrive(bar_addr(sb, B_PFULL + pb), lane);
#pragma unroll
    for (int m = 12; m < 16; m++) load_a(m, ad);
    pb += 2;
    if (pb >= NP) { pb -= NP; pphase ^= 1; }
  }
  if (threadIdx.x == 128) { PT(9); GT(13); }
}

__device__ __forceinline__ void init(const Params& p, uint32_t sb, int cidx) {
  const uint32_t t = threadIdx.x;
  if (t < NCH) {
    const uint32_t d = (uint32_t)__ldg(reinterpret_cast<const unsigned short*>(p.a_D + channel(cidx, t))) * 0x10001u;
    asm volatile("st.shared.u32 [%0], %1;" :: "r"(sb + OFF_D + t * 4), "r"(d) : "memory");
  }
#pragma unroll 1
  for (uint32_t u = t; u < NS * 32; u += 128) {
    const uint32_t r = u & 31;
    if (r < 28) sts16(sb + (u >> 5) * SSLOT + (r < 24 ? r * 16 : HE - 64 + (r - 24) * 16), 0, 0, 0, 0);
    if (u < NP * 32) sts16(sb + OFF_P + (u >> 3) * PART + (u & 7) * 16, 0, 0, 0, 0);
  }
  if (t == 0) {
    for (int i = 0; i < NS; i++) { mbar_init(bar_addr(sb, B_FULL + i), 1); mbar_init(bar_addr(sb, B_EMPTY + i), 4); }
    for (int i = 0; i < NP; i++) { mbar_init(bar_addr(sb, B_PFULL + i), 4); mbar_init(bar_addr(sb, B_PEMPTY + i), 1); }
  }
  fence_async_smem();
}

__device__ __forceinline__ void side_prepare(const Params& p, int cta, int rd) {
  const int lane = threadIdx.x & 31, t0 = 16 * cta + 8 * (lane & 1);
#pragma unroll 1
  for (int ch = 64 * rd + (lane & ~1); ch < 64 * rd + 64; ch += 32) {
    const uint4 sv = __ldg(at<const uint4>(p.a_shift, ch * 8));
    const uint32_t* kp = at<const uint32_t>(p.a_k, (t0 * DA + ch) * 2);
    const uint32_t* vp = at<const uint32_t>(p.a_v, (t0 * DA + ch) * 2);
    uint32_t k0 = 0, k1 = 0, k2 = 0, kk[8], x[8];
    if (t0 > 0) { k0 = __ldg(kp - 3 * (DA / 2)); k1 = __ldg(kp - 2 * (DA / 2)); k2 = __ldg(kp - DA / 2); }
#pragma unroll
    for (int i = 0; i < 8; i++) { kk[i] = __ldg(kp + i * (DA / 2)); x[i] = __ldg(vp + i * (DA / 2)); }
    const uint32_t sh0 = __byte_perm(sv.x, sv.z, 0x5410), sh1 = __byte_perm(sv.x, sv.z, 0x7632);
    const uint32_t sh2 = __byte_perm(sv.y, sv.w, 0x5410), sh3 = __byte_perm(sv.y, sv.w, 0x7632);
#pragma unroll
    for (int i = 0; i < 8; i++) {
      uint32_t ks = bmul(k0, sh3);
      ks = badd(ks, bmul(k1, sh2)); ks = badd(ks, bmul(k2, sh1)); ks = badd(ks, bmul(kk[i], sh0));
      x[i] = bmul(ks, x[i]);
      k0 = k1; k1 = k2; k2 = kk[i];
    }
    uint4* dst = at<uint4>(g_xs, ch * 4096 + t0 * 2);
    dst[0]   = make_uint4(__byte_perm(x[7], x[6], 0x5410), __byte_perm(x[5], x[4], 0x5410), __byte_perm(x[3], x[2], 0x5410), __byte_perm(x[1], x[0], 0x5410));
    dst[256] = make_uint4(__byte_perm(x[7], x[6], 0x7632), __byte_perm(x[5], x[4], 0x7632), __byte_perm(x[3], x[2], 0x7632), __byte_perm(x[1], x[0], 0x7632));
  }
  {
    const int hc = 64 * rd + (cta >> 1), r0 = (cta & 1) * 128 + lane;
    const uint4* src = at<const uint4>(p.a_ssmk, hc * 4096 + r0 * 16);
    uint4* dst = at<uint4>(g_ho, hc * HO_STRIDE + r0 * 16);
    uint4 w[4];
    uint32_t nx[4];
#pragma unroll
    for (int i = 0; i < 4; i++) { w[i] = __ldg(src + 32 * i); nx[i] = r0 + 32 * i < 255 ? __ldg(reinterpret_cast<const uint32_t*>(src + 32 * i + 1)) : 0u; }
#pragma unroll
    for (int i = 0; i < 4; i++)
      dst[32 * i + 2] = make_uint4(__byte_perm(w[i].x, w[i].y, 0x5432), __byte_perm(w[i].y, w[i].z, 0x5432), __byte_perm(w[i].z, w[i].w, 0x5432), __byte_perm(w[i].w, nx[i], 0x5432));
    const uint32_t h0 = __shfl_sync(0xffffffffu, w[0].x, 0);
    if (r0 < 2) dst[0] = make_uint4(0, 0, 0, r0 ? h0 << 16 : 0u);
  }
  __syncwarp();
  if (lane == 0) flag_signal(flag_at(g_flags.x_ready, rd));
}
__device__ __forceinline__ void side_finish(const Params& p, int cta, int rd) {
  const int lane = threadIdx.x & 31, t0 = 16 * cta + 8 * (lane & 1);
#pragma unroll 1
  for (int ch = 64 * rd + (lane & ~1); ch < 64 * rd + 64; ch += 32) {
    const uint4* src = at<const uint4>(g_xs, ch * 4096 + t0 * 2);
    const uint32_t* qp = at<const uint32_t>(p.a_q, (t0 * DA + ch) * 2);
    uint32_t* op = at<uint32_t>(p.out, (t0 * OUTW + ch) * 2);
    const uint4 z0 = __ldcg(src), z1 = __ldcg(src + 256);
    uint32_t q[8];
#pragma unroll
    for (int i = 0; i < 8; i++) q[i] = __ldg(qp + i * (DA / 2));
    const uint32_t a[4] = {z0.w, z0.z, z0.y, z0.x}, b[4] = {z1.w, z1.z, z1.y, z1.x};
#pragma unroll
    for (int i = 0; i < 4; i++) {
      op[(2 * i) * (OUTW / 2)]     = bmul(q[2 * i], __byte_perm(a[i], b[i], 0x7632));
      op[(2 * i + 1) * (OUTW / 2)] = bmul(q[2 * i + 1], __byte_perm(a[i], b[i], 0x5410));
    }
  }
}
__device__ __forceinline__ void clear_rows(const Params& p, int qt, int part) {
  const int lane = threadIdx.x & 31;
  if (lane < 28) {
    uint4* z = at<uint4>(p.out, ((qt * 128 + part * 16) * OUTW + DA) * 2 + lane * 16);
#pragma unroll
    for (int i = 0; i < 32; i++) z[(i >> 1) * (OUTW / 8) + (i & 1) * 28] = make_uint4(0, 0, 0, 0);
  }
  __syncwarp();
  if (lane == 0) flag_signal(flag_at(g_flags.zero_ready, qt));
}
__device__ __forceinline__ void side_work(const Params& p, int cta, unsigned epoch) {
#pragma unroll 1
  for (int rd = -SIDE_AHEAD; rd < EXP_LASTRD; rd++) {
    if (rd >= 0) {
      if ((threadIdx.x & 31) == 0) flag_wait<1000>(flag_at(g_flags.z_ready, rd), 3 * NCONV, epoch);
      __syncwarp();
    }
    if (rd + SIDE_AHEAD < 7) side_prepare(p, cta, rd + SIDE_AHEAD);
    if (rd >= 0) side_finish(p, cta, rd);
    if (rd == ZERO_RD) clear_rows(p, cta & 15, cta >> 4);
  }
}
}

__global__ void __cluster_dims__(2, 1, 1) __launch_bounds__(NTHREADS, 1)
concat_heads__ssm_conv_h3__compressed_kv_cla__prompt_kernel(const __grid_constant__ Params p) {
  extern __shared__ uint8_t smem_raw[];
  const uint32_t sb = (smem_u32(smem_raw) + 1023) & ~1023u;
  if (threadIdx.x == NTHREADS - 64) { prefetch_map(&p.wuk); prefetch_map(&p.ckv); }
  const int cta = blockIdx.x;
  const bool attn = cta < NMAIN;
  int g, t;
  {
    const int c = cta >> 1, u2 = ((c - 36) * 37) >> 8, i = c - 36 - 7 * u2;
    g = c < 4 ? 1 : c < 36 ? (c - 4) & 7 : i == 0 ? 0 : 1 + i;
    t = 2 * (c < 4 ? c : c < 36 ? 7 - ((c - 4) >> 3) : u2) + (cta & 1);
  }
  if (attn && threadIdx.x == NTHREADS - 32) {
    const uint32_t full = bar_addr(sb, B_FULL);
    mbar_init(full, 1);
    asm volatile("fence.mbarrier_init.release.cluster;" ::: "memory");
    mbar_expect_tx(full, 49152);
    load_w(p, g, t, 0, sb, full);
    load_a(p, g, t, 0, sb + QREG, full);
  }
  __syncwarp();
  const int lane = threadIdx.x & 31;
  const int warp = __shfl_sync(0xffffffffu, threadIdx.x >> 5, 0);
  const int wg = warp >> 2;
  if (wg != 0) {
    if (attn) {
      cluster_arrive();
      if (wg == 2) named_arrive(PP_BAR, 256);
    }
    asm volatile("setmaxnreg.inc.sync.aligned.u32 232;");
    if (!attn) {
      if (p.out != nullptr) { named_sync(0, NTHREADS); ssm::mma_warpgroup(sb, wg - 1); }
      return;
    }
    if (p.out != nullptr) consumer_main(p, sb, g, t, wg - 1, warp & 3);
  } else {
    asm volatile("setmaxnreg.dec.sync.aligned.u32 40;");
    if (!attn) {
      ssm::init(p, sb, cta - NMAIN);
      named_sync(0, NTHREADS);
      if (lane == 0) {
        if (warp == 0) { ssm::producer(p, sb, cta - NMAIN, load_epoch()); cta_done(32); }
        else ssm::reducer(sb, cta - NMAIN, warp - 1);
        if (warp == 1) GT(14);
      }
      return;
    }
    if (warp == 0) {
      if (lane == 0) {
        for (int i = 1; i < NSLOT; i++) mbar_init(bar_addr(sb, B_FULL + i), 1);
        asm volatile("fence.mbarrier_init.release.cluster;" ::: "memory");
      }
      __syncwarp();
      cluster_arrive();
      if (lane == 0) {
#pragma unroll 1
        for (int k = 1; k < EARLY_LD; k++) {
          const uint32_t full = bar_addr(sb, B_FULL + k);
          mbar_expect_tx(full, 49152);
          load_w(p, g, t, k & 15, sb + k * SLOT, full);
          load_a(p, g, t, k & 15, sb + QREG + k * 16384, full);
          __nanosleep(200);
        }
      }
      __syncwarp();
      cluster_wait();
      if (lane == 0) producer_main(p, sb, g, t);
      return;
    }
    if (lane == 0) {
      if (warp == 1) {
        for (int i = 0; i < NSLOT; i++) mbar_init(bar_addr(sb, B_EMPTY + i), 16);
        for (int i = 0; i < 2; i++) {
          mbar_init(bar_addr(sb, B_QFREE + i), 4); mbar_init(bar_addr(sb, B_QFULL + i), 1);
          mbar_init(bar_addr(sb, B_CTXOK + i), 1);
        }
      } else if (warp == 2) {
        for (int i = 0; i < 8; i++) { mbar_init(bar_addr(sb, B_S2_FULL + i), 4); mbar_init(bar_addr(sb, B_S2_EMPTY + i), 1); }
      } else {
        mbar_init(bar_addr(sb, B_DONE), 2);
        mbar_init(bar_addr(sb, B_KVOK), 1); mbar_init(bar_addr(sb, B_PF), 1);
        for (int i = 0; i < 2; i++) {
          mbar_init(bar_addr(sb, B_ST_KV + i), 4); mbar_init(bar_addr(sb, B_ST_Q + i), 4); mbar_init(bar_addr(sb, B_ST_CTX + i), 4);
        }
      }
      asm volatile("fence.mbarrier_init.release.cluster;" ::: "memory");
    }
    __syncwarp();
    cluster_arrive();
    cluster_wait();
    if (warp < 3) {
      if (warp == 2) {
        mbar_wait(bar_addr(sb, B_PF), 0);
        const uint8_t* a = at<const uint8_t>(p.b_x, (g * 16 + t) * 16 * DM * 2 + lane * 128);
#pragma unroll 1
        for (int i = 0; i < 4; i++) {
          if (i < 3 || lane < 16) asm volatile("prefetch.global.L2 [%0];" :: "l"(a + i * 4096));
          __nanosleep(1000);
        }
      }
      if (lane == 0) {
        if (warp == 1) { __nanosleep(2000); prefetch_map(&p.wuv); prefetch_map(&p.x); prefetch_map(&p.wq); prefetch_map(&p.o); prefetch_map(&p.wo); }
        helper_main(p, sb, g, t, warp - 1);
      }
    } else {
      ssm::side_work(p, g * 16 + t, load_epoch());
      if (lane == 0) { GT(57); mbar_wait(bar_addr(sb, B_DONE), 0); cta_done(1); }
    }
  }
}

typedef CUresult (*EncodeTiledFn)(CUtensorMap*, CUtensorMapDataType, cuuint32_t, void*, const cuuint64_t*, const cuuint64_t*,
                                  const cuuint32_t*, const cuuint32_t*, CUtensorMapInterleave, CUtensorMapSwizzle,
                                  CUtensorMapL2promotion, CUtensorMapFloatOOBfill);

void make_map(EncodeTiledFn enc, CUtensorMap* m, const void* ptr, int rank, const uint64_t* dims, const uint64_t* strides, const uint32_t* box) {
  cuuint64_t d[5], s[4]; cuuint32_t b[5], e[5] = {1, 1, 1, 1, 1};
  for (int i = 0; i < rank; i++) { d[i] = dims[i]; b[i] = box[i]; if (i) s[i - 1] = strides[i - 1]; }
  enc(m, CU_TENSOR_MAP_DATA_TYPE_BFLOAT16, rank, const_cast<void*>(ptr), d, s, b, e, CU_TENSOR_MAP_INTERLEAVE_NONE,
      CU_TENSOR_MAP_SWIZZLE_128B, CU_TENSOR_MAP_L2_PROMOTION_L2_256B, CU_TENSOR_MAP_FLOAT_OOB_FILL_NONE);
}
void map2(EncodeTiledFn enc, CUtensorMap* m, const void* ptr, uint64_t cols, uint64_t rows, uint32_t bc, uint32_t br) {
  const uint64_t dims[2] = {cols, rows}, st[1] = {cols * 2}; const uint32_t box[2] = {bc, br};
  make_map(enc, m, ptr, 2, dims, st, box);
}
void map3(EncodeTiledFn enc, CUtensorMap* m, const void* ptr, uint64_t rows, uint32_t nblk) {
  const uint64_t dims[3] = {64, rows, 64}, st[2] = {8192, 128}; const uint32_t box[3] = {64, 64, nblk};
  make_map(enc, m, ptr, 3, dims, st, box);
}

}

extern "C" void kernel_launch(void* const* d_in, const int* in_sizes, int n_in, void* d_out, int out_size) {
  (void)in_sizes; (void)n_in; (void)out_size;
  static EncodeTiledFn enc = nullptr;
  if (!enc) {
    void* fn = nullptr; cudaDriverEntryPointQueryResult qr;
    cudaGetDriverEntryPoint("cuTensorMapEncodeTiled", &fn, cudaEnableDefault, &qr);
    enc = (EncodeTiledFn)fn;
    cudaFuncSetAttribute(concat_heads__ssm_conv_h3__compressed_kv_cla__prompt_kernel, cudaFuncAttributeMaxDynamicSharedMemorySize, SMEM_BYTES);
  }
  Params p;
  p.a_q = (const bf16*)d_in[0]; p.a_k = (const bf16*)d_in[1]; p.a_v = (const bf16*)d_in[2];
  p.a_shift = (const bf16*)d_in[3]; p.a_ssmk = (const bf16*)d_in[4]; p.a_D = (const bf16*)d_in[5];
  p.out = (bf16*)d_out;
  p.b_x = (const bf16*)d_in[6];
  map2(enc, &p.x, d_in[6], DM, SEQ, 64, 128);
  map2(enc, &p.ckv, d_in[7], DC, SEQ, 64, 128);
  map3(enc, &p.wq, d_in[8], DM, 4);
  map3(enc, &p.wuk, d_in[9], DC, 4);
  map3(enc, &p.wuv, d_in[10], DC, 4);
  {
    const uint64_t dims[5] = {DM, 2, 4, 4, NH * HD / 32}, st[4] = {DM * 2, 8 * DM * 2, 2 * DM * 2, 32 * DM * 2}; const uint32_t box[5] = {64, 2, 4, 4, 4};
    make_map(enc, &p.wo, d_in[11], 5, dims, st, box);
  }
  map2(enc, &p.o, d_out, OUTW, SEQ, 64, 64);
  concat_heads__ssm_conv_h3__compressed_kv_cla__prompt_kernel<<<NCTA, NTHREADS, SMEM_BYTES>>>(p);
}
```

```cpp
#include <cuda_runtime.h>
#include <cuda_bf16.h>
#include <cuda.h>
#include <stdint.h>

namespace {

typedef __nv_bfloat16 bf16;

constexpr int SEQ  = 2048;
constexpr int DA   = 448;
constexpr int NH   = 16;
constexpr int HD   = 256;
constexpr int DM   = 448;
constexpr int DC   = 1024;
constexpr int OUTW = DA + DM;
constexpr int NMAIN = 128;
constexpr int NCONV = 4;
constexpr int NCTA  = NMAIN + NCONV;
constexpr int LOG_DONE = 8;
constexpr int NTHREADS = 384;

__device__ __align__(1024) bf16 g_kv[2ull * SEQ * NH * HD];
__device__ __align__(1024) bf16 g_qc[(size_t)NMAIN * 128 * HD];
__device__ __align__(128) uint8_t g_xs[DA * SEQ * 2];
constexpr uint32_t HO_STRIDE = 4224;
__device__ __align__(128) uint8_t g_ho[DA * HO_STRIDE];
struct alignas(128) Flag { unsigned v; unsigned pad[31]; };
struct Flags {
  Flag kv_ready[8];
  Flag ctx_ready[NMAIN * 2];
  Flag x_wanted[7];
  Flag x_ready[7];
  Flag z_ready[7];
  Flag zero_ready[16];
  alignas(128) unsigned long long done;
};
__device__ Flags g_flags;
#define TS(i)
#define TSC(i, cond)
#define TDUMP()
#define GT(i)
#define PT(i)

struct alignas(64) Params {
  CUtensorMap ckv;
  CUtensorMap wuk;
  CUtensorMap wuv;
  CUtensorMap x;
  CUtensorMap wq;
  CUtensorMap o;
  CUtensorMap wo;
  const bf16 *a_q, *a_k, *a_v, *a_shift, *a_ssmk, *a_D, *b_x;
  bf16* out;
};

constexpr uint32_t SLOT     = 32768;
constexpr int      NSLOT    = 5;
constexpr uint32_t QREG     = 163840;
constexpr uint32_t BARS     = 229376;
constexpr uint32_t SMEM_BYTES = BARS + 1024 + 1024;
enum : uint32_t {
  B_FULL = 0, B_EMPTY = 5, B_KVOK = 10, B_DONE = 11, B_ST_KV = 12, B_ST_Q = 14, B_ST_CTX = 16, B_CTXOK = 18, B_QFREE = 20, B_QFULL = 22,
  B_S2_FULL = 24, B_S2_EMPTY = 32, B_PF = 40
};
constexpr int P1_STEPS = 4 * 16 + 2 * 7, P1_XS = P1_STEPS - 2;

template <typename T> __device__ __forceinline__ T* at(const void* base, uint32_t off) {
  asm volatile("" : "+r"(off));
  return reinterpret_cast<T*>(const_cast<char*>(static_cast<const char*>(base)) + off);
}
__device__ __forceinline__ unsigned* flag_at(Flag* f, uint32_t i) { return at<unsigned>(f, i * (uint32_t)sizeof(Flag)); }
__device__ __forceinline__ uint32_t smem_u32(const void* p) { return (uint32_t)__cvta_generic_to_shared(p); }
__device__ __forceinline__ void mbar_init(uint32_t bar, uint32_t cnt) {
  asm volatile("mbarrier.init.shared::cta.b64 [%0], %1;" :: "r"(bar), "r"(cnt) : "memory");
}
__device__ __forceinline__ void mbar_expect_tx(uint32_t bar, uint32_t bytes) {
  asm volatile("mbarrier.arrive.expect_tx.shared::cta.b64 _, [%0], %1;" :: "r"(bar), "r"(bytes) : "memory");
}
__device__ __forceinline__ void mbar_arrive(uint32_t bar) {
  asm volatile("mbarrier.arrive.shared::cta.b64 _, [%0];" :: "r"(bar) : "memory");
}
__device__ __forceinline__ void mbar_arrive_remote(uint32_t bar, uint32_t cta) {
  asm volatile("{\n.reg .b32 ra;\nmapa.shared::cluster.u32 ra, %0, %1;\n"
               "mbarrier.arrive.shared::cluster.b64 _, [ra];\n}" :: "r"(bar), "r"(cta) : "memory");
}
__device__ __forceinline__ bool mbar_try(uint32_t bar, uint32_t parity) {
  uint32_t ok;
  asm volatile("{\n.reg .pred p;\nmbarrier.try_wait.parity.shared::cta.b64 p, [%1], %2;\nselp.u32 %0, 1, 0, p;\n}"
               : "=r"(ok) : "r"(bar), "r"(parity) : "memory");
  return ok;
}
__device__ __forceinline__ uint32_t mbar_test(uint32_t bar, uint32_t parity) {
  uint32_t ok;
  asm volatile("{\n.reg .pred p;\nmbarrier.test_wait.parity.shared::cta.b64 p, [%1], %2;\nselp.u32 %0, 1, 0, p;\n}"
               : "=r"(ok) : "r"(bar), "r"(parity) : "memory");
  return ok;
}
constexpr uint32_t SPIN_LIMIT = 1u << 24;
__device__ __forceinline__ void mbar_wait(uint32_t bar, uint32_t parity) {
  if (mbar_try(bar, parity)) return;
  uint32_t n = 0;
  while (!mbar_try(bar, parity)) { if (++n > SPIN_LIMIT) __trap(); }
}
__device__ __forceinline__ void mbar_wait_unless(uint32_t ready, uint32_t bar, uint32_t parity) {
  asm volatile("{\n.reg .pred p;\n.reg .b32 n;\nsetp.ne.u32 p, %0, 0;\nvote.sync.all.pred p, p, 0xffffffff;\n@p bra.uni WDONE;\nmov.u32 n, 0;\n"
               "WLOOP:\nmbarrier.try_wait.parity.shared::cta.b64 p, [%1], %2;\n@p bra.uni WDONE;\nadd.u32 n, n, 1;\nsetp.lt.u32 p, n, %3;\n@p bra.uni WLOOP;\ntrap;\nWDONE:\n}"
               :: "r"(ready), "r"(bar), "r"(parity), "n"(SPIN_LIMIT) : "memory");
}
__device__ __forceinline__ unsigned load_epoch() {
  unsigned long long d; asm volatile("ld.relaxed.gpu.global.u64 %0, [%1];" : "=l"(d) : "l"(&g_flags.done) : "memory");
  return (unsigned)(d >> LOG_DONE);
}
template <int SLEEP_NS>
__device__ __forceinline__ void flag_wait(const unsigned* f, unsigned count, unsigned epoch) {
  const unsigned target = (epoch + 1) * count;
  uint32_t n = 0;
  while (true) {
    unsigned v;
    asm volatile("ld.acquire.gpu.global.u32 %0, [%1];" : "=r"(v) : "l"(f) : "memory");
    if ((int)(v - target) >= 0) break;
    if (++n > SPIN_LIMIT / 4) __trap();
    __nanosleep(SLEEP_NS);
  }
}
__device__ __forceinline__ void flag_signal(unsigned* f) { asm volatile("red.release.gpu.global.add.u32 [%0], 1;" :: "l"(f) : "memory"); }
__device__ __forceinline__ void cta_done(unsigned long long n) { asm volatile("red.relaxed.gpu.global.add.u64 [%0], %1;" :: "l"(&g_flags.done), "l"(n) : "memory"); }
__device__ __forceinline__ void fence_async_global() { asm volatile("fence.proxy.async.global;" ::: "memory"); }
__device__ __forceinline__ void fence_async_smem() { asm volatile("fence.proxy.async.shared::cta;" ::: "memory"); }
__device__ __forceinline__ void tma_ld2(uint32_t dst, const CUtensorMap* m, uint32_t bar, int c0, int c1) {
  asm volatile("cp.async.bulk.tensor.2d.shared::cluster.global.mbarrier::complete_tx::bytes [%0], [%1, {%3, %4}], [%2];"
               :: "r"(dst), "l"(m), "r"(bar), "r"(c0), "r"(c1) : "memory");
}
__device__ __forceinline__ void tma_ld3(uint32_t dst, const CUtensorMap* m, uint32_t bar, int c0, int c1, int c2) {
  asm volatile("cp.async.bulk.tensor.3d.shared::cluster.global.mbarrier::complete_tx::bytes [%0], [%1, {%3, %4, %5}], [%2];"
               :: "r"(dst), "l"(m), "r"(bar), "r"(c0), "r"(c1), "r"(c2) : "memory");
}
__device__ __forceinline__ void tma_ld5_mc(uint32_t dst, const CUtensorMap* m, uint32_t bar, int c0, int c4) {
  asm volatile("cp.async.bulk.tensor.5d.shared::cluster.global.mbarrier::complete_tx::bytes.multicast::cluster [%0], [%1, {%3, %6, %6, %6, %4}], [%2], %5;"
               :: "r"(dst), "l"(m), "r"(bar), "r"(c0), "r"(c4), "h"((uint16_t)3), "r"(0) : "memory");
}
__device__ __forceinline__ void bulk_ld(uint32_t dst, const void* src, uint32_t bytes, uint32_t bar) {
  asm volatile("cp.async.bulk.shared::cluster.global.mbarrier::complete_tx::bytes [%0], [%1], %2, [%3];"
               :: "r"(dst), "l"(src), "r"(bytes), "r"(bar) : "memory");
}
__device__ __forceinline__ void bulk_ld_p(uint32_t dst, const void* src, uint32_t bytes, uint32_t bar, uint64_t pl) {
  asm volatile("cp.async.bulk.shared::cluster.global.mbarrier::complete_tx::bytes.L2::cache_hint [%0], [%1], %2, [%3], %4;"
               :: "r"(dst), "l"(src), "r"(bytes), "r"(bar), "l"(pl) : "memory");
}
__device__ __forceinline__ void bulk_ld_mc(uint32_t dst, const void* src, uint32_t bytes, uint32_t bar, uint64_t pl) {
  asm volatile("cp.async.bulk.shared::cluster.global.mbarrier::complete_tx::bytes.multicast::cluster.L2::cache_hint [%0], [%1], %2, [%3], %4, %5;"
               :: "r"(dst), "l"(src), "r"(bytes), "r"(bar), "h"((uint16_t)3), "l"(pl) : "memory");
}
__device__ __forceinline__ void tma_red2(const CUtensorMap* m, uint32_t src, int c0, int c1) {
  asm volatile("cp.reduce.async.bulk.tensor.2d.global.shared::cta.add.bulk_group [%0, {%2, %3}], [%1];"
               :: "l"(m), "r"(src), "r"(c0), "r"(c1) : "memory");
}
__device__ __forceinline__ void bulk_commit() { asm volatile("cp.async.bulk.commit_group;" ::: "memory"); }
__device__ __forceinline__ void bulk_wait_read() { asm volatile("cp.async.bulk.wait_group.read 0;" ::: "memory"); }
__device__ __forceinline__ void bulk_wait_all() { asm volatile("cp.async.bulk.wait_group 0;" ::: "memory"); }
__device__ __forceinline__ void prefetch_map(const CUtensorMap* m) { asm volatile("prefetch.tensormap [%0];" :: "l"(m) : "memory"); }
__device__ __forceinline__ void wg_fence() { asm volatile("wgmma.fence.sync.aligned;" ::: "memory"); }
__device__ __forceinline__ void wg_commit() { asm volatile("wgmma.commit_group.sync.aligned;" ::: "memory"); }
template <int N> __device__ __forceinline__ void wg_wait() { asm volatile("wgmma.wait_group.sync.aligned %0;" :: "n"(N) : "memory"); }
template <int N> __device__ __forceinline__ void reg_fence(float (&d)[N]) {
#pragma unroll
  for (int i = 0; i < N; i++) asm volatile("" : "+f"(d[i]) :: "memory");
}
template <int N> __device__ __forceinline__ void reg_fence(uint32_t (&d)[N]) {
#pragma unroll
  for (int i = 0; i < N; i++) asm volatile("" : "+r"(d[i]) :: "memory");
}
__device__ __forceinline__ uint32_t fresh_tid() { uint32_t t; asm volatile("mov.u32 %0, %%tid.x;" : "=r"(t)); return t; }
__device__ __forceinline__ uint32_t lane_base16() {
  const uint32_t t = fresh_tid(), lane = t & 31, wq = (t >> 5) & 3;
  return (16 * wq + (lane & 7) + 8 * ((lane >> 3) & 1)) * 128 + (((lane >> 4) ^ (lane & 7)) << 4);
}
__device__ __forceinline__ void cluster_arrive() { asm volatile("barrier.cluster.arrive.relaxed.aligned;" ::: "memory"); }
__device__ __forceinline__ void cluster_wait() { asm volatile("barrier.cluster.wait.acquire.aligned;" ::: "memory"); }
__device__ __forceinline__ void named_sync(int id, int n) { asm volatile("bar.sync %0, %1;" :: "r"(id), "r"(n) : "memory"); }
__device__ __forceinline__ void named_arrive(int id, int n) { asm volatile("bar.arrive %0, %1;" :: "r"(id), "r"(n) : "memory"); }
__device__ __forceinline__ uint32_t pack_bf16(float lo, float hi) {
  uint32_t r; asm("cvt.rn.bf16x2.f32 %0, %1, %2;" : "=r"(r) : "f"(hi), "f"(lo)); return r;
}
__device__ __forceinline__ float ex2(float x) { float y; asm("ex2.approx.ftz.f32 %0, %1;" : "=f"(y) : "f"(x)); return y; }
__device__ __forceinline__ void stsm4(uint32_t addr, uint32_t a, uint32_t b, uint32_t c, uint32_t d) {
  asm volatile("stmatrix.sync.aligned.m8n8.x4.shared.b16 [%0], {%1, %2, %3, %4};" :: "r"(addr), "r"(a), "r"(b), "r"(c), "r"(d) : "memory");
}
__device__ __forceinline__ uint64_t mk_desc(uint32_t addr, uint32_t lbo, uint32_t sbo) {
  return (uint64_t)(((addr & 0x3FFFF) >> 4) | ((lbo >> 4) << 16)) | ((uint64_t)((sbo >> 4) | (1u << 30)) << 32);
}
__device__ __forceinline__ uint64_t desc_k(uint32_t addr)  { return mk_desc(addr, 16, 1024); }
__device__ __forceinline__ uint64_t desc_mn(uint32_t addr) { return mk_desc(addr, 8192, 1024); }
__device__ __forceinline__ uint64_t desc_64(uint32_t addr) { return (uint64_t)(((addr & 0x3FFFF) >> 4) | ((4096u >> 4) << 16)) | ((uint64_t)((512u >> 4) | (2u << 30)) << 32); }
__device__ __forceinline__ uint64_t desc_add(uint64_t d, uint32_t bytes) { return d + (bytes >> 4); }

__device__ __forceinline__ void wgmma_ss_n256_tb(float (&d)[128], uint64_t da, uint64_t db, int sd) {
  asm volatile("{\n.reg .pred p;\nsetp.ne.b32 p, %130, 0;\n"
    "wgmma.mma_async.sync.aligned.m64n256k16.f32.bf16.bf16 "
    "{%0, %1, %2, %3, %4, %5, %6, %7, %8, %9, %10, %11, %12, %13, %14, %15, "
    "%16, %17, %18, %19, %20, %21, %22, %23, %24, %25, %26, %27, %28, %29, %30, %31, "
    "%32, %33, %34, %35, %36, %37, %38, %39, %40, %41, %42, %43, %44, %45, %46, %47, "
    "%48, %49, %50, %51, %52, %53, %54, %55, %56, %57, %58, %59, %60, %61, %62, %63, "
    "%64, %65, %66, %67, %68, %69, %70, %71, %72, %73, %74, %75, %76, %77, %78, %79, "
    "%80, %81, %82, %83, %84, %85, %86, %87, %88, %89, %90, %91, %92, %93, %94, %95, "
    "%96, %97, %98, %99, %100, %101, %102, %103, %104, %105, %106, %107, %108, %109, %110, %111, "
    "%112, %113, %114, %115, %116, %117, %118, %119, %120, %121, %122, %123, %124, %125, %126, %127}, "
    "%128, %129, p, 1, 1, 0, 1;\n}"
    : "+f"(d[0]), "+f"(d[1]), "+f"(d[2]), "+f"(d[3]), "+f"(d[4]), "+f"(d[5]), "+f"(d[6]), "+f"(d[7]),
      "+f"(d[8]), "+f"(d[9]), "+f"(d[10]), "+f"(d[11]), "+f"(d[12]), "+f"(d[13]), "+f"(d[14]), "+f"(d[15]),
      "+f"(d[16]), "+f"(d[17]), "+f"(d[18]), "+f"(d[19]), "+f"(d[20]), "+f"(d[21]), "+f"(d[22]), "+f"(d[23]),
      "+f"(d[24]), "+f"(d[25]), "+f"(d[26]), "+f"(d[27]), "+f"(d[28]), "+f"(d[29]), "+f"(d[30]), "+f"(d[31]),
      "+f"(d[32]), "+f"(d[33]), "+f"(d[34]), "+f"(d[35]), "+f"(d[36]), "+f"(d[37]), "+f"(d[38]), "+f"(d[39]),
      "+f"(d[40]), "+f"(d[41]), "+f"(d[42]), "+f"(d[43]), "+f"(d[44]), "+f"(d[45]), "+f"(d[46]), "+f"(d[47]),
      "+f"(d[48]), "+f"(d[49]), "+f"(d[50]), "+f"(d[51]), "+f"(d[52]), "+f"(d[53]), "+f"(d[54]), "+f"(d[55]),
      "+f"(d[56]), "+f"(d[57]), "+f"(d[58]), "+f"(d[59]), "+f"(d[60]), "+f"(d[61]), "+f"(d[62]), "+f"(d[63]),
      "+f"(d[64]), "+f"(d[65]), "+f"(d[66]), "+f"(d[67]), "+f"(d[68]), "+f"(d[69]), "+f"(d[70]), "+f"(d[71]),
      "+f"(d[72]), "+f"(d[73]), "+f"(d[74]), "+f"(d[75]), "+f"(d[76]), "+f"(d[77]), "+f"(d[78]), "+f"(d[79]),
      "+f"(d[80]), "+f"(d[81]), "+f"(d[82]), "+f"(d[83]), "+f"(d[84]), "+f"(d[85]), "+f"(d[86]), "+f"(d[87]),
      "+f"(d[88]), "+f"(d[89]), "+f"(d[90]), "+f"(d[91]), "+f"(d[92]), "+f"(d[93]), "+f"(d[94]), "+f"(d[95]),
      "+f"(d[96]), "+f"(d[97]), "+f"(d[98]), "+f"(d[99]), "+f"(d[100]), "+f"(d[101]), "+f"(d[102]), "+f"(d[103]),
      "+f"(d[104]), "+f"(d[105]), "+f"(d[106]), "+f"(d[107]), "+f"(d[108]), "+f"(d[109]), "+f"(d[110]), "+f"(d[111]),
      "+f"(d[112]), "+f"(d[113]), "+f"(d[114]), "+f"(d[115]), "+f"(d[116]), "+f"(d[117]), "+f"(d[118]), "+f"(d[119]),
      "+f"(d[120]), "+f"(d[121]), "+f"(d[122]), "+f"(d[123]), "+f"(d[124]), "+f"(d[125]), "+f"(d[126]), "+f"(d[127])
    : "l"(da), "l"(db), "r"(sd));
}
__device__ __forceinline__ void wgmma_ss_n64(float (&d)[32], uint64_t da, uint64_t db, int sd) {
  asm volatile("{\n.reg .pred p;\nsetp.ne.b32 p, %34, 0;\n"
    "wgmma.mma_async.sync.aligned.m64n64k16.f32.bf16.bf16 "
    "{%0, %1, %2, %3, %4, %5, %6, %7, %8, %9, %10, %11, %12, %13, %14, %15, "
    "%16, %17, %18, %19, %20, %21, %22, %23, %24, %25, %26, %27, %28, %29, %30, %31}, "
    "%32, %33, p, 1, 1, 0, 0;\n}"
    : "+f"(d[0]), "+f"(d[1]), "+f"(d[2]), "+f"(d[3]), "+f"(d[4]), "+f"(d[5]), "+f"(d[6]), "+f"(d[7]),
      "+f"(d[8]), "+f"(d[9]), "+f"(d[10]), "+f"(d[11]), "+f"(d[12]), "+f"(d[13]), "+f"(d[14]), "+f"(d[15]),
      "+f"(d[16]), "+f"(d[17]), "+f"(d[18]), "+f"(d[19]), "+f"(d[20]), "+f"(d[21]), "+f"(d[22]), "+f"(d[23]),
      "+f"(d[24]), "+f"(d[25]), "+f"(d[26]), "+f"(d[27]), "+f"(d[28]), "+f"(d[29]), "+f"(d[30]), "+f"(d[31])
    : "l"(da), "l"(db), "r"(sd));
}
__device__ __forceinline__ void wgmma_rs_n256_tb(float (&d)[128], uint32_t a0, uint32_t a1, uint32_t a2, uint32_t a3, uint64_t db, int sd) {
  asm volatile("{\n.reg .pred p;\nsetp.ne.b32 p, %133, 0;\n"
    "wgmma.mma_async.sync.aligned.m64n256k16.f32.bf16.bf16 "
    "{%0, %1, %2, %3, %4, %5, %6, %7, %8, %9, %10, %11, %12, %13, %14, %15, "
    "%16, %17, %18, %19, %20, %21, %22, %23, %24, %25, %26, %27, %28, %29, %30, %31, "
    "%32, %33, %34, %35, %36, %37, %38, %39, %40, %41, %42, %43, %44, %45, %46, %47, "
    "%48, %49, %50, %51, %52, %53, %54, %55, %56, %57, %58, %59, %60, %61, %62, %63, "
    "%64, %65, %66, %67, %68, %69, %70, %71, %72, %73, %74, %75, %76, %77, %78, %79, "
    "%80, %81, %82, %83, %84, %85, %86, %87, %88, %89, %90, %91, %92, %93, %94, %95, "
    "%96, %97, %98, %99, %100, %101, %102, %103, %104, %105, %106, %107, %108, %109, %110, %111, "
    "%112, %113, %114, %115, %116, %117, %118, %119, %120, %121, %122, %123, %124, %125, %126, %127}, "
    "{%128, %129, %130, %131}, %132, p, 1, 1, 1;\n}"
    : "+f"(d[0]), "+f"(d[1]), "+f"(d[2]), "+f"(d[3]), "+f"(d[4]), "+f"(d[5]), "+f"(d[6]), "+f"(d[7]),
      "+f"(d[8]), "+f"(d[9]), "+f"(d[10]), "+f"(d[11]), "+f"(d[12]), "+f"(d[13]), "+f"(d[14]), "+f"(d[15]),
      "+f"(d[16]), "+f"(d[17]), "+f"(d[18]), "+f"(d[19]), "+f"(d[20]), "+f"(d[21]), "+f"(d[22]), "+f"(d[23]),
      "+f"(d[24]), "+f"(d[25]), "+f"(d[26]), "+f"(d[27]), "+f"(d[28]), "+f"(d[29]), "+f"(d[30]), "+f"(d[31]),
      "+f"(d[32]), "+f"(d[33]), "+f"(d[34]), "+f"(d[35]), "+f"(d[36]), "+f"(d[37]), "+f"(d[38]), "+f"(d[39]),
      "+f"(d[40]), "+f"(d[41]), "+f"(d[42]), "+f"(d[43]), "+f"(d[44]), "+f"(d[45]), "+f"(d[46]), "+f"(d[47]),
      "+f"(d[48]), "+f"(d[49]), "+f"(d[50]), "+f"(d[51]), "+f"(d[52]), "+f"(d[53]), "+f"(d[54]), "+f"(d[55]),
      "+f"(d[56]), "+f"(d[57]), "+f"(d[58]), "+f"(d[59]), "+f"(d[60]), "+f"(d[61]), "+f"(d[62]), "+f"(d[63]),
      "+f"(d[64]), "+f"(d[65]), "+f"(d[66]), "+f"(d[67]), "+f"(d[68]), "+f"(d[69]), "+f"(d[70]), "+f"(d[71]),
      "+f"(d[72]), "+f"(d[73]), "+f"(d[74]), "+f"(d[75]), "+f"(d[76]), "+f"(d[77]), "+f"(d[78]), "+f"(d[79]),
      "+f"(d[80]), "+f"(d[81]), "+f"(d[82]), "+f"(d[83]), "+f"(d[84]), "+f"(d[85]), "+f"(d[86]), "+f"(d[87]),
      "+f"(d[88]), "+f"(d[89]), "+f"(d[90]), "+f"(d[91]), "+f"(d[92]), "+f"(d[93]), "+f"(d[94]), "+f"(d[95]),
      "+f"(d[96]), "+f"(d[97]), "+f"(d[98]), "+f"(d[99]), "+f"(d[100]), "+f"(d[101]), "+f"(d[102]), "+f"(d[103]),
      "+f"(d[104]), "+f"(d[105]), "+f"(d[106]), "+f"(d[107]), "+f"(d[108]), "+f"(d[109]), "+f"(d[110]), "+f"(d[111]),
      "+f"(d[112]), "+f"(d[113]), "+f"(d[114]), "+f"(d[115]), "+f"(d[116]), "+f"(d[117]), "+f"(d[118]), "+f"(d[119]),
      "+f"(d[120]), "+f"(d[121]), "+f"(d[122]), "+f"(d[123]), "+f"(d[124]), "+f"(d[125]), "+f"(d[126]), "+f"(d[127])
    : "r"(a0), "r"(a1), "r"(a2), "r"(a3), "l"(db), "r"(sd));
}
__device__ __forceinline__ void wgmma_rs_n64_tb(float (&d)[32], uint32_t a0, uint32_t a1, uint32_t a2, uint32_t a3, uint64_t db, int sd) {
  asm volatile("{\n.reg .pred p;\nsetp.ne.b32 p, %37, 0;\n"
    "wgmma.mma_async.sync.aligned.m64n64k16.f32.bf16.bf16 "
    "{%0, %1, %2, %3, %4, %5, %6, %7, %8, %9, %10, %11, %12, %13, %14, %15, "
    "%16, %17, %18, %19, %20, %21, %22, %23, %24, %25, %26, %27, %28, %29, %30, %31}, "
    "{%32, %33, %34, %35}, %36, p, 1, 1, 1;\n}"
    : "+f"(d[0]), "+f"(d[1]), "+f"(d[2]), "+f"(d[3]), "+f"(d[4]), "+f"(d[5]), "+f"(d[6]), "+f"(d[7]),
      "+f"(d[8]), "+f"(d[9]), "+f"(d[10]), "+f"(d[11]), "+f"(d[12]), "+f"(d[13]), "+f"(d[14]), "+f"(d[15]),
      "+f"(d[16]), "+f"(d[17]), "+f"(d[18]), "+f"(d[19]), "+f"(d[20]), "+f"(d[21]), "+f"(d[22]), "+f"(d[23]),
      "+f"(d[24]), "+f"(d[25]), "+f"(d[26]), "+f"(d[27]), "+f"(d[28]), "+f"(d[29]), "+f"(d[30]), "+f"(d[31])
    : "r"(a0), "r"(a1), "r"(a2), "r"(a3), "l"(db), "r"(sd));
}
__device__ __forceinline__ void wgmma_rs_n32(float (&d)[16], uint32_t a0, uint32_t a1, uint32_t a2, uint32_t a3, uint64_t db, int sd) {
  asm volatile("{\n.reg .pred p;\nsetp.ne.b32 p, %21, 0;\n"
    "wgmma.mma_async.sync.aligned.m64n32k16.f32.bf16.bf16 "
    "{%0, %1, %2, %3, %4, %5, %6, %7, %8, %9, %10, %11, %12, %13, %14, %15}, "
    "{%16, %17, %18, %19}, %20, p, 1, 1, 0;\n}"
    : "+f"(d[0]), "+f"(d[1]), "+f"(d[2]), "+f"(d[3]), "+f"(d[4]), "+f"(d[5]), "+f"(d[6]), "+f"(d[7]),
      "+f"(d[8]), "+f"(d[9]), "+f"(d[10]), "+f"(d[11]), "+f"(d[12]), "+f"(d[13]), "+f"(d[14]), "+f"(d[15])
    : "r"(a0), "r"(a1), "r"(a2), "r"(a3), "l"(db), "r"(sd));
}

__device__ __forceinline__ void sts16(uint32_t a, uint32_t x, uint32_t y, uint32_t z, uint32_t w) {
  asm volatile("st.shared.v4.u32 [%0], {%1, %2, %3, %4};" :: "r"(a), "r"(x), "r"(y), "r"(z), "r"(w) : "memory");
}
__device__ __forceinline__ uint32_t lds4(uint32_t a) { uint32_t v; asm volatile("ld.shared.u32 %0, [%1];" : "=r"(v) : "r"(a) : "memory"); return v; }
__device__ __forceinline__ uint32_t bmul(uint32_t a, uint32_t b) { uint32_t r; asm("mul.rn.bf16x2 %0, %1, %2;" : "=r"(r) : "r"(a), "r"(b)); return r; }
__device__ __forceinline__ uint32_t badd(uint32_t a, uint32_t b) { uint32_t r; asm("add.rn.bf16x2 %0, %1, %2;" : "=r"(r) : "r"(a), "r"(b)); return r; }

#define WANT_AT 4
#define POLL_NS 500
#define START_NS 0
#define NB 8
constexpr int EARLY_LD = 4;
constexpr int PP_BAR = 3;
template <int V> struct Int { static constexpr int value = V; };
struct Ring {
  uint32_t slot, phase;
  __device__ __forceinline__ void next() { if (++slot == NSLOT) { slot = 0; phase ^= 1; } }
};
__device__ __forceinline__ uint32_t bar_addr(uint32_t sb, uint32_t i) { return sb + BARS + 8 * i; }

__device__ __forceinline__ int kv_group(int g, int t) { return (g & 6) | (t & 1); }
__device__ __forceinline__ int kv_rows(int g, int t) { return (t & 14) | (g & 1); }
__device__ __forceinline__ void load_w(const Params& p, int g, int t, int it, uint32_t dst, uint32_t full) {
  if (it < 64) tma_ld3(dst, (it & 16) ? &p.wuv : &p.wuk, full, 0, (it & 15) * 64, (kv_group(g, t) + (it < 32 ? 8 : 0)) * 4);
  else tma_ld3(dst, &p.wq, full, 0, (it < 71 ? it - 64 : it - 71) * 64, (it < 71 ? g + 8 : g) * 4);
}
__device__ __forceinline__ void load_a(const Params& p, int g, int t, int it, uint32_t dst, uint32_t full) {
  if (it < 64) tma_ld2(dst, &p.ckv, full, (it & 15) * 64, kv_rows(g, t) * 128);
  else tma_ld2(dst, &p.x, full, (it < 71 ? it - 64 : it - 71) * 64, (it < 71 ? 15 - t : t) * 128);
}

__device__ __forceinline__ void producer_main(const Params& p, uint32_t sb, int g, int t) {
  const int rank = t & 1;
  Ring r{EARLY_LD, 0};
  auto wait_slot = [&]() { mbar_wait(bar_addr(sb, B_EMPTY + r.slot), r.phase ^ 1); };
  uint32_t prev = 0;
#pragma unroll 1
  for (int it = EARLY_LD; it < P1_STEPS; it++) {
    wait_slot();
    if (it > EARLY_LD && it <= P1_XS) load_a(p, g, t, it - 1, sb + QREG + ((it - 1) & 3) * 16384, prev);
    const uint32_t full = bar_addr(sb, B_FULL + r.slot);
    mbar_expect_tx(full, it < P1_XS ? 49152 : 32768);
    load_w(p, g, t, it, sb + r.slot * SLOT, full);
    prev = full;
    r.next();
    if (it == 50) mbar_arrive(bar_addr(sb, B_PF));
    if (it == P1_XS) {
      wait_slot();
      const uint32_t f2 = bar_addr(sb, B_FULL + r.slot);
      mbar_expect_tx(f2, 32768);
      load_a(p, g, t, P1_XS, sb + r.slot * SLOT, f2);
      load_a(p, g, t, P1_XS + 1, sb + r.slot * SLOT + 16384, f2);
      r.next();
    }
  }
  uint64_t once;
  asm volatile("createpolicy.fractional.L2::evict_first.b64 %0, 1.0;" : "=l"(once));
  const int na = 2 * t + 2, own = 2 * (t & ~1) + 2;
  mbar_wait(bar_addr(sb, B_KVOK), 0);
#pragma unroll 1
  for (int f = 0; f < 68; f++) {
    const bool isK = (f == 0) || ((f & 1) && f < 67);
    const int i = isK ? (f + 1) >> 1 : (f - 1) >> 1;
    wait_slot();
    const uint32_t full = bar_addr(sb, B_FULL + r.slot);
    mbar_expect_tx(full, 32768);
    const uint32_t src = (uint32_t)(((isK ? 0 : NH) + g) * 32 + (i >= na ? 8 * 32 + 33 - i : i)) * 32768;
    if ((i & ~1) != own) bulk_ld_mc(sb + r.slot * SLOT + rank * 16384, at<uint8_t>(g_kv, src + rank * 16384), 16384, full, once);
    else bulk_ld_p(sb + r.slot * SLOT, at<uint8_t>(g_kv, src), 32768, full, once);
    r.next();
  }
#pragma unroll 1
  for (int f = 0; f < 14; f++) {
    const int ch = f < 4 ? f & 1 : f >> 1, par = f < 4 ? f >> 1 : f & 1;
    wait_slot();
    const uint32_t full = bar_addr(sb, B_FULL + r.slot);
    mbar_expect_tx(full, 32768);
    tma_ld5_mc(sb + r.slot * SLOT + rank * 16384, &p.wo, full, ch * 64, (par ? g : g + 8) * 8 + rank * 4);
    r.next();
  }
}

__device__ __forceinline__ void helper_main(const Params& p, uint32_t sb, int g, int t, int w) {
  const unsigned epoch = load_epoch();
  const uint32_t qreg = sb + QREG + w * 32768, qfull = bar_addr(sb, B_QFULL + w);
  mbar_wait(bar_addr(sb, B_ST_KV + w), 0);
  flag_signal(flag_at(g_flags.kv_ready, kv_group(g, t)));
  if (w == 0) {
    flag_wait<20>(flag_at(g_flags.kv_ready, g), 32, epoch);
    fence_async_global();
    mbar_arrive(bar_addr(sb, B_KVOK));
  }
  mbar_wait(bar_addr(sb, B_ST_Q + w), 0);
  asm volatile("fence.release.gpu;" ::: "memory");
  fence_async_global();
  mbar_wait(bar_addr(sb, B_QFREE + w), 0);
  mbar_expect_tx(qfull, 32768);
  bulk_ld(qreg, at<uint8_t>(g_qc, ((g * 16 + t) * 2 + w) * 32768), 32768, qfull);
  auto publish = [&]() { mbar_wait(bar_addr(sb, B_ST_CTX + w), 0); flag_signal(flag_at(g_flags.ctx_ready, (g * 16 + t) * 2 + w)); };
  if (t < 8) publish();
  flag_wait<20>(flag_at(g_flags.ctx_ready, (g * 16 + 15 - t) * 2 + (w ^ 1)), 1, epoch);
  mbar_arrive(bar_addr(sb, B_CTXOK + w));
  mbar_arrive(bar_addr(sb, B_DONE));
  if (t >= 8) publish();
  flag_wait<20>(flag_at(g_flags.zero_ready, 15 - t), 8, epoch);
  fence_async_global();
#pragma unroll 1
  for (int ch = 0; ch < 6; ch++) {
    mbar_wait(bar_addr(sb, B_S2_FULL + w * 4 + (ch & 3)), ch >> 2);
    tma_red2(&p.o, qreg + (ch & 3) * 8192, DA + ch * 64, (15 - t) * 128 + (w ^ 1) * 64);
    bulk_commit();
    if (ch < 3) { bulk_wait_read(); mbar_arrive(bar_addr(sb, B_S2_EMPTY + w * 4 + ch)); }
  }
  bulk_wait_read();
  GT(48 + w);
}

__device__ __forceinline__ void store_block(uint32_t base, uint32_t lanebase, const uint32_t (&pk)[16]) {
#pragma unroll
  for (int J = 0; J < 8; J += 2) stsm4(base + (lanebase ^ (J << 4)), pk[2 * J], pk[2 * J + 1], pk[2 * J + 2], pk[2 * J + 3]);
}
__device__ __forceinline__ void pack_chunks(uint32_t (&pk)[64], const float (&acc)[128]) {
#pragma unroll
  for (int i = 0; i < 64; i++) { const int e = 16 * (i >> 3) + 4 * (i & 3) + 2 * ((i >> 2) & 1); pk[i] = pack_bf16(acc[e], acc[e + 1]); }
}
__device__ __forceinline__ uint32_t chunk_off() { const uint32_t t = fresh_tid(); return (t & 96) * 32 + (t & 28) * 16 + (((t ^ (t >> 3)) & 3) << 4); }
__device__ __forceinline__ void warp_arrive(uint32_t bar, int lane) { __syncwarp(); if (lane == 0) mbar_arrive(bar); }

__device__ __forceinline__ void consumer_main(const Params& p, uint32_t sb, int g, int t, int w, int wq) {
  const int lane = threadIdx.x & 31;
  const int rank = t & 1;

  auto turn_begin = [&]() { named_sync(PP_BAR + w, 256); };
  auto turn_end = [&]() { named_arrive(PP_BAR + (w ^ 1), 256); };
  Ring r{0, 0};
  auto take = [&](uint32_t ready = 0) { const uint32_t sl = r.slot; mbar_wait_unless(ready, bar_addr(sb, B_FULL + sl), r.phase); r.next(); return sl; };
  uint32_t rdy0 = 0, rdy1 = 0;
  auto peek2 = [&]() { Ring q = r; rdy0 = mbar_test(bar_addr(sb, B_FULL + q.slot), q.phase); q.next(); rdy1 = mbar_test(bar_addr(sb, B_FULL + q.slot), q.phase); };
  auto give = [&](uint32_t sl) { if (lane < 2) mbar_arrive_remote(bar_addr(sb, B_EMPTY + sl), rank ^ lane); };
  float acc[128];
#pragma unroll
  for (int i = 0; i < 128; i++) acc[i] = 0.f;
  uint32_t pk[64];
#pragma unroll
  for (int i = 0; i < 64; i++) pk[i] = 0;
  reg_fence(acc);
  reg_fence(pk);
  cluster_wait();
  TS(0);
  const uint32_t qreg = sb + QREG + w * 32768;
  {
    uint32_t xs = 0;
    uint4* row = nullptr;
    int it = 0;
#pragma unroll 1
    for (int tile = 0; tile < 6; tile++) {
      const bool isq = tile >= 4;
      const uint32_t abase = sb + QREG + (w ^ (tile == 4)) * 8192;
#pragma unroll 1
      for (int u = 0; u < (isq ? 4 : 8); u++) {
        const bool two = !(isq && u == 1), last = it == P1_XS;
        const uint32_t w0 = take(rdy0);
        TSC(1, it == 0);
        if (last) { xs = take(rdy1); rdy1 = 0; }
        const uint32_t xb = sb + xs * SLOT + w * 8192;
        const uint64_t da = desc_k(last ? xb : abase + (it & 3) * 16384), db = desc_mn(sb + w0 * SLOT);
        turn_begin();
        wg_fence();
#pragma unroll
        for (int kk = 0; kk < 4; kk++) wgmma_ss_n256_tb(acc, desc_add(da, kk * 32), desc_add(db, kk * 2048), (u | kk) != 0);
        wg_commit();
        uint32_t w1 = w0;
        if (two) {
          w1 = take(rdy1);
          const uint64_t da1 = desc_k(last ? xb + 16384 : abase + ((it + 1) & 3) * 16384), db1 = desc_mn(sb + w1 * SLOT);
          wg_fence();
#pragma unroll
          for (int kk = 0; kk < 4; kk++) wgmma_ss_n256_tb(acc, desc_add(da1, kk * 32), desc_add(db1, kk * 2048), 1);
          wg_commit();
          turn_end();
          wg_wait<1>();
          give(w0);
        } else {
          turn_end();
        }
        if (tile > 0) {
          uint32_t m = isq ? 0xC0380403u >> (8 * u) : 1u << u;
          asm volatile("" : "+r"(m));
#pragma unroll
          for (int i = 0; i < 16; i++)
            if (m & (1u << (i >> 1))) row[(i >> 1) * 256 + (i & 1) * 32] = make_uint4(pk[4 * i], pk[4 * i + 1], pk[4 * i + 2], pk[4 * i + 3]);
        }
        peek2();
        wg_wait<0>();
        give(w1);
        it += 1 + two;
      }
      reg_fence(acc);
      if (isq) warp_arrive(bar_addr(sb, (tile == 4 ? B_ST_KV : B_ST_Q) + w), lane);
      if (tile == 5) break;
      pack_chunks(pk, acc);
      row = at<uint4>(isq ? (const void*)g_qc : (const void*)g_kv, chunk_off() +
                      (uint32_t)(isq ? (g * 16 + t) * 2 + w : ((tile & 1) * NH + kv_group(g, t) + (tile < 2 ? 8 : 0)) * 32 + kv_rows(g, t) * 2 + w) * 32768);
      TS(2 + tile);
    }
    give(xs);
    const uint32_t qa = qreg + chunk_off();
    TS(7);
    pack_chunks(pk, acc);
#pragma unroll
    for (int i = 0; i < 16; i++) sts16(qa + (i >> 1) * 4096 + (i & 1) * 512, pk[4 * i], pk[4 * i + 1], pk[4 * i + 2], pk[4 * i + 3]);
    rdy0 = mbar_test(bar_addr(sb, B_FULL + r.slot), r.phase);
    fence_async_smem();
  }
  TS(8);

  auto normalise = [&](int c, float i0, float i1) {
    pk[4 * c]     = pack_bf16(acc[8 * c] * i0, acc[8 * c + 1] * i0);
    pk[4 * c + 1] = pack_bf16(acc[8 * c + 2] * i1, acc[8 * c + 3] * i1);
    pk[4 * c + 2] = pack_bf16(acc[8 * c + 4] * i0, acc[8 * c + 5] * i0);
    pk[4 * c + 3] = pack_bf16(acc[8 * c + 6] * i1, acc[8 * c + 7] * i1);
  };
  float il0 = 0.f, il1 = 0.f;
  constexpr float SC = 0.0625f * 1.4426950408889634f;
#pragma unroll 1
  for (int which = 0; which < 2; which++) {
    float s[32];
#pragma unroll
    for (int i = 0; i < 32; i++) s[i] = 0.f;
    uint32_t pa[16], pb[16];
    float m0 = 0.f, m1 = 0.f, l0 = 0.f, l1 = 0.f;
    const uint64_t dq = desc_64(qreg);
    uint64_t dk = 0, dqq = 0, dv = 0;
    auto prep_qk = [&](uint32_t kaddr) { dk = desc_64(kaddr); dqq = dq + (kaddr >> 31); asm volatile("" : "+l"(dk), "+l"(dqq)); };
    auto prep_pv = [&](uint32_t vaddr) { dv = desc_64(vaddr); asm volatile("" : "+l"(dv)); };
    auto issue_qk = [&]() {
#pragma unroll
      for (int kk = 0; kk < 16; kk++)
        wgmma_ss_n64(s, desc_add(dqq, (kk >> 1) * 4096 + (kk & 1) * 32), desc_add(dk, (kk >> 1) * 4096 + (kk & 1) * 32), kk != 0);
    };
    auto issue_pv = [&](int accumulate) {
#pragma unroll
      for (int kk = 0; kk < 4; kk++)
        wgmma_rs_n256_tb(acc, pa[4 * kk], pa[4 * kk + 1], pa[4 * kk + 2], pa[4 * kk + 3], desc_add(dv, kk * 1024), accumulate | kk);
    };
    auto mask_diag = [&]() {
      const int d = 16 * wq + (lane >> 2) - 2 * (lane & 3);
#pragma unroll
      for (int jj = 0; jj < 8; jj++) {
        if (8 * jj > d)     { s[4 * jj] = -INFINITY;     if (jj < 7) s[4 * jj + 6] = -INFINITY; }
        if (8 * jj + 1 > d) { s[4 * jj + 1] = -INFINITY; if (jj < 7) s[4 * jj + 7] = -INFINITY; }
      }
    };
    float a0, a1;
    auto softmax = [&]() -> bool {
      float x0 = fmaxf(s[0], s[1]), x1 = fmaxf(s[2], s[3]);
#pragma unroll
      for (int jj = 1; jj < 8; jj++) {
        x0 = fmaxf(x0, fmaxf(s[4 * jj], s[4 * jj + 1]));
        x1 = fmaxf(x1, fmaxf(s[4 * jj + 2], s[4 * jj + 3]));
      }
      x0 = fmaxf(x0, __shfl_xor_sync(0xffffffffu, x0, 1));
      x1 = fmaxf(x1, __shfl_xor_sync(0xffffffffu, x1, 1));
      x0 = fmaxf(x0, __shfl_xor_sync(0xffffffffu, x0, 2));
      x1 = fmaxf(x1, __shfl_xor_sync(0xffffffffu, x1, 2));
      const bool grow = __any_sync(0xffffffffu, fmaxf(x0 - m0, x1 - m1) * SC > 8.f);
      if (grow) {
        x0 = fmaxf(x0, m0); x1 = fmaxf(x1, m1);
        a0 = ex2((m0 - x0) * SC); a1 = ex2((m1 - x1) * SC);
        m0 = x0; m1 = x1;
        l0 *= a0; l1 *= a1;
      }
      const float b0 = -m0 * SC, b1 = -m1 * SC;
      float t0 = 0.f, t1 = 0.f, t2 = 0.f, t3 = 0.f;
#pragma unroll
      for (int jj = 0; jj < 8; jj++) {
        s[4 * jj]     = ex2(fmaf(s[4 * jj], SC, b0));
        s[4 * jj + 1] = ex2(fmaf(s[4 * jj + 1], SC, b0));
        s[4 * jj + 2] = ex2(fmaf(s[4 * jj + 2], SC, b1));
        s[4 * jj + 3] = ex2(fmaf(s[4 * jj + 3], SC, b1));
        t0 += s[4 * jj]; t1 += s[4 * jj + 1]; t2 += s[4 * jj + 2]; t3 += s[4 * jj + 3];
      }
      l0 += t0 + t1; l1 += t2 + t3;
      return grow;
    };
    auto softmax_fast = [&](uint32_t (&pp)[16], auto first, auto hook) -> bool {
      const float b0 = -m0 * SC, b1 = -m1 * SC;
      float t0 = 0.f, t1 = 0.f, t2 = 0.f, t3 = 0.f;
#pragma unroll
      for (int jj = 0; jj < 8; jj++) {
        const float e0 = ex2(fmaf(s[4 * jj], SC, b0)), e1 = ex2(fmaf(s[4 * jj + 1], SC, b0));
        const float e2 = ex2(fmaf(s[4 * jj + 2], SC, b1)), e3 = ex2(fmaf(s[4 * jj + 3], SC, b1));
        hook(jj, e0);
        pp[2 * jj] = pack_bf16(e0, e1); pp[2 * jj + 1] = pack_bf16(e2, e3);
        if (jj == 0) { t0 = e0; t1 = e1; t2 = e2; t3 = e3; } else { t0 += e0; t1 += e1; t2 += e2; t3 += e3; }
      }
      t0 += t1; t2 += t3;
      bool redo = __any_sync(0xffffffffu, !(t0 + t2 <= 16777216.f));
      if (decltype(first)::value) {
        uint32_t u0 = __ballot_sync(0xffffffffu, t0 >= 1.52587890625e-05f), u1 = __ballot_sync(0xffffffffu, t2 >= 1.52587890625e-05f);
        u0 |= u0 >> 1; u1 |= u1 >> 1;
        redo |= (((u0 | (u0 >> 2)) & (u1 | (u1 >> 2))) & 0x11111111u) != 0x11111111u;
      }
      if (!redo) { l0 += t0; l1 += t2; }
      return redo;
    };
    auto rescale = [&]() {
#pragma unroll
      for (int i = 0; i < 32; i++) { acc[4 * i] *= a0; acc[4 * i + 1] *= a0; acc[4 * i + 2] *= a1; acc[4 * i + 3] *= a1; }
    };
    auto to_p = [&](uint32_t (&pp)[16]) {
#pragma unroll
      for (int i = 0; i < 16; i++) pp[i] = pack_bf16(s[2 * i], s[2 * i + 1]);
    };
    auto q_free = [&]() { if (lane == 0) mbar_arrive(bar_addr(sb, B_QFREE + w)); };

    const int n = 2 * (which ? 15 - t : t) + 1 + (w ^ which);
    uint32_t ks = take(rdy0);
    TS(9 + 5 * which);
    prep_qk(sb + ks * SLOT);
    turn_begin();
    TS(20 + 10 * which);
    wg_fence();
    issue_qk();
    wg_commit();
    turn_end();
    if (which == 1) give(take(rdy1));
    TS(22 + 10 * which);
    wg_wait<0>();
    TS(21 + 10 * which);
    reg_fence(s);
    give(ks);
    if (which == 0 && n == 1) q_free();
    if (which == 1 || n == 1) mask_diag();
    {
      const uint4* dst = at<uint4>(g_qc, (uint32_t)((g * 16 + t) * 2 + w) * 32768 + (fresh_tid() & 127) * 16);
      const bool redo = softmax_fast(pa, Int<1>(), [&](int jj, float e) {
        if (jj == 7) peek2();
        const int i = 8 + jj;
        asm volatile("{\n.reg .pred p, q;\nsetp.ne.b32 q, %6, 0;\nsetp.geu.and.f32 p, %5, 0fBF800000, q;\n@p st.global.v4.u32 [%0], {%1, %2, %3, %4};\n}"
                       :: "l"(dst + i * 128), "r"(pk[4 * i]), "r"(pk[4 * i + 1]), "r"(pk[4 * i + 2]), "r"(pk[4 * i + 3]), "f"(e), "r"(which) : "memory");
      });
      if (redo) {
        m0 = -INFINITY; m1 = -INFINITY;
        softmax();
        to_p(pa);
      }
    }
    if (which == 1) warp_arrive(bar_addr(sb, B_ST_CTX + w), lane);
    TS(10 + 5 * which);
#pragma unroll 1
    for (int jj = 1; jj < n; jj++) {
      ks = take(rdy0);
      const uint32_t vs = take(rdy1);
      prep_qk(sb + ks * SLOT);
      prep_pv(sb + vs * SLOT);
      TSC(23 + 10 * which, jj == 1);
      turn_begin();
      TSC(24 + 10 * which, jj == 1);
      TSC(26 + 10 * which, jj == n - 1);
      wg_fence();
      issue_qk();
      wg_commit();
      issue_pv(jj > 1);
      wg_commit();
      turn_end();
      wg_wait<1>();
      TSC(25 + 10 * which, jj == 1);
      reg_fence(s);
      give(ks);
      if (jj == n - 1 && which == 0) { q_free(); mask_diag(); }
      if (softmax_fast(pb, Int<0>(), [](int, float) {})) {
        wg_wait<0>();
        reg_fence(acc);
        if (softmax()) rescale();
        to_p(pb);
      }
      peek2();
      wg_wait<0>();
      reg_fence(acc);
      reg_fence(pa);
      give(vs);
#pragma unroll
      for (int i = 0; i < 16; i++) pa[i] = pb[i] | (vs >> 8);
    }
    TS(11 + 5 * which);
    if (which == 0) { give(take(rdy0)); rdy0 = rdy1; }
    {
      const uint32_t vs = take(rdy0);
      prep_pv(sb + vs * SLOT);
      TS(27 + 10 * which);
      turn_begin();
      TS(28 + 10 * which);
      wg_fence();
      issue_pv(n > 1);
      wg_commit();
      turn_end();
      l0 += __shfl_xor_sync(0xffffffffu, l0, 1); l1 += __shfl_xor_sync(0xffffffffu, l1, 1);
      l0 += __shfl_xor_sync(0xffffffffu, l0, 2); l1 += __shfl_xor_sync(0xffffffffu, l1, 2);
      asm("rcp.approx.ftz.f32 %0, %0;" : "+f"(l0));
      asm("rcp.approx.ftz.f32 %0, %0;" : "+f"(l1));
      peek2();
      if (which == 0) mbar_wait(bar_addr(sb, B_QFULL + w), 0);
      wg_wait<0>();
      reg_fence(acc);
      reg_fence(pa);
      give(vs);
    }
    TS(12 + 5 * which);
    if (which == 1) { il0 = l0; il1 = l1; break; }
    {
      const uint4* dst = at<uint4>(g_qc, (uint32_t)((g * 16 + t) * 2 + w) * 32768 + (fresh_tid() & 127) * 16);
#pragma unroll
      for (int i = 0; i < 16; i++) {
        const int c = (i & 1) ? (i >> 1) + 8 : i >> 1;
        normalise(c, l0, l1);
        if (c < 8)
          asm volatile("st.global.v4.u32 [%0], {%1, %2, %3, %4};"
                       :: "l"(dst + c * 128), "r"(pk[4 * c]), "r"(pk[4 * c + 1]), "r"(pk[4 * c + 2]), "r"(pk[4 * c + 3]) : "memory");
      }
    }
    TS(13 + 5 * which);
  }

  {
    float oa[32], ob[32];
#pragma unroll
    for (int i = 0; i < 32; i++) { oa[i] = 0.f; ob[i] = 0.f; }
    uint32_t pk2[64];
    auto stage = [&](float (&o)[32], int ch) {
      reg_fence(o);
      uint32_t q[16];
#pragma unroll
      for (int i = 0; i < 16; i++) q[i] = pack_bf16(o[2 * i], o[2 * i + 1]);
      if (ch >= 4) mbar_wait(bar_addr(sb, B_S2_EMPTY + w * 4 + (ch & 3)), 0);
      store_block(qreg + (ch & 3) * 8192, lane_base16(), q);
    };
    auto hand_over = [&](int ch) {
      fence_async_smem();
      warp_arrive(bar_addr(sb, B_S2_FULL + w * 4 + (ch & 3)), lane);
    };
    uint32_t prev = 0;
    auto half = [&](int f, float (&o)[32], uint32_t (&a)[64], int accumulate) {
      if (f == 0) {
#pragma unroll
        for (int c = 0; c < NB; c++) normalise(c, il0, il1);
        TS(18);
      }
      const uint32_t sl = take(rdy0);
      const uint64_t d = desc_mn(sb + sl * SLOT);
      turn_begin();
      TS(40 + f);
      if (f == 0) {
#pragma unroll
        for (int c = NB; c < 16; c++) normalise(c, il0, il1);
      }
      wg_fence();
#pragma unroll
      for (int kk = 0; kk < 16; kk++) {
        wgmma_rs_n64_tb(o, a[4 * kk], a[4 * kk + 1], a[4 * kk + 2], a[4 * kk + 3], desc_add(d, kk * 2048), accumulate | kk);
        if (kk == 12 && (f < 13 || w == 0)) turn_end();
      }
      wg_commit();
      if (f < 13) rdy0 = mbar_test(bar_addr(sb, B_FULL + r.slot), r.phase);
      wg_wait<1>();
      if (f >= 1 && f <= 9) give(prev);
      prev = sl;
    };
    auto load_ctx = [&](auto h0) {
      constexpr int I0 = decltype(h0)::value * 8, NL = 8;
      const uint4* src = at<const uint4>(g_qc, (uint32_t)((g * 16 + 15 - t) * 2 + (w ^ 1)) * 32768 + (fresh_tid() & 127) * 16);
#pragma unroll
      for (int i = I0; i < I0 + NL; i++) { const uint4 v = __ldcg(src + i * 128); pk2[4 * i] = v.x; pk2[4 * i + 1] = v.y; pk2[4 * i + 2] = v.z; pk2[4 * i + 3] = v.w; }
    };
    half(0, oa, pk, 0);
    mbar_wait(bar_addr(sb, B_CTXOK + w), 0);
    load_ctx(Int<0>());
    half(1, ob, pk, 0);
    load_ctx(Int<1>());
    half(2, oa, pk2, 1);
#pragma unroll 1
    for (int i = 0; i < 3; i++) {
      half(4 * i + 3, ob, pk2, 1);
      if (i == 0) stage(oa, 0);
      half(4 * i + 4, oa, pk, 0);
      if (i == 0) hand_over(0);
      stage(ob, 2 * i + 1);
      hand_over(2 * i + 1);
      half(4 * i + 5, oa, pk2, 1);
      if (i == 2) break;
      half(4 * i + 6, ob, pk, 0);
      stage(oa, 2 * i + 2);
      hand_over(2 * i + 2);
    }
    mbar_wait(bar_addr(sb, B_S2_EMPTY + w * 4 + 2), 0);
    const uint32_t lb = lane_base16();
    wg_wait<0>();
    reg_fence(pk);
    reg_fence(pk2);
    reg_fence(oa);
    uint32_t q[16];
#pragma unroll
    for (int i = 0; i < 16; i++) q[i] = pack_bf16(oa[2 * i], oa[2 * i + 1]);
    store_block(qreg + 2 * 8192, lb, q);
    fence_async_smem();
    named_sync(1 + w, 128);
    if (wq == 0 && lane == 0) {
      tma_red2(&p.o, qreg + 2 * 8192, DA + 6 * 64, (15 - t) * 128 + (w ^ 1) * 64);
      bulk_commit();
      bulk_wait_read();
    }
  }
  TS(19);
  TDUMP();
}

namespace ssm {
constexpr int NCH = DA / NCONV;
constexpr int NS = 8, NP = 6;
constexpr uint32_t X0 = 384;
constexpr uint32_t HO = X0 + 4096;
constexpr uint32_t HE = HO + HO_STRIDE + 64;
constexpr uint32_t SSLOT = HE + 4096 + 64;
constexpr uint32_t PART = 264 * 16;
constexpr uint32_t OFF_P = NS * SSLOT, OFF_D = OFF_P + NP * 4 * PART, END = OFF_D + NCH * 4;
static_assert(SSLOT % 128 == 0 && HO % 128 == 0 && END <= BARS, "smem");
enum : uint32_t { B_FULL = 0, B_EMPTY = NS, B_PFULL = 2 * NS, B_PEMPTY = 2 * NS + NP };
__device__ __forceinline__ int channel(int cidx, int i) { return (i >> 4) * 64 + cidx * 16 + (i & 15); }

__device__ __forceinline__ void producer(const Params& p, uint32_t sb, int cidx, unsigned epoch) {
#pragma unroll 1
  for (int i = 0; i < NCH; i++) {
    const int s = i % NS, ch = channel(cidx, i);
    const uint32_t full = bar_addr(sb, B_FULL + s), dst = sb + s * SSLOT;
    mbar_wait(bar_addr(sb, B_EMPTY + s), ((i / NS) & 1) ^ 1);
    if (cidx == 0 && (i & 15) == WANT_AT && i < NCH - 16)
      asm volatile("red.relaxed.gpu.global.add.u32 [%0], 1;" :: "l"(flag_at(g_flags.x_wanted, (i >> 4) + 1)) : "memory");
    mbar_expect_tx(full, 4096 + 4128 + 4096);
    bulk_ld(dst + HE, at<uint8_t>(p.a_ssmk, ch * 4096), 4096, full);
    if ((i & 15) == 0) { flag_wait<20>(flag_at(g_flags.x_ready, i >> 4), NMAIN, epoch); fence_async_global(); }
    bulk_ld(dst + HO, at<uint8_t>(g_ho, ch * HO_STRIDE), 4128, full);
    bulk_ld(dst + X0, at<uint8_t>(g_xs, ch * 4096), 4096, full);
  }
}

__device__ __forceinline__ void reducer(uint32_t sb, int cidx, int rw) {
  uint32_t n = 0;
#pragma unroll 1
  for (int i = rw; i < NCH; i += 3, n++) {
    const uint32_t b = rw + 3 * (n & 1), pb = sb + OFF_P + b * 4 * PART;
    uint8_t* dst = at<uint8_t>(g_xs, channel(cidx, i) * 4096);
    mbar_wait(bar_addr(sb, B_PFULL + b), (n >> 1) & 1);
    asm volatile("cp.async.bulk.global.shared::cta.bulk_group [%0], [%1], 4096;" :: "l"(dst), "r"(pb + 3 * PART) : "memory");
    bulk_commit();
    bulk_wait_all();
#pragma unroll
    for (int k = 2; k >= 0; k--)
      asm volatile("cp.reduce.async.bulk.global.shared::cta.bulk_group.add.noftz.bf16 [%0], [%1], 4096;" :: "l"(dst), "r"(pb + k * PART) : "memory");
    bulk_commit();
    bulk_wait_read();
    mbar_arrive(bar_addr(sb, B_PEMPTY + b));
    if (((i + 3) >> 4) != (i >> 4)) {
      bulk_wait_all();
      fence_async_global();
      flag_signal(flag_at(g_flags.z_ready, i >> 4));
    }
  }
}

__device__ __forceinline__ void mma_warpgroup(uint32_t sb, int w) {
  const int lane = threadIdx.x & 31, g = lane >> 2, c = lane & 3, wq = (threadIdx.x >> 5) & 3;
  const uint32_t aoff = ((g & 1) ? HO + 30 : HE) + (16 * wq - g + 2 * c) * 2;
  const uint32_t poff = OFF_P + wq * PART + (2 * wq + lane) * 16;
  const uint32_t dmask = (wq == 0 && c == (g >> 1)) ? ((g & 1) ? 0xffff0000u : 0xffffu) : 0u;
  float acc[8][16];
  uint32_t fa[16][4];
#pragma unroll
  for (int e = 0; e < 8; e++)
#pragma unroll
    for (int i = 0; i < 16; i++) acc[e][i] = 0.f;
  auto load_a = [&](int m, uint32_t ad) {
    fa[m][0] = lds4(ad + m * 256 + 16); fa[m][1] = lds4(ad + m * 256 + 144); fa[m][2] = lds4(ad + m * 256); fa[m][3] = lds4(ad + m * 256 + 128);
  };
  if (w == 1) named_arrive(PP_BAR, 256);
  mbar_wait(bar_addr(sb, B_FULL + w), 0);
#pragma unroll
  for (int m = 0; m < 16; m++) load_a(m, sb + w * SSLOT + aoff);
  uint32_t dd = lds4(sb + OFF_D + w * 4);
  if (threadIdx.x == 128) { GT(12); PT(10); }
  uint32_t pb = w, pphase = 1;
#pragma unroll 1
  for (int i = w; i < NCH; i += 2) {
    fa[0][2] = badd(fa[0][2], dd & dmask);
    const uint64_t db = (uint64_t)((((sb + (i % NS) * SSLOT + X0 - 16) & 0x3FFFF) >> 4) | (1u << 16)) | ((uint64_t)8 << 32);
    named_sync(PP_BAR + w, 256);
    wg_fence();
#pragma unroll
    for (int r = 0; r < 16; r++) {
      auto mm = [&](int e, int m) { wgmma_rs_n32(acc[e], fa[m][0], fa[m][1], fa[m][2], fa[m][3], db + (int64_t)(32 * e - 16 * m), m != 0); };
      mm(7, r);
      if (r < 14) mm(6, r); else mm(0, r - 14);
      if (r < 12) mm(5, r); else mm(1, r - 12);
      if (r < 10) mm(4, r); else mm(2, r - 10);
      if ((r & 1) == 0) mm(3, r >> 1);
      if (r == 13 && (i + 1 < NCH)) named_arrive(PP_BAR + (w ^ 1), 256);
    }
    wg_commit();
    const int nx = i + 2 < NCH ? i + 2 : i;
    mbar_wait(bar_addr(sb, B_FULL + nx % NS), (nx / NS) & 1);
    mbar_wait(bar_addr(sb, B_PEMPTY + pb), pphase);
    const uint32_t ad = sb + (nx % NS) * SSLOT + aoff, pa = sb + pb * 4 * PART + poff;
    wg_wait<0>();
#pragma unroll
    for (int e = 0; e < 8; e++) reg_fence(acc[e]);
#pragma unroll
    for (int m = 0; m < 16; m++) reg_fence(fa[m]);
    if (lane == 0) mbar_arrive(bar_addr(sb, B_EMPTY + i % NS));
#pragma unroll
    for (int e = 0; e < 8; e++) {
      load_a(e, ad);
      uint32_t u[4];
#pragma unroll
      for (int j = 0; j < 4; j++) {
        const int T = 4 * e + j, U = T - 1;
        float lo = acc[e][4 * j], hi = acc[e][4 * j + 1];
        if (T > 0) { lo += acc[U >> 2][4 * (U & 3) + 2]; hi += acc[U >> 2][4 * (U & 3) + 3]; }
        u[j] = pack_bf16(lo, hi);
      }
      asm volatile("stmatrix.sync.aligned.m8n8.x4.trans.shared.b16 [%0], {%1, %2, %3, %4};" :: "r"(pa + e * 512), "r"(u[0]), "r"(u[1]), "r"(u[2]), "r"(u[3]) : "memory");
    }
    dd = lds4(sb + OFF_D + nx * 4);
#pragma unroll
    for (int m = 8; m < 12; m++) load_a(m, ad);
    fence_async_smem();
    warp_arrive(bar_addr(sb, B_PFULL + pb), lane);
#pragma unroll
    for (int m = 12; m < 16; m++) load_a(m, ad);
    pb += 2;
    if (pb >= NP) { pb -= NP; pphase ^= 1; }
  }
  if (threadIdx.x == 128) { PT(9); GT(13); }
}

__device__ __forceinline__ void init(const Params& p, uint32_t sb, int cidx) {
  const uint32_t t = threadIdx.x;
  if (t < NCH) {
    const uint32_t d = (uint32_t)__ldg(reinterpret_cast<const unsigned short*>(p.a_D + channel(cidx, t))) * 0x10001u;
    asm volatile("st.shared.u32 [%0], %1;" :: "r"(sb + OFF_D + t * 4), "r"(d) : "memory");
  }
#pragma unroll 1
  for (uint32_t u = t; u < NS * 32; u += 128) {
    const uint32_t r = u & 31;
    if (r < 28) sts16(sb + (u >> 5) * SSLOT + (r < 24 ? r * 16 : HE - 64 + (r - 24) * 16), 0, 0, 0, 0);
    if (u < NP * 32) sts16(sb + OFF_P + (u >> 3) * PART + (u & 7) * 16, 0, 0, 0, 0);
  }
  if (t == 0) {
    for (int i = 0; i < NS; i++) { mbar_init(bar_addr(sb, B_FULL + i), 1); mbar_init(bar_addr(sb, B_EMPTY + i), 4); }
    for (int i = 0; i < NP; i++) { mbar_init(bar_addr(sb, B_PFULL + i), 4); mbar_init(bar_addr(sb, B_PEMPTY + i), 1); }
  }
  fence_async_smem();
}

__device__ __forceinline__ void side_prepare(const Params& p, int cta, int rd) {
  const int lane = threadIdx.x & 31, t0 = 16 * cta + 8 * (lane & 1);
#pragma unroll 1
  for (int ch = 64 * rd + (lane & ~1); ch < 64 * rd + 64; ch += 32) {
    const uint4 sv = __ldg(at<const uint4>(p.a_shift, ch * 8));
    const uint32_t* kp = at<const uint32_t>(p.a_k, (t0 * DA + ch) * 2);
    const uint32_t* vp = at<const uint32_t>(p.a_v, (t0 * DA + ch) * 2);
    uint32_t k0 = 0, k1 = 0, k2 = 0, kk[8], x[8];
    if (t0 > 0) { k0 = __ldg(kp - 3 * (DA / 2)); k1 = __ldg(kp - 2 * (DA / 2)); k2 = __ldg(kp - DA / 2); }
#pragma unroll
    for (int i = 0; i < 8; i++) { kk[i] = __ldg(kp + i * (DA / 2)); x[i] = __ldg(vp + i * (DA / 2)); }
    const uint32_t sh0 = __byte_perm(sv.x, sv.z, 0x5410), sh1 = __byte_perm(sv.x, sv.z, 0x7632);
    const uint32_t sh2 = __byte_perm(sv.y, sv.w, 0x5410), sh3 = __byte_perm(sv.y, sv.w, 0x7632);
#pragma unroll
    for (int i = 0; i < 8; i++) {
      uint32_t ks = bmul(k0, sh3);
      ks = badd(ks, bmul(k1, sh2)); ks = badd(ks, bmul(k2, sh1)); ks = badd(ks, bmul(kk[i], sh0));
      x[i] = bmul(ks, x[i]);
      k0 = k1; k1 = k2; k2 = kk[i];
    }
    uint4* dst = at<uint4>(g_xs, ch * 4096 + t0 * 2);
    dst[0]   = make_uint4(__byte_perm(x[7], x[6], 0x5410), __byte_perm(x[5], x[4], 0x5410), __byte_perm(x[3], x[2], 0x5410), __byte_perm(x[1], x[0], 0x5410));
    dst[256] = make_uint4(__byte_perm(x[7], x[6], 0x7632), __byte_perm(x[5], x[4], 0x7632), __byte_perm(x[3], x[2], 0x7632), __byte_perm(x[1], x[0], 0x7632));
  }
  {
    const int hc = 64 * rd + (cta >> 1), r0 = (cta & 1) * 128 + lane;
    const uint4* src = at<const uint4>(p.a_ssmk, hc * 4096 + r0 * 16);
    uint4* dst = at<uint4>(g_ho, hc * HO_STRIDE + r0 * 16);
    uint4 w[4];
    uint32_t nx[4];
#pragma unroll
    for (int i = 0; i < 4; i++) { w[i] = __ldg(src + 32 * i); nx[i] = r0 + 32 * i < 255 ? __ldg(reinterpret_cast<const uint32_t*>(src + 32 * i + 1)) : 0u; }
#pragma unroll
    for (int i = 0; i < 4; i++)
      dst[32 * i + 2] = make_uint4(__byte_perm(w[i].x, w[i].y, 0x5432), __byte_perm(w[i].y, w[i].z, 0x5432), __byte_perm(w[i].z, w[i].w, 0x5432), __byte_perm(w[i].w, nx[i], 0x5432));
    const uint32_t h0 = __shfl_sync(0xffffffffu, w[0].x, 0);
    if (r0 < 2) dst[0] = make_uint4(0, 0, 0, r0 ? h0 << 16 : 0u);
  }
  __syncwarp();
  if (lane == 0) flag_signal(flag_at(g_flags.x_ready, rd));
}
__device__ __forceinline__ void side_finish(const Params& p, int cta, int rd) {
  const int lane = threadIdx.x & 31, t0 = 16 * cta + 8 * (lane & 1);
#pragma unroll 1
  for (int ch = 64 * rd + (lane & ~1); ch < 64 * rd + 64; ch += 32) {
    const uint4* src = at<const uint4>(g_xs, ch * 4096 + t0 * 2);
    const uint32_t* qp = at<const uint32_t>(p.a_q, (t0 * DA + ch) * 2);
    uint32_t* op = at<uint32_t>(p.out, (t0 * OUTW + ch) * 2);
    const uint4 z0 = __ldcg(src), z1 = __ldcg(src + 256);
    uint32_t q[8];
#pragma unroll
    for (int i = 0; i < 8; i++) q[i] = __ldg(qp + i * (DA / 2));
    const uint32_t a[4] = {z0.w, z0.z, z0.y, z0.x}, b[4] = {z1.w, z1.z, z1.y, z1.x};
#pragma unroll
    for (int i = 0; i < 4; i++) {
      op[(2 * i) * (OUTW / 2)]     = bmul(q[2 * i], __byte_perm(a[i], b[i], 0x7632));
      op[(2 * i + 1) * (OUTW / 2)] = bmul(q[2 * i + 1], __byte_perm(a[i], b[i], 0x5410));
    }
  }
}
__device__ __forceinline__ void clear_rows(const Params& p, int qt, int part) {
  const int lane = threadIdx.x & 31;
  if (lane < 28) {
    uint4* z = at<uint4>(p.out, ((qt * 128 + part * 16) * OUTW + DA) * 2 + lane * 16);
#pragma unroll
    for (int i = 0; i < 32; i++) z[(i >> 1) * (OUTW / 8) + (i & 1) * 28] = make_uint4(0, 0, 0, 0);
  }
  __syncwarp();
  if (lane == 0) flag_signal(flag_at(g_flags.zero_ready, qt));
}
__device__ __forceinline__ void side_work(const Params& p, int cta, unsigned epoch) {
  const bool poll = (threadIdx.x & 31) == 0;
  if (START_NS) __nanosleep(START_NS);
#pragma unroll 1
  for (int rd = 0; rd < 7; rd++) {
    if (rd > 0 && poll) flag_wait<POLL_NS>(flag_at(g_flags.x_wanted, rd), 1, epoch);
    __syncwarp();
    side_prepare(p, cta, rd);
  }
  clear_rows(p, cta & 15, cta >> 4);
#pragma unroll 1
  for (int rd = 0; rd < 7; rd++) {
    if (poll) flag_wait<POLL_NS>(flag_at(g_flags.z_ready, rd), 3 * NCONV, epoch);
    __syncwarp();
    side_finish(p, cta, rd);
  }
}
}

__global__ void __cluster_dims__(2, 1, 1) __launch_bounds__(NTHREADS, 1)
concat_heads__ssm_conv_h3__compressed_kv_cla__prompt_kernel(const __grid_constant__ Params p) {
  extern __shared__ uint8_t smem_raw[];
  const uint32_t sb = (smem_u32(smem_raw) + 1023) & ~1023u;
  if (threadIdx.x == NTHREADS - 64) { prefetch_map(&p.wuk); prefetch_map(&p.ckv); }
  const int cta = blockIdx.x;
  const bool attn = cta < NMAIN;
  int g, t;
  {
    const int c = cta >> 1, u2 = ((c - 36) * 37) >> 8, i = c - 36 - 7 * u2;
    g = c < 4 ? 1 : c < 36 ? (c - 4) & 7 : i == 0 ? 0 : 1 + i;
    t = 2 * (c < 4 ? c : c < 36 ? 7 - ((c - 4) >> 3) : u2) + (cta & 1);
  }
  if (attn && threadIdx.x == NTHREADS - 32) {
    const uint32_t full = bar_addr(sb, B_FULL);
    mbar_init(full, 1);
    asm volatile("fence.mbarrier_init.release.cluster;" ::: "memory");
    mbar_expect_tx(full, 49152);
    load_w(p, g, t, 0, sb, full);
    load_a(p, g, t, 0, sb + QREG, full);
  }
  __syncwarp();
  const int lane = threadIdx.x & 31;
  const int warp = __shfl_sync(0xffffffffu, threadIdx.x >> 5, 0);
  const int wg = warp >> 2;
  if (wg != 0) {
    if (attn) {
      cluster_arrive();
      if (wg == 2) named_arrive(PP_BAR, 256);
    }
    asm volatile("setmaxnreg.inc.sync.aligned.u32 232;");
    if (!attn) {
      if (p.out != nullptr) { named_sync(0, NTHREADS); ssm::mma_warpgroup(sb, wg - 1); }
      return;
    }
    if (p.out != nullptr) consumer_main(p, sb, g, t, wg - 1, warp & 3);
  } else {
    asm volatile("setmaxnreg.dec.sync.aligned.u32 40;");
    if (!attn) {
      ssm::init(p, sb, cta - NMAIN);
      named_sync(0, NTHREADS);
      if (lane == 0) {
        if (warp == 0) { ssm::producer(p, sb, cta - NMAIN, load_epoch()); cta_done(32); }
        else ssm::reducer(sb, cta - NMAIN, warp - 1);
        if (warp == 1) GT(14);
      }
      return;
    }
    if (warp == 0) {
      if (lane == 0) {
        for (int i = 1; i < NSLOT; i++) mbar_init(bar_addr(sb, B_FULL + i), 1);
        asm volatile("fence.mbarrier_init.release.cluster;" ::: "memory");
      }
      __syncwarp();
      cluster_arrive();
      if (lane == 0) {
#pragma unroll 1
        for (int k = 1; k < EARLY_LD; k++) {
          const uint32_t full = bar_addr(sb, B_FULL + k);
          mbar_expect_tx(full, 49152);
          load_w(p, g, t, k & 15, sb + k * SLOT, full);
          load_a(p, g, t, k & 15, sb + QREG + k * 16384, full);
          __nanosleep(200);
        }
      }
      __syncwarp();
      cluster_wait();
      if (lane == 0) producer_main(p, sb, g, t);
      return;
    }
    if (lane == 0) {
      if (warp == 1) {
        for (int i = 0; i < NSLOT; i++) mbar_init(bar_addr(sb, B_EMPTY + i), 16);
        for (int i = 0; i < 2; i++) {
          mbar_init(bar_addr(sb, B_QFREE + i), 4); mbar_init(bar_addr(sb, B_QFULL + i), 1);
          mbar_init(bar_addr(sb, B_CTXOK + i), 1);
        }
      } else if (warp == 2) {
        for (int i = 0; i < 8; i++) { mbar_init(bar_addr(sb, B_S2_FULL + i), 4); mbar_init(bar_addr(sb, B_S2_EMPTY + i), 1); }
      } else {
        mbar_init(bar_addr(sb, B_DONE), 2);
        mbar_init(bar_addr(sb, B_KVOK), 1); mbar_init(bar_addr(sb, B_PF), 1);
        for (int i = 0; i < 2; i++) {
          mbar_init(bar_addr(sb, B_ST_KV + i), 4); mbar_init(bar_addr(sb, B_ST_Q + i), 4); mbar_init(bar_addr(sb, B_ST_CTX + i), 4);
        }
      }
      asm volatile("fence.mbarrier_init.release.cluster;" ::: "memory");
    }
    __syncwarp();
    cluster_arrive();
    cluster_wait();
    if (warp < 3) {
      if (warp == 2) {
        mbar_wait(bar_addr(sb, B_PF), 0);
        const uint8_t* a = at<const uint8_t>(p.b_x, (g * 16 + t) * 16 * DM * 2 + lane * 128);
#pragma unroll 1
        for (int i = 0; i < 4; i++) {
          if (i < 3 || lane < 16) asm volatile("prefetch.global.L2 [%0];" :: "l"(a + i * 4096));
          __nanosleep(1000);
        }
      }
      if (lane == 0) {
        if (warp == 1) { __nanosleep(2000); prefetch_map(&p.wuv); prefetch_map(&p.x); prefetch_map(&p.wq); prefetch_map(&p.o); prefetch_map(&p.wo); }
        helper_main(p, sb, g, t, warp - 1);
      }
    } else {
      ssm::side_work(p, g * 16 + t, load_epoch());
      if (lane == 0) { GT(57); mbar_wait(bar_addr(sb, B_DONE), 0); cta_done(1); }
    }
  }
}

typedef CUresult (*EncodeTiledFn)(CUtensorMap*, CUtensorMapDataType, cuuint32_t, void*, const cuuint64_t*, const cuuint64_t*,
                                  const cuuint32_t*, const cuuint32_t*, CUtensorMapInterleave, CUtensorMapSwizzle,
                                  CUtensorMapL2promotion, CUtensorMapFloatOOBfill);

void make_map(EncodeTiledFn enc, CUtensorMap* m, const void* ptr, int rank, const uint64_t* dims, const uint64_t* strides, const uint32_t* box) {
  cuuint64_t d[5], s[4]; cuuint32_t b[5], e[5] = {1, 1, 1, 1, 1};
  for (int i = 0; i < rank; i++) { d[i] = dims[i]; b[i] = box[i]; if (i) s[i - 1] = strides[i - 1]; }
  enc(m, CU_TENSOR_MAP_DATA_TYPE_BFLOAT16, rank, const_cast<void*>(ptr), d, s, b, e, CU_TENSOR_MAP_INTERLEAVE_NONE,
      CU_TENSOR_MAP_SWIZZLE_128B, CU_TENSOR_MAP_L2_PROMOTION_L2_256B, CU_TENSOR_MAP_FLOAT_OOB_FILL_NONE);
}
void map2(EncodeTiledFn enc, CUtensorMap* m, const void* ptr, uint64_t cols, uint64_t rows, uint32_t bc, uint32_t br) {
  const uint64_t dims[2] = {cols, rows}, st[1] = {cols * 2}; const uint32_t box[2] = {bc, br};
  make_map(enc, m, ptr, 2, dims, st, box);
}
void map3(EncodeTiledFn enc, CUtensorMap* m, const void* ptr, uint64_t rows, uint32_t nblk) {
  const uint64_t dims[3] = {64, rows, 64}, st[2] = {8192, 128}; const uint32_t box[3] = {64, 64, nblk};
  make_map(enc, m, ptr, 3, dims, st, box);
}

}

extern "C" void kernel_launch(void* const* d_in, const int* in_sizes, int n_in, void* d_out, int out_size) {
  (void)in_sizes; (void)n_in; (void)out_size;
  static EncodeTiledFn enc = nullptr;
  if (!enc) {
    void* fn = nullptr; cudaDriverEntryPointQueryResult qr;
    cudaGetDriverEntryPoint("cuTensorMapEncodeTiled", &fn, cudaEnableDefault, &qr);
    enc = (EncodeTiledFn)fn;
    cudaFuncSetAttribute(concat_heads__ssm_conv_h3__compressed_kv_cla__prompt_kernel, cudaFuncAttributeMaxDynamicSharedMemorySize, SMEM_BYTES);
  }
  Params p;
  p.a_q = (const bf16*)d_in[0]; p.a_k = (const bf16*)d_in[1]; p.a_v = (const bf16*)d_in[2];
  p.a_shift = (const bf16*)d_in[3]; p.a_ssmk = (const bf16*)d_in[4]; p.a_D = (const bf16*)d_in[5];
  p.out = (bf16*)d_out;
  p.b_x = (const bf16*)d_in[6];
  map2(enc, &p.x, d_in[6], DM, SEQ, 64, 128);
  map2(enc, &p.ckv, d_in[7], DC, SEQ, 64, 128);
  map3(enc, &p.wq, d_in[8], DM, 4);
  map3(enc, &p.wuk, d_in[9], DC, 4);
  map3(enc, &p.wuv, d_in[10], DC, 4);
  {
    const uint64_t dims[5] = {DM, 2, 4, 4, NH * HD / 32}, st[4] = {DM * 2, 8 * DM * 2, 2 * DM * 2, 32 * DM * 2}; const uint32_t box[5] = {64, 2, 4, 4, 4};
    make_map(enc, &p.wo, d_in[11], 5, dims, st, box);
  }
  map2(enc, &p.o, d_out, OUTW, SEQ, 64, 64);
  concat_heads__ssm_conv_h3__compressed_kv_cla__prompt_kernel<<<NCTA, NTHREADS, SMEM_BYTES>>>(p);
}
```
